```python
import torch

def _softmax(x, axis=-1):
    return torch.softmax(x, dim=axis)

def _gelu(x):
    return torch.nn.functional.gelu(x, approximate='tanh')

def _silu(x):
    return torch.nn.functional.silu(x)

def _sigmoid(x):
    return torch.sigmoid(x)

def _layernorm(x, axis=-1, eps=1e-05):
    m = x.mean(dim=axis, keepdim=True)
    v = x.var(dim=axis, keepdim=True, unbiased=False)
    return (x - m) / torch.sqrt(v + eps)

def _scatter_add(tgt, idx, src, axis=0):
    return tgt.clone().index_add_(axis, idx, src)

def _segment_sum(src, seg, n):
    out = torch.zeros((n,) + src.shape[1:], dtype=src.dtype)
    return out.index_add_(0, seg, src)

def _pad(x, pw):
    flat = tuple((v for pair in reversed(pw) for v in pair))
    return torch.nn.functional.pad(x, flat)
kernel_name = 'standalone__tensor_product_equiv_equiformer__graph'

def setup_inputs():

    _w = lambda a: (lambda t: t.to(torch.bfloat16) if t.is_floating_point() else t)(torch.as_tensor(a))
    N, deg, C, De = (10000, 32, 128, max(16, 1))
    E = N * deg
    src = (lambda lo, hi, *s: torch.randint(lo, hi, s))(0, N, E).to(torch.int64)
    dst = (lambda lo, hi, *s: torch.randint(lo, hi, s))(0, N, E).to(torch.int64)
    rvec = (lambda *s: torch.randn(*s, dtype=torch.bfloat16) * 0.05)(E, 3).to(float)
    rn = (torch.linalg.norm(rvec, dim=-1, keepdim=True) + 1e-06).to(float)
    rhat = (rvec / rn).to(float)
    eps = torch.zeros((3, 3, 3), dtype=float)
    eps[0, 1, 2] = eps[1, 2, 0] = eps[2, 0, 1] = 1.0
    eps[0, 2, 1] = eps[2, 1, 0] = eps[1, 0, 2] = -1.0
    return {'x': _w((lambda *s: torch.randn(*s, dtype=torch.bfloat16) * 0.2)(N, 4 * C).to(float)), 'rhat': _w(rhat), 'e_attr': _w((lambda *s: torch.randn(*s, dtype=torch.bfloat16) * 0.2)(E, De).to(float)), 'src': _w(src), 'dst': _w(dst), 'w_rad': _w((lambda *s: torch.randn(*s, dtype=torch.bfloat16) * 0.2)(De, 5 * C).to(float)), 'w_si0': _w((lambda *s: torch.randn(*s, dtype=torch.bfloat16) * 0.2)(2 * C, C).to(float)), 'w_si1': _w((lambda *s: torch.randn(*s, dtype=torch.bfloat16) * 0.05)(3 * C, C).to(float)), 'cg_eps': _w(eps)}

def reference(x, rhat, e_attr, src, dst, w_rad, w_si0, w_si1, cg_eps):
    N = x.shape[0]
    C = w_si0.shape[1]
    E = rhat.shape[0]
    x0 = x[:, :C].clone()
    x1 = x[:, C:].reshape(N, 3, C)
    R = (e_attr @ w_rad).reshape(E, 5, C)
    f0 = x0[src]
    f1 = x1[src]
    Y1 = rhat
    p00_0 = f0 * R[:, 0, :]
    p11_0 = torch.einsum('ejc,ej->ec', f1, Y1) * R[:, 1, :]
    p01_1 = torch.einsum('ec,ej->ejc', f0, Y1) * R[:, 2, :][:, None, :]
    p10_1 = f1 * R[:, 3, :][:, None, :]
    p11_1 = torch.einsum('ijk,ekc,ej->eic', cg_eps, f1, Y1) * R[:, 4, :][:, None, :]
    m0 = torch.concatenate([p00_0, p11_0], axis=-1) @ w_si0
    m1 = torch.einsum('ejp,pc->ejc', torch.concatenate([p01_1, p10_1, p11_1], axis=-1), w_si1)
    agg0 = _segment_sum(m0, dst, N)
    agg1 = _segment_sum(m1.reshape(E, 3 * C), dst, N).reshape(N, 3, C)
    gate = _sigmoid(agg0)
    out1 = agg1 * gate[:, None, :]
    return torch.concatenate([agg0, out1.reshape(N, 3 * C)], axis=-1)
```

```cpp
#include <cuda_runtime.h>
#include <cuda_bf16.h>
#include <cuda.h>
#include <stdint.h>

namespace {

constexpr int NN = 10000;
constexpr int NE = 320000;
constexpr int G = 132;
constexpr int NT = 384;
constexpr int CH = 2432;
constexpr int NLOC = (NN + G - 1) / G;
constexpr int NPOOL = 8;
constexpr int NPRIV = NLOC - NPOOL;
constexpr int CAP = 2816;
constexpr int KMAX = (CAP + NT - 1) / NT;
constexpr int SEGW = 11;
constexpr int HSTR = 160;

#define NSLOT 5
#define PSBO 256
#define PREFETCH 1

constexpr int SLOT = 17408;
constexpr int S_A = 16384, S_C = S_A + 512, S_FULL = S_C + 448, S_EMPTY = S_FULL + 8, S_META = S_FULL + 16;

constexpr int PPAD = (PSBO == 256) ? 16 : 0;
constexpr int PB1 = 5 * PSBO + 256 + PPAD, PB0 = PSBO + 256 + PPAD;
constexpr int P_1P0 = 0, P_1P1 = PB1, P_0P1 = 2 * PB1, P_0P0 = P_0P1 + PB0, P_1P2 = P_0P0 + PB0;
constexpr int PW = P_1P2 + PB1 - PPAD;

constexpr int cmax(int a, int b) { return a > b ? a : b; }
constexpr int O_W1 = 0;
constexpr int O_RING = 98304;
constexpr int O_W0S = O_RING, O_WRS = O_RING + 65536;
constexpr int O_P = O_RING + cmax(NSLOT * SLOT, 86016);
constexpr int O_TRASH = O_P + 8 * PW;
constexpr int O_TMP = O_P + CAP * 16;
constexpr int O_BCNT = O_TMP, O_BOFF = O_BCNT + 544, O_NCNT = O_BOFF + 544;
constexpr int O_MISC = cmax(O_TRASH + 512, O_NCNT + 320);
constexpr int O_WBA = O_MISC, O_WBB = O_MISC + 8, O_TOT = O_MISC + 16, O_SUM = O_MISC + 20, O_END = O_MISC + 24;
constexpr int O_NOFF = O_MISC + 32;
constexpr int SMEM_BYTES = O_NOFF + 320;
static_assert(SMEM_BYTES <= 232448, "smem");
static_assert(G * CH >= NE && NE % 8 == 0 && CH <= CAP, "chunks");
static_assert(SEGW * (NT / 32) >= G, "segments");
static_assert(NLOC <= 78, "scan width");

__device__ uint4 g_outbox[G * CH];
__device__ uint4 g_sorted[NE + G * 16];
__device__ uint32_t g_hdr[G * HSTR];
__device__ int2 g_info[G * NPOOL];
__device__ unsigned g_pub, g_ticket, g_done;
#define TS(i)
#define TSW(i)

constexpr int SPIN_LIMIT = 1 << 24;

__device__ __forceinline__ void mbar_init(uint32_t a, int c) { asm volatile("mbarrier.init.shared::cta.b64 [%0], %1;" ::"r"(a), "r"(c) : "memory"); }
__device__ __forceinline__ void mbar_expect(uint32_t a, int b) { asm volatile("mbarrier.arrive.expect_tx.shared::cta.b64 _, [%0], %1;" ::"r"(a), "r"(b) : "memory"); }
__device__ __forceinline__ void mbar_arrive(uint32_t a) { asm volatile("mbarrier.arrive.shared::cta.b64 _, [%0];" ::"r"(a) : "memory"); }
__device__ __forceinline__ void mbar_wait(uint32_t a, uint32_t ph) {
    uint32_t ok;
    int it = 0;
    do {
        asm volatile("{.reg .pred p; mbarrier.try_wait.parity.shared::cta.b64 p, [%1], %2; selp.u32 %0,1,0,p;}" : "=r"(ok) : "r"(a), "r"(ph) : "memory");
        if (++it > SPIN_LIMIT) __trap();
    } while (!ok);
}
__device__ __forceinline__ void tma2d(uint32_t dst, const CUtensorMap* m, int c0, int c1, uint32_t bar) {
    asm volatile("cp.async.bulk.tensor.2d.shared::cluster.global.mbarrier::complete_tx::bytes [%0], [%1, {%3, %4}], [%2];"
                 ::"r"(dst), "l"(m), "r"(bar), "r"(c0), "r"(c1) : "memory");
}
__device__ __forceinline__ void cpa16(uint32_t d, const void* g) { asm volatile("cp.async.cg.shared.global [%0], [%1], 16;" ::"r"(d), "l"(g) : "memory"); }
__device__ __forceinline__ void cpa16z(uint32_t d, const void* g, int sz) { asm volatile("cp.async.cg.shared.global [%0], [%1], 16, %2;" ::"r"(d), "l"(g), "r"(sz) : "memory"); }
__device__ __forceinline__ void ldsm4(uint32_t* r, uint32_t a) { asm volatile("ldmatrix.sync.aligned.m8n8.x4.shared.b16 {%0,%1,%2,%3}, [%4];" : "=r"(r[0]), "=r"(r[1]), "=r"(r[2]), "=r"(r[3]) : "r"(a) : "memory"); }
__device__ __forceinline__ void ldsm2(uint32_t* r, uint32_t a) { asm volatile("ldmatrix.sync.aligned.m8n8.x2.shared.b16 {%0,%1}, [%2];" : "=r"(r[0]), "=r"(r[1]) : "r"(a) : "memory"); }
__device__ __forceinline__ void ldsm4t(uint32_t* r, uint32_t a) { asm volatile("ldmatrix.sync.aligned.m8n8.x4.trans.shared.b16 {%0,%1,%2,%3}, [%4];" : "=r"(r[0]), "=r"(r[1]), "=r"(r[2]), "=r"(r[3]) : "r"(a) : "memory"); }
__device__ __forceinline__ void stsm4t(uint32_t a, uint32_t r0, uint32_t r1, uint32_t r2, uint32_t r3) { asm volatile("stmatrix.sync.aligned.m8n8.x4.trans.shared.b16 [%0], {%1,%2,%3,%4};" ::"r"(a), "r"(r0), "r"(r1), "r"(r2), "r"(r3) : "memory"); }
__device__ __forceinline__ void mma16(float* d, uint32_t a0, uint32_t a1, uint32_t a2, uint32_t a3, uint32_t b0, uint32_t b1) {
    asm("mma.sync.aligned.m16n8k16.row.col.f32.bf16.bf16.f32 {%0,%1,%2,%3}, {%4,%5,%6,%7}, {%8,%9}, {%0,%1,%2,%3};"
        : "+f"(d[0]), "+f"(d[1]), "+f"(d[2]), "+f"(d[3]) : "r"(a0), "r"(a1), "r"(a2), "r"(a3), "r"(b0), "r"(b1));
}
__device__ __forceinline__ void mma16z(float* d, const uint32_t* a, uint32_t b0, uint32_t b1) {
    asm("mma.sync.aligned.m16n8k16.row.col.f32.bf16.bf16.f32 {%0,%1,%2,%3}, {%4,%5,%6,%7}, {%8,%9}, {%10,%10,%10,%10};"
        : "=f"(d[0]), "=f"(d[1]), "=f"(d[2]), "=f"(d[3]) : "r"(a[0]), "r"(a[1]), "r"(a[2]), "r"(a[3]), "r"(b0), "r"(b1), "f"(0.f));
}
__device__ __forceinline__ void mma8(float* d, uint32_t a0, uint32_t a1, uint32_t b0) {
    asm("mma.sync.aligned.m16n8k8.row.col.f32.bf16.bf16.f32 {%0,%1,%2,%3}, {%4,%5}, {%6}, {%0,%1,%2,%3};"
        : "+f"(d[0]), "+f"(d[1]), "+f"(d[2]), "+f"(d[3]) : "r"(a0), "r"(a1), "r"(b0));
}
__device__ __forceinline__ uint32_t pack(float lo, float hi) { uint32_t r; asm("cvt.rn.bf16x2.f32 %0, %1, %2;" : "=r"(r) : "f"(hi), "f"(lo)); return r; }
__device__ __forceinline__ uint32_t hmul(uint32_t a, uint32_t b) { uint32_t r; asm("mul.rn.bf16x2 %0, %1, %2;" : "=r"(r) : "r"(a), "r"(b)); return r; }
__device__ __forceinline__ uint32_t hfma(uint32_t a, uint32_t b, uint32_t c) { uint32_t r; asm("fma.rn.bf16x2 %0, %1, %2, %3;" : "=r"(r) : "r"(a), "r"(b), "r"(c)); return r; }
__device__ __forceinline__ uint4 lds128(uint32_t a) { uint4 v; asm volatile("ld.shared.v4.u32 {%0,%1,%2,%3}, [%4];" : "=r"(v.x), "=r"(v.y), "=r"(v.z), "=r"(v.w) : "r"(a) : "memory"); return v; }
__device__ __forceinline__ void sts128(uint32_t a, uint4 v) { asm volatile("st.shared.v4.u32 [%0], {%1,%2,%3,%4};" ::"r"(a), "r"(v.x), "r"(v.y), "r"(v.z), "r"(v.w) : "memory"); }
__device__ __forceinline__ int lds32(uint32_t a) { int v; asm volatile("ld.shared.u32 %0, [%1];" : "=r"(v) : "r"(a) : "memory"); return v; }
__device__ __forceinline__ void sts32(uint32_t a, int v) { asm volatile("st.shared.u32 [%0], %1;" ::"r"(a), "r"(v) : "memory"); }
__device__ __forceinline__ void sts16(uint32_t a, uint32_t v) { asm volatile("st.shared.u16 [%0], %1;" ::"r"(a), "h"((unsigned short)v) : "memory"); }
__device__ __forceinline__ int atoms_add(uint32_t a, int v) { int r; asm volatile("atom.shared.add.u32 %0, [%1], %2;" : "=r"(r) : "r"(a), "r"(v) : "memory"); return r; }
__device__ __forceinline__ uint32_t ld_acq(const void* p) { uint32_t v; asm volatile("ld.acquire.gpu.global.u32 %0, [%1];" : "=r"(v) : "l"(p) : "memory"); return v; }
__device__ __forceinline__ uint32_t ld_rlx(const void* p) { uint32_t v; asm volatile("ld.relaxed.gpu.global.u32 %0, [%1];" : "=r"(v) : "l"(p) : "memory"); return v; }
__device__ __forceinline__ uint4 ldcg128(const void* p) { uint4 v; asm volatile("ld.global.cg.v4.u32 {%0,%1,%2,%3}, [%4];" : "=r"(v.x), "=r"(v.y), "=r"(v.z), "=r"(v.w) : "l"(p) : "memory"); return v; }
__device__ __forceinline__ void bar_sync(int id, int n) { asm volatile("bar.sync %0, %1;" ::"r"(id), "r"(n) : "memory"); }

__device__ __forceinline__ void wg_rs16(float* d, const uint32_t* a, uint64_t db, int sc) {
    asm volatile("{.reg .pred p; setp.ne.b32 p, %13, 0;\n"
                 "wgmma.mma_async.sync.aligned.m64n16k16.f32.bf16.bf16 {%0,%1,%2,%3,%4,%5,%6,%7}, {%8,%9,%10,%11}, %12, p, 1, 1, 0;}"
                 : "+f"(d[0]), "+f"(d[1]), "+f"(d[2]), "+f"(d[3]), "+f"(d[4]), "+f"(d[5]), "+f"(d[6]), "+f"(d[7])
                 : "r"(a[0]), "r"(a[1]), "r"(a[2]), "r"(a[3]), "l"(db), "r"(sc));
}
__device__ __forceinline__ void wg_ss48(float* d, uint64_t da, uint64_t db, int sc) {
    asm volatile("{.reg .pred p; setp.ne.b32 p, %26, 0;\n"
                 "wgmma.mma_async.sync.aligned.m64n48k16.f32.bf16.bf16 {%0,%1,%2,%3,%4,%5,%6,%7,%8,%9,%10,%11,%12,%13,%14,%15,%16,%17,%18,%19,%20,%21,%22,%23}, %24, %25, p, 1, 1, 1, 0;}"
                 : "+f"(d[0]), "+f"(d[1]), "+f"(d[2]), "+f"(d[3]), "+f"(d[4]), "+f"(d[5]), "+f"(d[6]), "+f"(d[7]),
                   "+f"(d[8]), "+f"(d[9]), "+f"(d[10]), "+f"(d[11]), "+f"(d[12]), "+f"(d[13]), "+f"(d[14]), "+f"(d[15]),
                   "+f"(d[16]), "+f"(d[17]), "+f"(d[18]), "+f"(d[19]), "+f"(d[20]), "+f"(d[21]), "+f"(d[22]), "+f"(d[23])
                 : "l"(da), "l"(db), "r"(sc));
}

template <int PER>
__device__ __forceinline__ void warp_scan(uint32_t cnt, uint32_t off, int n, int lane) {
    int v[PER], s = 0;
#pragma unroll
    for (int i = 0; i < PER; i++) { int k = lane * PER + i; v[i] = (k < n) ? lds32(cnt + 4 * k) : 0; s += v[i]; }
    int inc = s;
#pragma unroll
    for (int o = 1; o < 32; o <<= 1) { int u = __shfl_up_sync(0xffffffffu, inc, o); if (lane >= o) inc += u; }
    int e = inc - s;
#pragma unroll
    for (int i = 0; i < PER; i++) { int k = lane * PER + i; if (k <= n) sts32(off + 4 * k, e); e += v[i]; }
    __syncwarp();
}

struct Acc {
    uint32_t p00[4], p110[4], p10[3][4];
    float t01[4], t11[4];
};

template <int S>
__device__ __forceinline__ void flush(Acc& A, uint32_t addr, int g, int q) {
    const int gs = g ^ (S * 4);
    const bool mine = (q >> 1) == S;
    const uint32_t one = 0x3F803F80u;
    float x[4];
#pragma unroll
    for (int i = 0; i < 4; i++) { x[i] = mine ? A.t01[i] : 0.f; A.t01[i] = mine ? 0.f : A.t01[i]; }
    mma16(x, A.p10[0][2 * S], A.p10[0][2 * S + 1], A.p10[1][2 * S], A.p10[1][2 * S + 1], gs == 4 ? one : 0u, gs == 5 ? one : 0u);
    mma8(A.t11, A.p110[2 * S], A.p110[2 * S + 1], gs == 3 ? one : 0u);
    mma16(x, A.p10[2][2 * S], A.p10[2][2 * S + 1], A.p00[2 * S], A.p00[2 * S + 1], gs == 6 ? one : 0u, gs == 7 ? one : 0u);
    stsm4t(addr, pack(x[0], x[1]), pack(x[2], x[3]), pack(A.t11[0], A.t11[1]), pack(A.t11[2], A.t11[3]));
#pragma unroll
    for (int i = 0; i < 4; i++) A.t11[i] = mine ? 0.f : A.t11[i];
#pragma unroll
    for (int i = 2 * S; i < 2 * S + 2; i++) { A.p00[i] = 0; A.p110[i] = 0; A.p10[0][i] = 0; A.p10[1][i] = 0; A.p10[2][i] = 0; }
}

struct Blk { int node, n, last; uint4 e; };

__global__ void __launch_bounds__(NT, 1)
tp_kernel(const __grid_constant__ CUtensorMap m_wr, const __grid_constant__ CUtensorMap m_w0, const __grid_constant__ CUtensorMap m_w1,
          const char* __restrict__ x, const uint4* __restrict__ rhat, const char* __restrict__ ea,
          const int4* __restrict__ src, const int4* __restrict__ dst, const __nv_bfloat16* __restrict__ eps,
          char* __restrict__ out) {
    extern __shared__ __align__(1024) char smem_raw[];
    const uint32_t sm = (uint32_t)__cvta_generic_to_shared(smem_raw);
    const int t = threadIdx.x, w = t >> 5, lane = t & 31, b = blockIdx.x;

    const int ne = min(CH, NE - b * CH);
    const bool act = t * 8 < ne;
    const int e0 = b * CH + t * 8;
    int d[8], s[8];
    uint32_t y[12];
    if (act) {
        *(int4*)&d[0] = __ldg(dst + e0 / 4); *(int4*)&d[4] = __ldg(dst + e0 / 4 + 1);
        *(int4*)&s[0] = __ldg(src + e0 / 4); *(int4*)&s[4] = __ldg(src + e0 / 4 + 1);
#pragma unroll
        for (int i = 0; i < 3; i++) *(uint4*)&y[4 * i] = __ldg(rhat + (e0 / 8) * 3 + i);
    }
    float E[9];
    if (w >= 8) {
#pragma unroll
        for (int i = 0; i < 3; i++)
#pragma unroll
            for (int j = 0; j < 3; j++)
                E[i * 3 + j] = (lane < 8) ? (i == j ? 1.f : 0.f) : __bfloat162float(eps[i * 9 + j * 3 + (lane >> 3) - 1]);
    }
    const int seg = w * SEGW + lane;
    const bool hseg = lane < SEGW && seg < G;
    uint32_t* hp = &g_hdr[b * HSTR + seg];
    uint32_t hv = 0;
    if (hseg) hv = ld_rlx(hp);
    if (t == NT - 1) {
        mbar_init(sm + O_WBA, 1); mbar_init(sm + O_WBB, 1);
        asm volatile("fence.proxy.async.shared::cta;" ::: "memory");
        mbar_expect(sm + O_WBA, 86016); mbar_expect(sm + O_WBB, 98304);
        tma2d(sm + O_W0S, &m_w0, 0, 0, sm + O_WBA);
        tma2d(sm + O_W0S + 32768, &m_w0, 64, 0, sm + O_WBA);
        for (int j = 0; j < 10; j++) tma2d(sm + O_WRS + j * 2048, &m_wr, 64 * j, 0, sm + O_WBA);
        for (int j = 0; j < 4; j++) tma2d(sm + O_W1 + j * 24576, &m_w1, 64 * (j >> 1), 192 * (j & 1), sm + O_WBB);
    }
    if (t < 136) sts32(sm + O_BCNT + 4 * t, 0);
    if (t < 80) sts32(sm + O_NCNT + 4 * t, 0);
    if (t < 2) { sts32(sm + O_TOT + 4 * t, 0); sts32(sm + O_END + 4 * t, 0x7fffffff); }
    __syncthreads();
    int rk[8];
    if (act) {
#pragma unroll
        for (int i = 0; i < 8; i++) {
            int loc = d[i] / G, own = d[i] - loc * G;
            d[i] = own | (loc << 16);
            rk[i] = atoms_add(sm + O_BCNT + 4 * own, 1);
        }
    }
    TS(0);
    if (t == NT - 1) {
        constexpr int PC = 19392;
        for (int j = 0; j < 4; j++) {
            int o = (b * 4 + j) * PC, n = min(PC, NN * 1024 - o);
            if (b == G - 1 && j == 3) n = NN * 1024 - o;
            asm volatile("cp.async.bulk.prefetch.L2.global [%0], %1;" ::"l"(x + o), "r"(n) : "memory");
            asm volatile("cp.async.bulk.prefetch.L2.global [%0], %1;" ::"l"(ea + o), "r"(n) : "memory");
        }
    }
    __syncthreads();
    warp_scan<5>(sm + O_BCNT, sm + O_BOFF, G, lane);
    if (act) {
#pragma unroll
        for (int i = 0; i < 8; i++) {
            uint32_t lo, hi;
            if (i & 1) { lo = __byte_perm(y[(3 * i) / 2], y[(3 * i) / 2 + 1], 0x5432); hi = y[(3 * i) / 2 + 1] >> 16; }
            else { lo = y[(3 * i) / 2]; hi = y[(3 * i) / 2 + 1] & 0xffffu; }
            int pos = lds32(sm + O_BOFF + 4 * (d[i] & 0xffff)) + rk[i];
            sts128(sm + O_P + pos * 16, make_uint4(s[i], e0 + i, lo, hi | (d[i] & 0xffff0000u)));
        }
    }
    __syncthreads();
#pragma unroll
    for (int k = 0; k < (CH + NT - 1) / NT; k++) {
        int i = t + k * NT;
        if (i < ne) g_outbox[b * CH + i] = lds128(sm + O_P + i * 16);
    }
    __syncthreads();
    TS(1);
    if (t < G) {
        int o0 = lds32(sm + O_BOFF + 4 * t), o1 = lds32(sm + O_BOFF + 4 * t + 4);
        uint32_t hw = 0x80000000u | (o0 << 16) | (o1 - o0);
        asm volatile("st.release.gpu.global.u32 [%0], %1;" ::"l"(&g_hdr[t * HSTR + b]), "r"(hw) : "memory");
    }
    TS(2);

    const int g = lane >> 2, q = lane & 3, mat = lane >> 3, r = lane & 7;
    uint32_t wr[5][4], w0[16][4];
    if (w < 8) {
        mbar_wait(sm + O_WBA, 0);
        const int row = (mat >> 1) * 8 + r;
        const uint32_t sw = (uint32_t)(((2 * (w & 3) + (mat & 1)) ^ r) * 16 + row * 128);
#pragma unroll
        for (int p = 0; p < 5; p++) ldsm4t(wr[p], sm + O_WRS + (2 * p + (w >> 2)) * 2048 + sw);
#pragma unroll
        for (int k = 0; k < 16; k++) ldsm4t(w0[k], sm + O_W0S + (w >> 2) * 32768 + k * 2048 + sw);
    }
    TS(3);

    int hoff = 0, hcnt = 0, hpos = 0;
    if (hseg) {
        int it = 0;
        while (!(hv >> 31)) { hv = ld_rlx(hp); if (++it > SPIN_LIMIT) __trap(); }
        asm volatile("fence.acq_rel.gpu;" ::: "memory");
        *hp = 0;
        hoff = (hv >> 16) & 0x7fff; hcnt = hv & 0xffff;
        hpos = atoms_add(sm + O_TOT, hcnt);
        atoms_add(sm + O_SUM, hoff);
    }
    __syncwarp();
    TS(4);
    for (int j = 0; j < SEGW; j++) {
        int o = __shfl_sync(0xffffffffu, hoff, j), c = __shfl_sync(0xffffffffu, hcnt, j), p = __shfl_sync(0xffffffffu, hpos, j);
        if (p + c <= CAP)
            for (int i = lane; i < c; i += 32) cpa16(sm + O_P + (p + i) * 16, &g_outbox[(w * SEGW + j) * CH + o + i]);
    }
    asm volatile("cp.async.wait_all;" ::: "memory");
    __syncthreads();
    TS(5);
    const int total = lds32(sm + O_TOT);
    const int gbase = ((lds32(sm + O_SUM) + 7) & ~7) + 8 * b;
    if (t < NSLOT * 4) {
        uint32_t sb = sm + O_RING + (t >> 2) * SLOT;
        sts128(sb + S_C + 192 + (t & 1) * 16 + ((t >> 1) & 1) * 224, make_uint4(0, 0, 0, 0));
        if ((t & 3) == 0) { mbar_init(sb + S_FULL, 66); mbar_init(sb + S_EMPTY, 8); }
    }
    if (total <= CAP) {
        uint4 en[KMAX];
        int rn[KMAX];
#pragma unroll
        for (int k = 0; k < KMAX; k++) {
            int i = t + k * NT;
            if (i < total) { en[k] = lds128(sm + O_P + i * 16); rn[k] = atoms_add(sm + O_NCNT + 4 * (en[k].w >> 16), 1); }
        }
        __syncthreads();
        warp_scan<3>(sm + O_NCNT, sm + O_NOFF, NLOC, lane);
#pragma unroll
        for (int k = 0; k < KMAX; k++) {
            int i = t + k * NT;
            if (i < total) sts128(sm + O_P + (lds32(sm + O_NOFF + 4 * (en[k].w >> 16)) + rn[k]) * 16, en[k]);
        }
        __syncthreads();
        const int tot8 = (total + 7) & ~7;
#pragma unroll
        for (int k = 0; k < KMAX; k++) {
            int i = t + k * NT;
            if (i < tot8) g_sorted[gbase + i] = lds128(sm + O_P + i * 16);
        }
    } else {
        for (int j = 0; j < SEGW; j++) {
            int o = __shfl_sync(0xffffffffu, hoff, j), c = __shfl_sync(0xffffffffu, hcnt, j);
            for (int i = lane; i < c; i += 32) {
                uint4 e = ldcg128(&g_outbox[(w * SEGW + j) * CH + o + i]);
                atoms_add(sm + O_NCNT + 4 * (e.w >> 16), 1);
            }
        }
        __syncthreads();
        warp_scan<3>(sm + O_NCNT, sm + O_NOFF, NLOC, lane);
        __syncthreads();
        for (int j = 0; j < SEGW; j++) {
            int o = __shfl_sync(0xffffffffu, hoff, j), c = __shfl_sync(0xffffffffu, hcnt, j);
            for (int i = lane; i < c; i += 32) {
                uint4 e = ldcg128(&g_outbox[(w * SEGW + j) * CH + o + i]);
                int rr = atoms_add(sm + O_NCNT + 4 * (e.w >> 16), -1) - 1;
                g_sorted[gbase + lds32(sm + O_NOFF + 4 * (e.w >> 16)) + rr] = e;
            }
        }
    }
    if (t < NPOOL) {
        int o0 = lds32(sm + O_NOFF + 4 * (NPRIV + t)), o1 = lds32(sm + O_NOFF + 4 * (NPRIV + t) + 4);
        g_info[b * NPOOL + t] = make_int2(gbase + o0, o1 - o0);
    }
    __syncthreads();
    TS(6);

    if (w >= 8) {
        asm volatile("setmaxnreg.dec.sync.aligned.u32 72;");
        if (w >= 10) return;
        const int st = w - 8;
        const uint32_t xoff0 = (st * 8 + mat) * 1024 + ((r ^ mat) * 16);
        const uint32_t xoff1 = (st * 8 + 4 + mat) * 1024 + ((r ^ (4 + mat)) * 16);
        const uint32_t aoff = S_A + (st * 8 + (lane >> 1)) * 32 + (((lane & 1) ^ ((lane >> 3) & 1)) * 16);
        const uint32_t coff = S_C + (mat & 1) * 96 + (mat >> 1) * 224 + st * 16 + r * 2;
        const char* xl = x + r * 16;
        const char* al = ea + (lane & 1) * 16;

        int gl = st;
        int gnode = 0, gpos = 0, grem = 0;
        int tk1 = 0, tk2 = 0;
        int2 inf = make_int2(0, 0);
        bool pool = false;
        auto take = [&]() { int v = 0; if (lane == 0) v = (int)atomicAdd(&g_ticket, 1u); return v; };
        auto info = [&](int tk) {
            int2 v = make_int2(0, 0);
            if (NPRIV * G + tk < NN) { int l = tk / G; v = __ldcg(&g_info[(tk - l * G) * NPOOL + l]); }
            return v;
        };
        auto next = [&]() {
            Blk B;
            if (grem == 0 && gnode >= 0) {
                if (gl < NPRIV) {
                    int o0 = lds32(sm + O_NOFF + 4 * gl), o1 = lds32(sm + O_NOFF + 4 * gl + 4);
                    gnode = gl * G + b; gpos = gbase + o0; grem = o1 - o0;
                    gl += 2;
                    if (gl >= NPRIV - 2 && gl < NPRIV) tk2 = take();
                    else if (gl >= NPRIV) pool = true;
                } else {
                    gnode = NPRIV * G + tk1; gpos = inf.x; grem = inf.y;
                    if (gnode >= NN) gnode = -1;
                }
                if (pool && gnode >= 0) {
                    if (gl < NPRIV + 2) {
                        int it = 0;
                        while (ld_acq(&g_pub) < (unsigned)G) if (++it > SPIN_LIMIT) __trap();
                        gl = NPRIV + 2;
                    }
                    tk1 = __shfl_sync(0xffffffffu, tk2, 0);
                    inf = info(tk1);
                    tk2 = take();
                }
            }
            B.node = gnode;
            B.n = min(grem, 32);
            B.last = grem <= 32;
            B.e = make_uint4(0, 0, 0, 0);
            if (lane < B.n) B.e = ldcg128(&g_sorted[gpos + lane]);
            gpos += B.n; grem -= B.n;
            return B;
        };

        uint32_t so = sm + O_RING, ph = 1;
        int tile = 0;
        auto emit = [&](const Blk& B, int base, int meta) {
            mbar_wait(so + S_EMPTY, ph);
            int s0 = __shfl_sync(0xffffffffu, (int)B.e.x, base + mat), s1 = __shfl_sync(0xffffffffu, (int)B.e.x, base + 4 + mat);
            int id = __shfl_sync(0xffffffffu, (int)B.e.y, base + ((lane >> 1) & 7));
            uint32_t y01 = __shfl_sync(0xffffffffu, B.e.z, base + r), y2 = __shfl_sync(0xffffffffu, B.e.w, base + r);
            if (base + mat < B.n) {
                const char* gp = xl + (size_t)s0 * 1024;
#pragma unroll
                for (int k = 0; k < 8; k++) cpa16(so + xoff0 + k * 128, gp + k * 128);
            }
            if (base + 4 + mat < B.n) {
                const char* gp = xl + (size_t)s1 * 1024;
#pragma unroll
                for (int k = 0; k < 8; k++) cpa16(so + xoff1 + k * 128, gp + k * 128);
            }
            if (lane < 16) cpa16z(so + aoff, al + (size_t)id * 32, (base + (lane >> 1) < B.n) ? 16 : 0);
            asm volatile("cp.async.mbarrier.arrive.noinc.shared::cta.b64 [%0];" ::"r"(so + S_FULL) : "memory");
            float f0 = __uint_as_float(y01 << 16), f1 = __uint_as_float(y01 & 0xffff0000u), f2 = __uint_as_float(y2 << 16);
#pragma unroll
            for (int i = 0; i < 3; i++) sts16(so + coff + i * 32, pack(E[i * 3] * f0 + E[i * 3 + 1] * f1 + E[i * 3 + 2] * f2, 0.f));
            if (lane == 0) sts32(so + S_META + st * 4, meta);
            __syncwarp();
            if (lane == 0) mbar_arrive(so + S_FULL);
            so += SLOT;
            if (so == sm + O_RING + NSLOT * SLOT) { so = sm + O_RING; ph ^= 1; }
            tile++;
        };

        Blk c0 = next(), c1 = next(), c2 = next();
        while (c0.node >= 0) {
            int base = 0;
            do {
                emit(c0, base, (c0.last && base + 8 >= c0.n) ? c0.node : -1);
                base += 8;
            } while (base < c0.n);
            c0 = c1; c1 = c2; c2 = next();
        }
        TSW(8 + st);
        const int myend = tile + (tk2 >> 31);
        if (lane == 0) sts32(sm + O_END + 4 * st, myend);
        __syncwarp();
        while (true) {
            int oe = lds32(sm + O_END + 4 * (st ^ 1));
            if (tile > max(myend, oe)) break;
            emit(c0, 0, -2);
        }
        asm volatile("cp.async.wait_all;" ::: "memory");
    } else {
        asm volatile("setmaxnreg.inc.sync.aligned.u32 216;");
        if (t == 0) asm volatile("red.release.gpu.global.add.u32 [%0], 1;" ::"l"(&g_pub) : "memory");
        const uint32_t xa = ((mat >> 1) * 8 + r) * 1024 + (w >> 2) * 128 + (((2 * (w & 3) + (mat & 1)) ^ r) * 16);
        const uint32_t aa = S_A + ((mat >> 1) * 8 + r) * 32 + (((mat & 1) ^ (r >> 2)) * 16);
        const uint32_t ya = S_C + mat * 16;
        const bool cv = ((r >> 2) == (mat & 1)) && (r & 3) < 3;
        const uint32_t ma = S_C + (cv ? (mat >> 1) * 96 + (r & 3) * 32 + (mat & 1) * 16 : 192 + ((mat & 1) ^ 1) * 16);
        const uint32_t pw = sm + O_P + w * PW;
        uint32_t fa[2];
#pragma unroll
        for (int S = 0; S < 2; S++) {
            const int c = r ^ (S * 4);
            int o, tr = -1;
            if (mat < 2) { if (c < 3) o = P_1P0 + 2 * c * PSBO; else if (c == 3) tr = 6; else if (c < 7) o = P_1P1 + 2 * (c - 4) * PSBO; else o = P_0P0; }
            else { if (c < 3) o = P_1P2 + 2 * c * PSBO; else if (c == 3) o = P_0P1; else tr = 2 * (c - 4) + 1; }
            fa[S] = (tr < 0) ? pw + o + (mat & 1) * 128 : sm + O_TRASH + ((((pw - sm - O_TRASH) >> 4) + tr) & 7) * 16;
        }
        Acc A;
#pragma unroll
        for (int i = 0; i < 4; i++) { A.p00[i] = A.p110[i] = A.p10[0][i] = A.p10[1][i] = A.p10[2][i] = 0; A.t01[i] = A.t11[i] = 0.f; }
        int slot = 0, mynode = 0;
        bool w1ok = false;
        uint32_t so = sm + O_RING, ph = 0;
        while (true) {
            mbar_wait(so + S_FULL, ph);
            int fA, fB;
            asm volatile("ld.shared.v2.u32 {%0,%1}, [%2];" : "=r"(fA), "=r"(fB) : "r"(so + S_META) : "memory");
            uint32_t a[4], yb[6], ym[8], f[4][4];
            ldsm4(a, so + aa);
#pragma unroll
            for (int m = 0; m < 4; m++) ldsm4t(f[m], so + xa + m * 256);
            ldsm4(yb, so + ya); ldsm2(yb + 4, so + ya + 64);
            ldsm4(ym, so + ma); ldsm4(ym + 4, so + ma + 224);
            __syncwarp();
            if (lane == 0) mbar_arrive(so + S_EMPTY);
            so += SLOT;
            if (so == sm + O_RING + NSLOT * SLOT) { so = sm + O_RING; ph ^= 1; }
            int pend;
            if (fA + fB == -4) {
                pend = 4;
            } else {
                uint32_t R[5][4];
#pragma unroll
                for (int p = 0; p < 5; p++) {
                    float c[4];
                    mma16z(c, wr[p], a[0], a[1]); R[p][0] = pack(c[0], c[1]); R[p][1] = pack(c[2], c[3]);
                    mma16z(c, wr[p], a[2], a[3]); R[p][2] = pack(c[0], c[1]); R[p][3] = pack(c[2], c[3]);
                }
                uint32_t u[4];
#pragma unroll
                for (int i = 0; i < 4; i++) {
                    A.p00[i] = hfma(f[0][i], R[0][i], A.p00[i]);
                    uint32_t sdot = hfma(f[3][i], yb[4 + (i >> 1)], hfma(f[2][i], yb[2 + (i >> 1)], hmul(f[1][i], yb[i >> 1])));
                    A.p110[i] = hfma(sdot, R[1][i], A.p110[i]);
                    u[i] = hmul(f[0][i], R[2][i]);
                }
                mma16(A.t01, u[0], u[1], u[2], u[3], ym[0], ym[1]);
#pragma unroll
                for (int k = 0; k < 3; k++) {
#pragma unroll
                    for (int i = 0; i < 4; i++) {
                        A.p10[k][i] = hfma(f[1 + k][i], R[3][i], A.p10[k][i]);
                        u[i] = hmul(f[1 + k][i], R[4][i]);
                    }
                    mma16(A.t11, u[0], u[1], u[2], u[3], ym[2 + 2 * k], ym[3 + 2 * k]);
                }
                pend = (fA >= 0 ? 1 : 0) | (fB >= 0 ? 2 : 0);
            }
            while (pend) {
                const uint32_t sof = (slot & 7) * 16 + (slot >> 3) * PSBO;
                if (pend & 1) { flush<0>(A, fa[0] + sof, g, q); if (lane == slot) mynode = fA; slot++; pend &= 2; }
                else if (pend & 2) { flush<1>(A, fa[1] + sof, g, q); if (lane == slot) mynode = fB; slot++; pend = 0; }
                if (slot == 16 || (pend == 4 && slot > 0)) {
                    if (!w1ok) { mbar_wait(sm + O_WBB, 0); w1ok = true; }
                    asm volatile("fence.proxy.async.shared::cta;" ::: "memory");
                    bar_sync(1, 256);
                    float d0[8], d1[24];
#pragma unroll
                    for (int i = 0; i < 8; i++) d0[i] = 0.f;
#pragma unroll
                    for (int i = 0; i < 24; i++) d1[i] = 0.f;
                    const uint64_t db = (uint64_t)(((sm + O_P) >> 4) & 0x3fff) | (8ull << 16) | ((uint64_t)(PSBO / 16) << 32);
                    const uint64_t da = (uint64_t)(((sm + O_W1 + (w >> 2) * 49152) >> 4) & 0x3fff) | (1ull << 16) | (64ull << 32) | (1ull << 62);
                    asm volatile("wgmma.fence.sync.aligned;" ::: "memory");
#pragma unroll
                    for (int k = 0; k < 16; k++) wg_rs16(d0, w0[k], db + (((k & 7) * PW + ((k >> 3) ? P_0P1 : P_0P0)) >> 4), k);
#pragma unroll
                    for (int k = 0; k < 24; k++)
                        wg_ss48(d1, da + k * 128, db + (((k & 7) * PW + ((k >> 3) == 0 ? P_1P0 : (k >> 3) == 1 ? P_1P1 : P_1P2)) >> 4), k);
                    asm volatile("wgmma.commit_group.sync.aligned;" ::: "memory");
                    asm volatile("wgmma.wait_group.sync.aligned 0;" ::: "memory");
#pragma unroll
                    for (int i = 0; i < 8; i++) asm volatile("" : "+f"(d0[i])::"memory");
#pragma unroll
                    for (int i = 0; i < 24; i++) asm volatile("" : "+f"(d1[i])::"memory");
                    uint32_t o[4][4];
#pragma unroll
                    for (int i = 0; i < 4; i++) {
                        float g0 = __fdividef(1.f, 1.f + __expf(-d0[2 * i])), g1 = __fdividef(1.f, 1.f + __expf(-d0[2 * i + 1]));
                        o[0][i] = pack(d0[2 * i], d0[2 * i + 1]);
#pragma unroll
                        for (int j = 0; j < 3; j++) o[1 + j][i] = pack(d1[8 * j + 2 * i] * g0, d1[8 * j + 2 * i + 1] * g1);
                    }
                    bar_sync(1, 256);
                    const uint32_t sg = sm + O_P + (w & 4) * PW + ((mat >> 1) * 8 + r) * 128 + (((2 * (w & 3) + (mat & 1)) ^ r) * 16);
#pragma unroll
                    for (int j = 0; j < 4; j++) stsm4t(sg + j * PW, o[j][0], o[j][1], o[j][2], o[j][3]);
                    bar_sync(2 + (w >> 2), 128);
#pragma unroll
                    for (int it = 0; it < 4; it++) {
                        const int row = it * 4 + mat;
                        const int nd = __shfl_sync(0xffffffffu, mynode, row);
                        uint4 v = lds128(pw + row * 128 + ((r ^ (row & 7)) * 16));
                        if (row < slot) *(uint4*)(out + (size_t)nd * 1024 + (w & 3) * 256 + (w >> 2) * 128 + r * 16) = v;
                    }
                    __syncwarp();
                    slot = 0;
                }
                if (pend == 4) break;
            }
            if (pend == 4) break;
        }
        TS(10);
        if (t == 0) {
            __threadfence();
            if (atomicInc(&g_done, G - 1) == G - 1) { g_pub = 0; g_ticket = 0; }
        }
    }
}

typedef CUresult (*EncFn)(CUtensorMap*, CUtensorMapDataType, cuuint32_t, void*, const cuuint64_t*, const cuuint64_t*,
                          const cuuint32_t*, const cuuint32_t*, CUtensorMapInterleave, CUtensorMapSwizzle,
                          CUtensorMapL2promotion, CUtensorMapFloatOOBfill);

void make_map(EncFn fn, CUtensorMap* m, void* p, int rows, int cols, int brows) {
    cuuint64_t dims[2] = {(cuuint64_t)cols, (cuuint64_t)rows}, strides[1] = {(cuuint64_t)cols * 2};
    cuuint32_t box[2] = {64, (cuuint32_t)brows}, es[2] = {1, 1};
    fn(m, CU_TENSOR_MAP_DATA_TYPE_BFLOAT16, 2, p, dims, strides, box, es, CU_TENSOR_MAP_INTERLEAVE_NONE,
       CU_TENSOR_MAP_SWIZZLE_128B, CU_TENSOR_MAP_L2_PROMOTION_NONE, CU_TENSOR_MAP_FLOAT_OOB_FILL_NONE);
}

}

extern "C" void kernel_launch(void* const* d_in, const int* in_sizes, int n_in, void* d_out, int out_size) {
    static EncFn enc = nullptr;
    if (!enc) {
        void* fn = nullptr;
        cudaDriverEntryPointQueryResult qr;
        cudaGetDriverEntryPoint("cuTensorMapEncodeTiled", &fn, cudaEnableDefault, &qr);
        enc = (EncFn)fn;
        cudaFuncSetAttribute(tp_kernel, cudaFuncAttributeMaxDynamicSharedMemorySize, SMEM_BYTES);
    }
    CUtensorMap m_wr, m_w0, m_w1;
    make_map(enc, &m_wr, d_in[5], 16, 640, 16);
    make_map(enc, &m_w0, d_in[6], 256, 128, 256);
    make_map(enc, &m_w1, d_in[7], 384, 128, 192);
    tp_kernel<<<G, NT, SMEM_BYTES>>>(m_wr, m_w0, m_w1, (const char*)d_in[0], (const uint4*)d_in[1], (const char*)d_in[2],
                                     (const int4*)d_in[3], (const int4*)d_in[4], (const __nv_bfloat16*)d_in[8], (char*)d_out);
}
```

```cpp
#include <cuda_runtime.h>
#include <cuda_bf16.h>
#include <cuda.h>
#include <stdint.h>

namespace {

constexpr int NN = 10000;
constexpr int NE = 320000;
constexpr int G = 132;
constexpr int NT = 384;
constexpr int CH = 2432;
constexpr int NLOC = (NN + G - 1) / G;
constexpr int NPOOL = 8;
constexpr int NPRIV = NLOC - NPOOL;
constexpr int NS0 = NPRIV / 2;
constexpr int SEGW = 11;
constexpr int HSTR = 160;
constexpr uint32_t META_END = 0x3fff;

#define NSLOT 5
#define PREFETCH 1
#define W1EARLY 1
#define CREG 216
#define PREG 72
#define STR2(x) #x
#define STR(x) STR2(x)

constexpr int S_A = 16384, S_C = S_A + 512, S_FULL = S_C + 144, S_EMPTY = S_FULL + 8, S_H = S_C + 160, SLOT = 17152;

constexpr int PSBO = 272;
constexpr int PB1 = 5 * PSBO + 256, PB0 = PSBO + 256;
constexpr int P_1P0 = 0, P_1P1 = PB1, P_0P1 = 2 * PB1, P_0P0 = P_0P1 + PB0, P_1P2 = P_0P0 + PB0;
constexpr int PW = P_1P2 + PB1;

constexpr int O_W1 = 0;
constexpr int O_P = 98304;
constexpr int O_RING = O_P + 8 * PW;
constexpr int O_W0S = O_P + CH * 16, O_WRS = O_W0S + 65536;
constexpr int O_BCNT = O_WRS + 20480, O_NCNT = O_BCNT + 544, O_NC2 = O_NCNT + 320, O_NCUR = O_NC2 + 320;
constexpr int O_BOFF = O_NCUR + 320, O_NOFF = O_BOFF + 544;
constexpr int O_TRASH = O_RING + 5 * SLOT;
constexpr int O_WBA = O_TRASH + 512, O_WBB = O_WBA + 8, O_WBC = O_WBA + 16, O_NODE = O_WBA + 32;
constexpr int O_SUM = O_NODE + 64, O_END = O_SUM + 4, O_MB = O_SUM + 16;
constexpr int SMEM_BYTES = O_MB + 256;
constexpr int O_L = O_P - 24576;
constexpr int CAPB = (O_W0S - O_L) / 128;
constexpr int NBLK = NE / 8 + G * (NLOC + 5) + 1;
static_assert(SMEM_BYTES <= 232448 && NSLOT == 5 && CH * 10 <= 24576 && CAPB % 4 == 0 && NBLK < 65536, "smem");
static_assert(O_W0S % 1024 == 0 && O_BCNT >= O_RING + 4 * SLOT && O_NOFF + 320 <= O_RING + 4 * SLOT + S_A, "layout");
static_assert(G * CH >= NE && NE % 8 == 0 && CH < 4096, "chunks");
static_assert(SEGW * (NT / 32) == G, "segments");
static_assert(NLOC <= 78 && NN < META_END, "scan width");

struct __align__(128) Scratch {
    uint4 list[NBLK * 8];
    uint4 outbox[G * CH];
    uint32_t hdr[G * HSTR];
    uint32_t info[G * NPOOL];
    unsigned epoch, done, pad0[30], pub, pad1[31], ticket;
};
__device__ Scratch g_scratch;
#define TS(i)
#define TSW(i)

constexpr int SPIN_LIMIT = 1 << 24;

__device__ __forceinline__ void mbar_init(uint32_t a, int c) { asm volatile("mbarrier.init.shared::cta.b64 [%0], %1;" ::"r"(a), "r"(c) : "memory"); }
__device__ __forceinline__ void mbar_expect(uint32_t a, int b) { asm volatile("mbarrier.arrive.expect_tx.shared::cta.b64 _, [%0], %1;" ::"r"(a), "r"(b) : "memory"); }
__device__ __forceinline__ void mbar_arrive(uint32_t a) { asm volatile("mbarrier.arrive.shared::cta.b64 _, [%0];" ::"r"(a) : "memory"); }
__device__ __forceinline__ void mbar_wait(uint32_t a, uint32_t ph) {
    asm volatile("{\n.reg .pred p, q;\n.reg .u32 it;\n"
                 "mbarrier.try_wait.parity.shared::cta.b64 p, [%0], %1;\n"
                 "@p bra DONE;\n"
                 "mov.u32 it, 0;\n"
                 "LOOP:\n"
                 "mbarrier.try_wait.parity.shared::cta.b64 p, [%0], %1;\n"
                 "@p bra DONE;\n"
                 "add.u32 it, it, 1;\n"
                 "setp.gt.u32 q, it, %2;\n"
                 "@q trap;\n"
                 "bra LOOP;\n"
                 "DONE:\n}" ::"r"(a), "r"(ph), "n"(SPIN_LIMIT) : "memory");
}
__device__ __forceinline__ void spin_check(int it) {
    asm volatile("{\n.reg .pred q;\nsetp.gt.s32 q, %0, %1;\n@q trap;\n}" ::"r"(it), "n"(SPIN_LIMIT));
}
__device__ __forceinline__ void tma2d(uint32_t dst, const CUtensorMap* m, int c0, int c1, uint32_t bar) {
    asm volatile("cp.async.bulk.tensor.2d.shared::cluster.global.mbarrier::complete_tx::bytes [%0], [%1, {%3, %4}], [%2];"
                 ::"r"(dst), "l"(m), "r"(bar), "r"(c0), "r"(c1) : "memory");
}
__device__ __forceinline__ uint32_t mbar_test(uint32_t a, uint32_t ph) {
    uint32_t ok;
    asm volatile("{\n.reg .pred p;\nmbarrier.test_wait.parity.shared::cta.b64 p, [%1], %2;\nselp.u32 %0, 1, 0, p;\n}" : "=r"(ok) : "r"(a), "r"(ph) : "memory");
    return ok;
}
__device__ __forceinline__ void cpa16z(uint32_t d, const void* g, uint32_t v) {
    asm volatile("{\n.reg .pred p;\nsetp.eq.u32 p, %2, 0;\ncp.async.cg.shared.global [%0], [%1], 16, p;\n}" ::"r"(d), "l"(g), "r"(v) : "memory");
}
__device__ __forceinline__ void ldsm4(uint32_t* r, uint32_t a) { asm volatile("ldmatrix.sync.aligned.m8n8.x4.shared.b16 {%0,%1,%2,%3}, [%4];" : "=r"(r[0]), "=r"(r[1]), "=r"(r[2]), "=r"(r[3]) : "r"(a) : "memory"); }
__device__ __forceinline__ void ldsm4t(uint32_t* r, uint32_t a) { asm volatile("ldmatrix.sync.aligned.m8n8.x4.trans.shared.b16 {%0,%1,%2,%3}, [%4];" : "=r"(r[0]), "=r"(r[1]), "=r"(r[2]), "=r"(r[3]) : "r"(a) : "memory"); }
__device__ __forceinline__ void stsm4t(uint32_t a, uint32_t r0, uint32_t r1, uint32_t r2, uint32_t r3) { asm volatile("stmatrix.sync.aligned.m8n8.x4.trans.shared.b16 [%0], {%1,%2,%3,%4};" ::"r"(a), "r"(r0), "r"(r1), "r"(r2), "r"(r3) : "memory"); }
__device__ __forceinline__ void mma16(float* d, uint32_t a0, uint32_t a1, uint32_t a2, uint32_t a3, uint32_t b0, uint32_t b1) {
    asm("mma.sync.aligned.m16n8k16.row.col.f32.bf16.bf16.f32 {%0,%1,%2,%3}, {%4,%5,%6,%7}, {%8,%9}, {%0,%1,%2,%3};"
        : "+f"(d[0]), "+f"(d[1]), "+f"(d[2]), "+f"(d[3]) : "r"(a0), "r"(a1), "r"(a2), "r"(a3), "r"(b0), "r"(b1));
}
__device__ __forceinline__ void mma16z(float* d, const uint32_t* a, uint32_t b0, uint32_t b1) {
    asm("mma.sync.aligned.m16n8k16.row.col.f32.bf16.bf16.f32 {%0,%1,%2,%3}, {%4,%5,%6,%7}, {%8,%9}, {%10,%10,%10,%10};"
        : "=f"(d[0]), "=f"(d[1]), "=f"(d[2]), "=f"(d[3]) : "r"(a[0]), "r"(a[1]), "r"(a[2]), "r"(a[3]), "r"(b0), "r"(b1), "f"(0.f));
}
__device__ __forceinline__ uint32_t pack(float lo, float hi) { uint32_t r; asm("cvt.rn.bf16x2.f32 %0, %1, %2;" : "=r"(r) : "f"(hi), "f"(lo)); return r; }
__device__ __forceinline__ uint32_t hmul(uint32_t a, uint32_t b) { uint32_t r; asm("mul.rn.bf16x2 %0, %1, %2;" : "=r"(r) : "r"(a), "r"(b)); return r; }
__device__ __forceinline__ uint32_t hfma(uint32_t a, uint32_t b, uint32_t c) { uint32_t r; asm("fma.rn.bf16x2 %0, %1, %2, %3;" : "=r"(r) : "r"(a), "r"(b), "r"(c)); return r; }
__device__ __forceinline__ uint4 lds128(uint32_t a) { uint4 v; asm volatile("ld.shared.v4.u32 {%0,%1,%2,%3}, [%4];" : "=r"(v.x), "=r"(v.y), "=r"(v.z), "=r"(v.w) : "r"(a) : "memory"); return v; }
__device__ __forceinline__ void sts128(uint32_t a, uint4 v) { asm volatile("st.shared.v4.u32 [%0], {%1,%2,%3,%4};" ::"r"(a), "r"(v.x), "r"(v.y), "r"(v.z), "r"(v.w) : "memory"); }
__device__ __forceinline__ int lds32(uint32_t a) { int v; asm volatile("ld.shared.u32 %0, [%1];" : "=r"(v) : "r"(a) : "memory"); return v; }
__device__ __forceinline__ void sts32(uint32_t a, int v) { asm volatile("st.shared.u32 [%0], %1;" ::"r"(a), "r"(v) : "memory"); }
__device__ __forceinline__ int atoms_add(uint32_t a, int v) { int r; asm volatile("atom.shared.add.u32 %0, [%1], %2;" : "=r"(r) : "r"(a), "r"(v) : "memory"); return r; }
__device__ __forceinline__ uint32_t ld_acq(const void* p) { uint32_t v; asm volatile("ld.acquire.gpu.global.u32 %0, [%1];" : "=r"(v) : "l"(p) : "memory"); return v; }
__device__ __forceinline__ uint32_t ld_rlx(const void* p) { uint32_t v; asm volatile("ld.relaxed.gpu.global.u32 %0, [%1];" : "=r"(v) : "l"(p) : "memory"); return v; }
__device__ __forceinline__ uint4 ld_rlx128(const void* p) {
    uint64_t a, b;
    asm volatile("ld.relaxed.gpu.global.v2.b64 {%0,%1}, [%2];" : "=l"(a), "=l"(b) : "l"(p) : "memory");
    return make_uint4((uint32_t)a, (uint32_t)(a >> 32), (uint32_t)b, (uint32_t)(b >> 32));
}
__device__ __forceinline__ void st_rlx128(void* p, uint4 v) {
    asm volatile("st.relaxed.gpu.global.v2.b64 [%0], {%1,%2};" ::"l"(p), "l"(v.x | ((uint64_t)v.y << 32)), "l"(v.z | ((uint64_t)v.w << 32)) : "memory");
}
__device__ __forceinline__ void bulk(uint32_t dst, const void* g, int n, uint32_t bar) {
    asm volatile("cp.async.bulk.shared::cluster.global.mbarrier::complete_tx::bytes [%0], [%1], %2, [%3];" ::"r"(dst), "l"(g), "r"(n), "r"(bar) : "memory");
}
__device__ __forceinline__ uint2 lds64(uint32_t a) { uint2 v; asm volatile("ld.shared.v2.u32 {%0,%1}, [%2];" : "=r"(v.x), "=r"(v.y) : "r"(a) : "memory"); return v; }
__device__ __forceinline__ uint64_t madw(uint32_t a, uint32_t b, uint64_t c) { uint64_t r; asm("mad.wide.u32 %0, %1, %2, %3;" : "=l"(r) : "r"(a), "r"(b), "l"(c)); return r; }
__device__ __forceinline__ uint32_t opaque(uint32_t v, int lane) { return __shfl_sync(0xffffffffu, v, lane); }
__device__ __forceinline__ void bar_sync(int id, int n) { asm volatile("bar.sync %0, %1;" ::"r"(id), "r"(n) : "memory"); }

__device__ __forceinline__ void wg_rs16(float* d, const uint32_t* a, uint64_t db, int sc) {
    asm volatile("{.reg .pred p; setp.ne.b32 p, %13, 0;\n"
                 "wgmma.mma_async.sync.aligned.m64n16k16.f32.bf16.bf16 {%0,%1,%2,%3,%4,%5,%6,%7}, {%8,%9,%10,%11}, %12, p, 1, 1, 0;}"
                 : "+f"(d[0]), "+f"(d[1]), "+f"(d[2]), "+f"(d[3]), "+f"(d[4]), "+f"(d[5]), "+f"(d[6]), "+f"(d[7])
                 : "r"(a[0]), "r"(a[1]), "r"(a[2]), "r"(a[3]), "l"(db), "r"(sc));
}
__device__ __forceinline__ void wg_ss48(float* d, uint64_t da, uint64_t db, int sc) {
    asm volatile("{.reg .pred p; setp.ne.b32 p, %26, 0;\n"
                 "wgmma.mma_async.sync.aligned.m64n48k16.f32.bf16.bf16 {%0,%1,%2,%3,%4,%5,%6,%7,%8,%9,%10,%11,%12,%13,%14,%15,%16,%17,%18,%19,%20,%21,%22,%23}, %24, %25, p, 1, 1, 1, 0;}"
                 : "+f"(d[0]), "+f"(d[1]), "+f"(d[2]), "+f"(d[3]), "+f"(d[4]), "+f"(d[5]), "+f"(d[6]), "+f"(d[7]),
                   "+f"(d[8]), "+f"(d[9]), "+f"(d[10]), "+f"(d[11]), "+f"(d[12]), "+f"(d[13]), "+f"(d[14]), "+f"(d[15]),
                   "+f"(d[16]), "+f"(d[17]), "+f"(d[18]), "+f"(d[19]), "+f"(d[20]), "+f"(d[21]), "+f"(d[22]), "+f"(d[23])
                 : "l"(da), "l"(db), "r"(sc));
}

__device__ __forceinline__ int warp_incl(int v, int lane) {
#pragma unroll
    for (int o = 1; o < 32; o <<= 1) { int u = __shfl_up_sync(0xffffffffu, v, o); if (lane >= o) v += u; }
    return v;
}

struct Acc {
    uint32_t p00[4], p110[4], p10[3][4];
    float t01[4], m[3][4];
};

template <int S>
__device__ __forceinline__ void flush(Acc& A, uint32_t addr, const uint32_t* oh, const uint32_t* eb, bool s1) {
    const bool mine = S ? s1 : !s1;
    float x[4], z[4];
    uint32_t mp[4];
#pragma unroll
    for (int i = 0; i < 4; i++) x[i] = mine ? A.t01[i] : 0.f;
    mp[0] = pack(A.m[0][0], A.m[0][1]); mp[1] = pack(A.m[0][2], A.m[0][3]);
    mp[2] = pack(A.m[1][0], A.m[1][1]); mp[3] = pack(A.m[1][2], A.m[1][3]);
    mma16(x, A.p10[0][2 * S], A.p10[0][2 * S + 1], A.p10[1][2 * S], A.p10[1][2 * S + 1], oh[4 ^ (4 * S)], oh[5 ^ (4 * S)]);
    mma16z(z, mp, eb[0], eb[1]);
    mma16(x, A.p10[2][2 * S], A.p10[2][2 * S + 1], A.p00[2 * S], A.p00[2 * S + 1], oh[6 ^ (4 * S)], oh[7 ^ (4 * S)]);
    mma16(z, pack(A.m[2][0], A.m[2][1]), pack(A.m[2][2], A.m[2][3]), A.p110[2 * S], A.p110[2 * S + 1], eb[2], oh[3 ^ (4 * S)]);
    if (mine) {
#pragma unroll
        for (int i = 0; i < 4; i++) { A.t01[i] = 0.f; A.m[0][i] = 0.f; A.m[1][i] = 0.f; A.m[2][i] = 0.f; }
    }
#pragma unroll
    for (int i = 2 * S; i < 2 * S + 2; i++) { A.p00[i] = 0; A.p110[i] = 0; A.p10[0][i] = 0; A.p10[1][i] = 0; A.p10[2][i] = 0; }
    stsm4t(addr, pack(x[0], x[1]), pack(x[2], x[3]), pack(z[0], z[1]), pack(z[2], z[3]));
}

__global__ void __launch_bounds__(NT, 1)
tp_kernel(const int4* __restrict__ dst, const char* __restrict__ src, const char* __restrict__ rhat, Scratch* __restrict__ gs,
          const char* __restrict__ x, const char* __restrict__ ea, const __nv_bfloat16* __restrict__ eps, char* __restrict__ out,
          const __grid_constant__ CUtensorMap m_wr, const __grid_constant__ CUtensorMap m_w0, const __grid_constant__ CUtensorMap m_w1) {
    extern __shared__ __align__(1024) char smem_raw[];
    const uint32_t sm = (uint32_t)__cvta_generic_to_shared(smem_raw);
    const int t = threadIdx.x, w = t >> 5, lane = t & 31, b = blockIdx.x;

    const int e0 = b * CH + t * 4;
    const bool act[2] = {t < CH / 8, t < CH / 8 && e0 + CH / 2 < NE};
    int d[8];
#pragma unroll
    for (int k = 0; k < 2; k++)
        if (act[k]) *(int4*)&d[4 * k] = __ldg(dst + e0 / 4 + k * (CH / 8));
    if (t == NT - 1) {
        const int ne = min(CH, NE - b * CH);
        mbar_init(sm + O_WBA, 1); mbar_init(sm + O_WBB, 1); mbar_init(sm + O_WBC, 1);
        asm volatile("fence.proxy.async.shared::cta;" ::: "memory");
        mbar_expect(sm + O_WBC, ne * 10);
        bulk(sm + O_L, src + b * (CH * 4), ne * 4, sm + O_WBC);
        bulk(sm + O_L + CH * 4, rhat + b * (CH * 6), ne * 6, sm + O_WBC);
        mbar_expect(sm + O_WBA, 86016); mbar_expect(sm + O_WBB, 98304);
        tma2d(sm + O_W0S, &m_w0, 0, 0, sm + O_WBA);
        tma2d(sm + O_W0S + 32768, &m_w0, 64, 0, sm + O_WBA);
        for (int j = 0; j < 10; j++) tma2d(sm + O_WRS + j * 2048, &m_wr, 64 * j, 0, sm + O_WBA);
        for (int j = 0; j < 3; j++) tma2d(sm + O_W1 + j * 24576, &m_w1, 64 * (j >> 1), 192 * (j & 1), sm + O_WBB);
    }
    uint32_t epoch = ld_rlx(&gs->epoch);
    sts32(sm + O_BCNT + 4 * t, 0);
    if (t < 68) sts32(sm + O_SUM + 4 * t, 0);
    __syncthreads();
    int rk[8];
#pragma unroll
    for (int k = 0; k < 2; k++)
        if (act[k]) {
#pragma unroll
            for (int i = 4 * k; i < 4 * k + 4; i++) {
                int loc = d[i] / G, own = d[i] - loc * G;
                d[i] = own | (loc << 16);
                rk[i] = atoms_add(sm + O_BCNT + 4 * own, 1);
            }
        }
    TS(0);
    __syncthreads();
    {
        int v[5], sum = 0;
#pragma unroll
        for (int i = 0; i < 5; i++) { v[i] = (lane * 5 + i < G) ? lds32(sm + O_BCNT + 4 * (lane * 5 + i)) : 0; sum += v[i]; }
        int e = warp_incl(sum, lane) - sum;
#pragma unroll
        for (int i = 0; i < 5; i++) { if (lane * 5 + i < G) sts32(sm + O_BOFF + 4 * (lane * 5 + i), e); e += v[i]; }
        __syncwarp();
    }
    asm volatile("" : "+r"(epoch));
    const uint32_t tag = (epoch + 1) << 24;
    if ((unsigned)(t - 320) < 34u) {
        const uint4 o = lds128(sm + O_BOFF + 16 * (t - 320)), c = lds128(sm + O_BCNT + 16 * (t - 320));
        st_rlx128(&gs->hdr[b * HSTR + 4 * (t - 320)], make_uint4(tag | o.x << 12 | c.x, tag | o.y << 12 | c.y, tag | o.z << 12 | c.z, tag | o.w << 12 | c.w));
    }
#pragma unroll
    for (int k = 0; k < 2; k++)
        if (act[k]) {
#pragma unroll
            for (int i = 4 * k; i < 4 * k + 4; i++) rk[i] += lds32(sm + O_BOFF + 4 * (d[i] & 0xffff));
        }
    mbar_wait(sm + O_WBC, 0);
    TS(11);
    if (t == NT - 1) {
        constexpr int PC = 19392;
        for (int j = 0; j < 8; j++) {
            int o = (b * 4 + (j & 3)) * PC, n = PC;
            if (b == G - 1 && (j & 3) == 3) n = NN * 1024 - o;
            asm volatile("cp.async.bulk.prefetch.L2.global [%0], %1;" ::"l"((j < 4 ? x : ea) + o), "r"(n) : "memory");
        }
    }
#pragma unroll
    for (int k = 0; k < 2; k++)
        if (act[k]) {
            const uint4 s4 = lds128(sm + O_L + (k * (CH / 8) + t) * 16);
            const uint32_t s[4] = {s4.x, s4.y, s4.z, s4.w};
            uint32_t y[6];
#pragma unroll
            for (int i = 0; i < 3; i++) *(uint2*)&y[2 * i] = lds64(sm + O_L + CH * 4 + (k * (CH / 8) + t) * 24 + i * 8);
#pragma unroll
            for (int i = 0; i < 4; i++) {
                uint32_t lo, hi, id = e0 + k * (CH / 2) + i + 1;
                if (i & 1) { lo = __byte_perm(y[(3 * i) / 2], y[(3 * i) / 2 + 1], 0x5432); hi = y[(3 * i) / 2 + 1] >> 16; }
                else { lo = y[(3 * i) / 2]; hi = y[(3 * i) / 2 + 1] & 0xffffu; }
                sts128(sm + O_P + rk[4 * k + i] * 16, make_uint4((s[i] + 1) | (id << 16), (id >> 16) | (d[4 * k + i] & 0xffff0000u) | tag, lo, hi | tag));
            }
        }
    const uint32_t* hp = &gs->hdr[(w * SEGW + min(lane, SEGW - 1)) * HSTR + b];
    uint32_t hv = ld_rlx(hp);
    __syncthreads();
    TS(12);
    {
        constexpr int K = CH / NT;
        uint64_t v[K + 1][2];
        uint4* op = &gs->outbox[b * CH + t];
#pragma unroll
        for (int k = 0; k <= K; k++) asm volatile("ld.shared.v2.b64 {%0,%1}, [%2];" : "=l"(v[k][0]), "=l"(v[k][1]) : "r"(sm + O_P + (t + k * NT) * 16) : "memory");
#pragma unroll
        for (int k = 0; k <= K; k++)
            asm volatile("{.reg .pred p; setp.lt.s32 p, %3, %4; @p st.relaxed.gpu.global.v2.b64 [%0], {%1,%2};}"
                         ::"l"(op + k * NT), "l"(v[k][0]), "l"(v[k][1]), "r"(k < K ? 0 : t), "n"(CH - K * NT) : "memory");
    }
    TS(1);

    for (int it = 0; __any_sync(0xffffffffu, (hv ^ tag) >> 24); it++) { hv = ld_rlx(hp); spin_check(it); }
    TS(3);
    const uint4* ob = gs->outbox + w * SEGW * CH + lane;
    uint64_t ea_[SEGW], eb_[SEGW];
    uint32_t have = 0;
#pragma unroll
    for (int j = 0; j < SEGW; j++) {
        const uint32_t h = __shfl_sync(0xffffffffu, hv, j);
        asm volatile("{.reg .pred p; setp.lt.u32 p, %4, %5; mov.b64 %0, 0; mov.b64 %1, 0;\n"
                     "@p ld.relaxed.gpu.global.v2.b64 {%0,%1}, [%3]; @p or.b32 %2, %2, %6;}"
                     : "=l"(ea_[j]), "=l"(eb_[j]), "+r"(have) : "l"(ob + j * CH + ((h >> 12) & 0xfff)), "r"(lane), "r"(h & 0xfff), "r"(1 << j) : "memory");
    }
    {
        int so = __reduce_add_sync(0xffffffffu, lane < SEGW ? (hv >> 12) & 0xfff : 0);
        if (lane == 0) atoms_add(sm + O_SUM, so);
    }
    const int g = lane >> 2, q = lane & 3, mat = lane >> 3, r = lane & 7;
    const uint32_t sw = (uint32_t)(((2 * (w & 3) + (mat & 1)) ^ r) * 16 + ((mat >> 1) * 8 + r) * 128);
    uint32_t wr[5][4], w0[16][4];
    if (w < 8) {
        mbar_wait(sm + O_WBA, 0);
#pragma unroll
        for (int k = 0; k < 16; k++) ldsm4t(w0[k], sm + O_W0S + (w >> 2) * 32768 + k * 2048 + sw);
    }
    TS(2);
    for (int it = 0;; it++) {
        uint32_t pend = 0;
#pragma unroll
        for (int j = 0; j < SEGW; j++)
            if ((((uint32_t)(ea_[j] >> 32) ^ tag) | ((uint32_t)(eb_[j] >> 32) ^ tag)) >> 24) pend |= 1u << j;
        pend &= have;
        if (!__any_sync(0xffffffffu, pend)) break;
        spin_check(it);
#pragma unroll
        for (int j = 0; j < SEGW; j++) {
            const uint32_t h = __shfl_sync(0xffffffffu, hv, j);
            asm volatile("{.reg .pred p; setp.ne.u32 p, %3, 0; @p ld.relaxed.gpu.global.v2.b64 {%0,%1}, [%2];}"
                         : "+l"(ea_[j]), "+l"(eb_[j]) : "l"(ob + j * CH + ((h >> 12) & 0xfff)), "r"(pend & (1u << j)) : "memory");
        }
    }
    TS(13);
    uint4 en[SEGW];
#pragma unroll
    for (int j = 0; j < SEGW; j++) {
        en[j] = make_uint4((uint32_t)ea_[j], (uint32_t)(ea_[j] >> 32), (uint32_t)eb_[j], (uint32_t)(eb_[j] >> 32));
        uint32_t rank;
        asm volatile("{.reg .pred p; setp.ne.u32 p, %2, 0; mov.u32 %0, 0; @p atom.shared.add.u32 %0, [%1], 1;}"
                     : "=r"(rank) : "r"(sm + O_NCNT + ((en[j].y >> 14) & 0x3fc)), "r"(have & (1u << j)) : "memory");
        en[j].w = __byte_perm(en[j].w, rank, 0x5410);
    }
    auto fresh = [&](const uint4& e) { return (((e.y ^ tag) | (e.w ^ tag)) >> 24) == 0; };
    const bool longseg = __any_sync(0xffffffffu, (hv & 0xfff) > 32);
    if (longseg) {
        for (int j = 0; j < SEGW; j++) {
            const uint32_t h = __shfl_sync(0xffffffffu, hv, j);
            for (int i = 32; i + lane < (h & 0xfff); i += 32) {
                uint4 e;
                int it = 0;
                do { e = ld_rlx128(ob + j * CH + ((h >> 12) & 0xfff) + i); spin_check(it++); } while (!fresh(e));
                atoms_add(sm + O_NC2 + ((e.y >> 14) & 0x3fc), 1);
            }
        }
    }
    __syncthreads();
    TS(4);
    int total;
    {
        int v[3], sum = 0;
#pragma unroll
        for (int i = 0; i < 3; i++) {
            const int l = lane * 3 + i;
            v[i] = (l * G + b < NN) ? max(1, (lds32(sm + O_NCNT + 4 * l) + lds32(sm + O_NC2 + 4 * l) + 7) >> 3) : 0;
            sum += v[i];
        }
        int e = warp_incl(sum, lane);
        total = __shfl_sync(0xffffffffu, e, 31);
        e -= sum;
#pragma unroll
        for (int i = 0; i < 3; i++) { if (lane * 3 + i < NLOC) sts32(sm + O_NOFF + 4 * (lane * 3 + i), e | ((v[i] - 1) << 16)); e += v[i]; }
        __syncwarp();
    }
    const int gbase = (lds32(sm + O_SUM) >> 3) + (NLOC + 5) * b + 1;
    const bool big = total > CAPB;
    auto place = [&](uint4 e, int l, uint32_t o, int rank, bool on) {
        e.w = (e.w & 0xffffu) | (rank == (int)(o >> 16) * 8 ? (uint32_t)(l * G + b + 1) << 16 : 0u);
        const int idx = (o & 0xffff) * 8 + rank;
        if (on && !big) sts128(sm + O_L + idx * 16, e);
        if (on && big) {
            unsigned short* p = (unsigned short*)(gs->list + (gbase + (idx >> 3)) * 8);
            const int c = idx & 7, c2 = (c >> 1) * 4 + (c & 1);
            p[c2] = e.x; p[c2 + 2] = e.x >> 16; ((unsigned char*)p)[32 + c2] = e.y; p[17 + (c & 6)] = gbase + (idx >> 3);
            p[32 + c] = e.z; p[40 + c] = e.z >> 16; p[48 + c] = e.w; p[56 + c] = e.w >> 16;
        }
    };
    {
        uint32_t o[SEGW];
#pragma unroll
        for (int j = 0; j < SEGW; j++) o[j] = lds32(sm + O_NOFF + ((en[j].y >> 14) & 0x3fc));
        if (!big) {
#pragma unroll
            for (int j = 0; j < SEGW; j++) place(en[j], (en[j].y >> 16) & 0xff, o[j], en[j].w >> 16, have >> j & 1);
        } else {
#pragma unroll
            for (int j = 0; j < SEGW; j++) place(en[j], (en[j].y >> 16) & 0xff, o[j], en[j].w >> 16, have >> j & 1);
        }
    }
#pragma unroll
    for (int i = t; i < NLOC * 8; i += NT) {
        const int l = i >> 3, p = lds32(sm + O_NCNT + 4 * l) + lds32(sm + O_NC2 + 4 * l) + (i & 7);
        const uint32_t o = lds32(sm + O_NOFF + 4 * l);
        place(make_uint4(0, 0, 0, 0), l, o, p, l * G + b < NN && p < (int)(o >> 16) * 8 + 8);
    }
    if (longseg) {
        for (int j = 0; j < SEGW; j++) {
            const uint32_t h = __shfl_sync(0xffffffffu, hv, j);
            for (int i = 32; i + lane < (h & 0xfff); i += 32) {
                const uint4 e = ld_rlx128(ob + j * CH + ((h >> 12) & 0xfff) + i);
                const int l = (e.y >> 16) & 0xff;
                place(e, l, lds32(sm + O_NOFF + 4 * l), lds32(sm + O_NCNT + 4 * l) + atoms_add(sm + O_NCUR + 4 * l, 1), true);
            }
        }
    }
    if (w < 8) {
#pragma unroll
        for (int p = 0; p < 5; p++) ldsm4t(wr[p], sm + O_WRS + (2 * p + (w >> 2)) * 2048 + sw);
    }
    if (t < NPOOL) {
        const uint32_t o = lds32(sm + O_NOFF + 4 * (NPRIV + t)), p = gbase + (o & 0xffff);
        gs->info[b * NPOOL + t] = p | (p + (o >> 16) + 1) << 16;
    }
    int pos = gbase + (w & 1 ? lds32(sm + O_NOFF + 4 * NS0) & 0xffff : 0);
    int end = gbase + (lds32(sm + O_NOFF + 4 * (w & 1 ? NPRIV : NS0)) & 0xffff);
    __syncthreads();
    TS(5);
    if (t >= NT - NSLOT) {
        const uint32_t sb = sm + O_RING + (NT - 1 - t) * SLOT;
        sts128(sb + S_C + 64, make_uint4(0, 0, 0, 0));
        mbar_init(sb + S_FULL, 64); mbar_init(sb + S_EMPTY, 8);
    }
    if (!big) {
        uint32_t* lp = (uint32_t*)(gs->list + gbase * 8) + (g < 2 ? q * 2 + g : lane);
        const uint32_t sel = g == 2 ? 0x5420 : 0x3210;
        for (int c = w; c * 4 < total; c += 48) {
            uint32_t v[4][4];
#pragma unroll
            for (int k = 0; k < 4; k++) if ((c + 12 * k) * 4 < total) ldsm4t(v[k], sm + O_L + (c + 12 * k) * 512 + lane * 16);
#pragma unroll
            for (int k = 0; k < 4; k++)
                if ((c + 12 * k) * 4 < total) {
#pragma unroll
                    for (int i = 0; i < 4; i++) lp[((c + 12 * k) * 4 + i) * 32] = __byte_perm(v[k][i], gbase + (c + 12 * k) * 4 + i, sel);
                }
        }
    }
    __syncthreads();
    TS(6);

    if (w >= 8) {
        asm volatile("setmaxnreg.dec.sync.aligned.u32 " STR(PREG) ";");
        const int st = w & 1, h = (w >> 1) & 1;
        const uint32_t ring = sm + O_RING;
        if (q < 3 && 2 * g + h < NSLOT) cpa16z(ring + (2 * g + h) * SLOT + S_H + st * 48 + q * 16, gs->list + (pos + 2 * g + h) * 8 + q, 1);
        if (t == NT - 1) {
            asm volatile("fence.proxy.async.shared::cta;" ::: "memory");
            tma2d(sm + O_L, &m_w1, 64, 192, sm + O_WBB);
            asm volatile("red.release.gpu.global.add.u32 [%0], 1;" ::"l"(&gs->pub) : "memory");
        }
        const uint32_t xoff = opaque((st * 8 + 2 * mat) * 1024 + ((r ^ (2 * mat)) * 16), lane);
        const uint32_t aoff = opaque(r < 4 ? S_A + (st * 8 + 2 * mat + (r >> 1)) * 32 + (((r & 1) ^ (mat >> 1)) * 16)
                                           : r == 4 ? S_C + st * 80 + mat * 16 : S_H + st * 48 + mat * 16, lane);
        const uint32_t hoff = opaque(S_H + st * 48 + mat * 8, lane), hoff2 = opaque(S_H + st * 48 + 32 + mat * 4, lane);
        const uint32_t psel = opaque(r >= 4 ? 0xcc76 : (r & 2) ? 0xd532 : 0xc410, lane);
        const uint32_t amul = opaque(r < 4 ? 32 : (r == 4 || (r == 5 && mat < 3)) ? 128 : 0, lane);
        const bool fut = opaque(r == 5, lane);
        const uint64_t xl = __shfl_sync(0xffffffffu, (uint64_t)(x - 1024 + r * 16), lane);
        const uint64_t al = __shfl_sync(0xffffffffu, r < 4 ? (uint64_t)(ea - 32 + (r & 1) * 16) : (uint64_t)(gs->list + mat + (r == 4 ? 4 : 0)), lane);
        pos = __reduce_max_sync(0xffffffffu, pos) + NSLOT + h; end = __reduce_max_sync(0xffffffffu, end);

        int ev = h ? end : end - 12, state = h ? 2 : 0, tk = 0, nr = 0;
        uint32_t inf = 0;
        auto take = [&]() {
            int v = 0;
            asm volatile("{.reg .pred p; setp.eq.s32 p, %2, 0; @p atom.relaxed.gpu.global.add.u32 %0, [%1], 1;}" : "+r"(v) : "l"(&gs->ticket), "r"(lane) : "memory");
            return v;
        };
        auto resolve = [&]() {
            const int k = __reduce_max_sync(0xffffffffu, tk);
            inf = 0;
            if (NPRIV * G + k < NN) { const int l = k / G; inf = __ldcg(&gs->info[(k - l * G) * NPOOL + l]); tk = take(); }
        };
        uint32_t so = ring + h * SLOT, ph = 1;
        auto advance = [&]() {
            so += 2 * SLOT;
            if (so >= ring + NSLOT * SLOT) { so -= NSLOT * SLOT; ph ^= 1; }
        };
        asm volatile("cp.async.wait_all;" ::: "memory");
        __syncwarp();
        while (true) {
            mbar_wait(so + S_EMPTY, ph);
            const uint2 e = lds64(so + hoff);
            const uint32_t e2 = lds32(so + hoff2);
            if (__any_sync(0xffffffffu, e2 < 0x10000u)) break;
            const uint32_t s0 = e.x & 0xffffu, s1 = e.x >> 16;
            uint32_t id;
            asm("prmt.b32 %0, %1, %2, %3;" : "=r"(id) : "r"(e.y), "r"(e2), "r"(psel));
            if (fut) id = max(pos, 0);
            const char* g0 = (const char*)madw(s0, 1024, xl);
            const char* g1 = (const char*)madw(s1, 1024, xl);
            const char* ga = (const char*)madw(id, amul, al);
            const uint32_t d0 = so + xoff, d1 = d0 ^ 16;
            if (amul) cpa16z(so + aoff, ga, id);
#pragma unroll
            for (int k = 0; k < 8; k++) cpa16z(d0 + k * 128, g0 + k * 128, s0);
#pragma unroll
            for (int k = 0; k < 8; k++) cpa16z(d1 + 1024 + k * 128, g1 + k * 128, s1);
            asm volatile("cp.async.mbarrier.arrive.noinc.shared::cta.b64 [%0];" ::"r"(so + S_FULL) : "memory");
            advance();
            pos += 2;
            if (pos >= ev) {
                if (state == 0) { ev = end - 6; state = 1; tk = take(); }
                else if (state == 1) {
                    for (int it = 0; __any_sync(0xffffffffu, ld_acq(&gs->pub) < (unsigned)G); it++) spin_check(it);
                    resolve();
                    ev = end; state = 2;
                } else {
                    do {
                        const uint32_t mb = sm + O_MB + st * 128 + (nr & 15) * 8;
                        uint32_t rg;
                        nr++;
                        if (h == 0) {
                            rg = __reduce_max_sync(0xffffffffu, inf);
                            asm volatile("st.release.cta.shared.b64 [%0], %1;" ::"r"(mb), "l"(rg | (uint64_t)nr << 32) : "memory");
                            if (rg) resolve();
                        } else {
                            uint64_t m;
                            for (int it = 0;; it++) {
                                asm volatile("ld.acquire.cta.shared.b64 %0, [%1];" : "=l"(m) : "r"(mb) : "memory");
                                if (__all_sync(0xffffffffu, (int)(m >> 32) == nr)) break;
                                spin_check(it);
                            }
                            rg = __reduce_max_sync(0xffffffffu, (uint32_t)m);
                        }
                        pos += (rg & 0xffff) - end; end = rg >> 16;
                        if (!rg) pos = -(1 << 30);
                    } while (pos >= end);
                    ev = end;
                }
            }
        }
        TSW(8 + st);
        for (bool go = true; go;) {
            if (lane == 0) sts32(so + S_C + st * 80 + 48, META_END);
            mbar_arrive(so + S_FULL);
            advance();
            for (int it = 0; !__all_sync(0xffffffffu, mbar_test(so + S_EMPTY, ph)); it++) {
                if (__any_sync(0xffffffffu, lds32(sm + O_END))) { go = false; break; }
                __nanosleep(40);
                spin_check(it);
            }
        }
        asm volatile("cp.async.wait_all;" ::: "memory");
    } else {
        asm volatile("setmaxnreg.inc.sync.aligned.u32 " STR(CREG) ";");
        const uint32_t xa = opaque(((mat >> 1) * 8 + r) * 1024 + (w >> 2) * 128 + (((2 * (w & 3) + (mat & 1)) ^ r) * 16), lane);
        const uint32_t aa = opaque(S_A + ((mat >> 1) * 8 + r) * 32 + (((mat & 1) ^ (r >> 2)) * 16), lane);
        const uint32_t ya = opaque(S_C + (mat & 1) * 80 + (mat >> 1) * 16, lane);
        const uint32_t yc = opaque(S_C + (mat < 2 ? mat * 80 + 32 : (r >> 2) == (mat & 1) ? (mat & 1) * 80 + (r & 3) * 16 : 64), lane);
        const uint32_t msel = opaque(lane == 12 ? 0x4410 : lane == 28 ? 0x5400 : lane < 16 ? 0x4444 : 0x0000, lane);
        const uint32_t pw = sm + O_P + w * PW;
        uint32_t fa[2], oh[8], eb[3];
#pragma unroll
        for (int S = 0; S < 2; S++) {
            const int c = r ^ (S * 4);
            int o, tr = -1;
            if (mat < 2) { if (c < 3) o = P_1P0 + 2 * c * PSBO; else if (c == 3) tr = 6; else if (c < 7) o = P_1P1 + 2 * (c - 4) * PSBO; else o = P_0P0; }
            else { if (c < 3) o = P_1P2 + 2 * c * PSBO; else if (c == 3) o = P_0P1; else tr = 2 * (c - 4) + 1; }
            fa[S] = opaque((tr < 0) ? pw + o + (mat & 1) * 128 : sm + O_TRASH + ((((pw - sm - O_TRASH) >> 4) + tr) & 7) * 16, lane);
        }
#pragma unroll
        for (int c = 0; c < 8; c++) oh[c] = opaque(g == c ? 0x3F803F80u : 0u, lane);
#pragma unroll
        for (int k = 0; k < 3; k++) {
            const unsigned short* ep = (const unsigned short*)eps + (g & 3) * 9 + (q & 1) * 6 + k;
            eb[k] = 0;
            if ((g & 3) < 3 && (q >> 1) == (g >> 2)) eb[k] = ep[0] | ((q & 1) ? 0u : (uint32_t)ep[3] << 16);
        }
        const bool s1 = opaque(q >> 1, lane), l0 = opaque(lane == 0, lane);
        Acc A;
#pragma unroll
        for (int i = 0; i < 4; i++) { A.p00[i] = A.p110[i] = A.p10[0][i] = A.p10[1][i] = A.p10[2][i] = 0; A.t01[i] = A.m[0][i] = A.m[1][i] = A.m[2][i] = 0.f; }
        int slot = 0;
        bool w1ok = false;
        uint32_t so = sm + O_RING, ph = 0, a[4];
        mbar_wait(so + S_FULL, 0);
        ldsm4(a, so + aa);
        TS(7);
        while (true) {
            uint32_t yb[8], f[4][4], R[5][4];
            ldsm4t(f[0], so + xa);
            ldsm4(yb + 4, so + yc);
#pragma unroll
            for (int m = 1; m < 4; m++) ldsm4t(f[m], so + xa + m * 256);
            ldsm4(yb, so + ya);
            if (l0) mbar_arrive(so + S_EMPTY);
            so += SLOT;
            if (so == sm + O_RING + NSLOT * SLOT) { so = sm + O_RING; ph ^= 1; }
#pragma unroll
            for (int p = 0; p < 5; p++) {
                float c[4];
                mma16z(c, wr[p], a[0], a[1]); R[p][0] = pack(c[0], c[1]); R[p][1] = pack(c[2], c[3]);
                mma16z(c, wr[p], a[2], a[3]); R[p][2] = pack(c[0], c[1]); R[p][3] = pack(c[2], c[3]);
            }
            uint32_t ok;
            asm volatile("{\n.reg .pred p;\nmbarrier.test_wait.parity.shared::cta.b64 p, [%5], %6;\nselp.u32 %4, 1, 0, p;\n"
                         "@p ldmatrix.sync.aligned.m8n8.x4.shared.b16 {%0,%1,%2,%3}, [%7];\n}"
                         : "+r"(a[0]), "+r"(a[1]), "+r"(a[2]), "+r"(a[3]), "=r"(ok) : "r"(so + S_FULL), "r"(ph), "r"(so + aa) : "memory");
            uint32_t mt = __reduce_or_sync(0xffffffffu, __byte_perm(yb[6], yb[7], msel));
            uint32_t u[4];
#pragma unroll
            for (int i = 0; i < 4; i++) {
                A.p00[i] = hfma(f[0][i], R[0][i], A.p00[i]);
                u[i] = hmul(f[0][i], R[2][i]);
            }
            mma16(A.t01, u[0], u[1], u[2], u[3], yb[6], yb[7]);
#pragma unroll
            for (int k = 0; k < 3; k++) {
#pragma unroll
                for (int i = 0; i < 4; i++) {
                    A.p10[k][i] = hfma(f[1 + k][i], R[3][i], A.p10[k][i]);
                    u[i] = hmul(f[1 + k][i], R[4][i]);
                }
                mma16(A.m[k], u[0], u[1], u[2], u[3], yb[6], yb[7]);
            }
#pragma unroll
            for (int i = 0; i < 4; i++) {
                uint32_t sdot = hfma(f[3][i], yb[4 + (i >> 1)], hfma(f[2][i], yb[2 + (i >> 1)], hmul(f[1][i], yb[i >> 1])));
                A.p110[i] = hfma(sdot, R[1][i], A.p110[i]);
            }
            if (mt == 0) {
                if (!ok) { mbar_wait(so + S_FULL, ph); ldsm4(a, so + aa); }
                continue;
            }
            const bool last = mt == META_END * 0x10001u;
            while (true) {
                if ((mt & 0xffff) - 1 < NN) {
                    sts32(sm + O_NODE + 4 * slot, mt & 0xffff);
                    flush<0>(A, fa[0] + (slot & 7) * 16 + (slot >> 3) * PSBO, oh, eb, s1);
                    slot++;
                }
                mt &= 0xffff0000u;
                if (mt - 1 < NN * 0x10000u && slot < 16) {
                    sts32(sm + O_NODE + 4 * slot, mt >> 16);
                    flush<1>(A, fa[1] + (slot & 7) * 16 + (slot >> 3) * PSBO, oh, eb, s1);
                    slot++; mt = 0;
                }
                if (slot < 16 && !last) break;
                if (last) sts32(sm + O_END, 1);
                if (slot > 0) {
                    if (!w1ok) { mbar_wait(sm + O_WBB, 0); w1ok = true; }
                    asm volatile("fence.proxy.async.shared::cta;" ::: "memory");
                    bar_sync(1, 256);
                    float d0[8], d1[24];
                    const uint64_t db = (uint64_t)(((sm + O_P) >> 4) & 0x3fff) | (8ull << 16) | ((uint64_t)(PSBO / 16) << 32);
                    const uint64_t da = (uint64_t)(((sm + O_W1 + (w >> 2) * 49152) >> 4) & 0x3fff) | (1ull << 16) | (64ull << 32) | (1ull << 62);
                    asm volatile("wgmma.fence.sync.aligned;" ::: "memory");
#pragma unroll
                    for (int k = 0; k < 16; k++) wg_rs16(d0, w0[k], db + (((k & 7) * PW + ((k >> 3) ? P_0P1 : P_0P0)) >> 4), k);
                    asm volatile("wgmma.commit_group.sync.aligned;" ::: "memory");
#pragma unroll
                    for (int k = 0; k < 24; k++)
                        wg_ss48(d1, da + k * 128, db + (((k & 7) * PW + ((k >> 3) == 0 ? P_1P0 : (k >> 3) == 1 ? P_1P1 : P_1P2)) >> 4), k);
                    asm volatile("wgmma.commit_group.sync.aligned;" ::: "memory");
                    int nd[4];
#pragma unroll
                    for (int it = 0; it < 4; it++) nd[it] = lds32(sm + O_NODE + 4 * (it * 4 + mat));
                    asm volatile("wgmma.wait_group.sync.aligned 1;" ::: "memory");
#pragma unroll
                    for (int i = 0; i < 8; i++) asm volatile("" : "+f"(d0[i])::"memory");
                    uint32_t o[4][4];
                    float gt[8];
#pragma unroll
                    for (int i = 0; i < 8; i++) gt[i] = __fdividef(1.f, 1.f + __expf(-d0[i]));
#pragma unroll
                    for (int i = 0; i < 4; i++) o[0][i] = pack(d0[2 * i], d0[2 * i + 1]);
#pragma unroll
                    for (int i = 0; i < 8; i++) asm volatile("" : "+f"(gt[i])::"memory");
                    asm volatile("wgmma.wait_group.sync.aligned 0;" ::: "memory");
#pragma unroll
                    for (int i = 0; i < 24; i++) asm volatile("" : "+f"(d1[i])::"memory");
                    bar_sync(1, 256);
#pragma unroll
                    for (int i = 0; i < 4; i++)
#pragma unroll
                        for (int j = 0; j < 3; j++) o[1 + j][i] = pack(d1[8 * j + 2 * i] * gt[2 * i], d1[8 * j + 2 * i + 1] * gt[2 * i + 1]);
                    const uint32_t sg = sm + O_P + (w & 4) * PW + ((mat >> 1) * 8 + r) * 128 + (((2 * (w & 3) + (mat & 1)) ^ r) * 16);
#pragma unroll
                    for (int j = 0; j < 4; j++) stsm4t(sg + j * PW, o[j][0], o[j][1], o[j][2], o[j][3]);
                    bar_sync(2 + (w >> 2), 128);
                    uint4 v[4];
#pragma unroll
                    for (int it = 0; it < 4; it++) v[it] = lds128(pw + (it * 4 + mat) * 128 + ((r ^ ((it * 4 + mat) & 7)) * 16));
                    char* op = out - 1024 + (w & 3) * 256 + (w >> 2) * 128 + r * 16;
#pragma unroll
                    for (int it = 0; it < 4; it++) if (it * 4 + mat < slot) *(uint4*)(op + (size_t)nd[it] * 1024) = v[it];
                    __syncwarp();
                    slot = 0;
                }
                if (last) break;
            }
            if (last) break;
            if (!ok) { mbar_wait(so + S_FULL, ph); ldsm4(a, so + aa); }
        }
        TS(10);
        if (t == 0) {
            __threadfence();
            if (atomicInc(&gs->done, G - 1) == G - 1) { gs->pub = 0; gs->ticket = 0; gs->epoch = epoch + 1; }
        }
    }
}

typedef CUresult (*EncFn)(CUtensorMap*, CUtensorMapDataType, cuuint32_t, void*, const cuuint64_t*, const cuuint64_t*,
                          const cuuint32_t*, const cuuint32_t*, CUtensorMapInterleave, CUtensorMapSwizzle,
                          CUtensorMapL2promotion, CUtensorMapFloatOOBfill);

void make_map(EncFn fn, CUtensorMap* m, void* p, int rows, int cols, int brows) {
    cuuint64_t dims[2] = {(cuuint64_t)cols, (cuuint64_t)rows}, strides[1] = {(cuuint64_t)cols * 2};
    cuuint32_t box[2] = {64, (cuuint32_t)brows}, es[2] = {1, 1};
    fn(m, CU_TENSOR_MAP_DATA_TYPE_BFLOAT16, 2, p, dims, strides, box, es, CU_TENSOR_MAP_INTERLEAVE_NONE,
       CU_TENSOR_MAP_SWIZZLE_128B, CU_TENSOR_MAP_L2_PROMOTION_NONE, CU_TENSOR_MAP_FLOAT_OOB_FILL_NONE);
}

}

extern "C" void kernel_launch(void* const* d_in, const int* in_sizes, int n_in, void* d_out, int out_size) {
    static EncFn enc = nullptr;
    static void* scratch = nullptr;
    if (!enc) {
        void* fn = nullptr;
        cudaDriverEntryPointQueryResult qr;
        cudaGetDriverEntryPoint("cuTensorMapEncodeTiled", &fn, cudaEnableDefault, &qr);
        enc = (EncFn)fn;
        cudaGetSymbolAddress(&scratch, g_scratch);
        cudaFuncSetAttribute(tp_kernel, cudaFuncAttributeMaxDynamicSharedMemorySize, SMEM_BYTES);
    }
    CUtensorMap m_wr, m_w0, m_w1;
    make_map(enc, &m_wr, d_in[5], 16, 640, 16);
    make_map(enc, &m_w0, d_in[6], 256, 128, 256);
    make_map(enc, &m_w1, d_in[7], 384, 128, 192);
    tp_kernel<<<G, NT, SMEM_BYTES>>>((const int4*)d_in[4], (const char*)d_in[3], (const char*)d_in[1], (Scratch*)scratch,
                                     (const char*)d_in[0], (const char*)d_in[2], (const __nv_bfloat16*)d_in[8], (char*)d_out,
                                     m_wr, m_w0, m_w1);
}
```

```cpp
#include <cuda_runtime.h>
#include <cuda_bf16.h>
#include <cuda.h>
#include <stdint.h>

namespace {

constexpr int NN = 10000;
constexpr int NE = 320000;
constexpr int G = 132;
constexpr int NT = 384;
constexpr int CH = 2432;
constexpr int NLOC = (NN + G - 1) / G;
#define NPOOL 5
constexpr int NPAIR = NLOC / 2, NPRIV = NPAIR - NPOOL;
constexpr int SEGW = 11;
constexpr int HSTR = 160;
constexpr uint32_t META_END = 0x3fff;

#define NSLOT 5
#define PREFETCH 0
#define W1EARLY 1
#define CREG 216
#define PREG 72
#define STR2(x) #x
#define STR(x) STR2(x)

constexpr int S_A = 16384, S_C = S_A + 512, S_FULL = S_C + 144, S_EMPTY = S_FULL + 8, S_H = S_C + 160, SLOT = 17152;

constexpr int PSBO = 272;
constexpr int PB1 = 5 * PSBO + 256, PB0 = PSBO + 256;
constexpr int P_1P0 = 0, P_1P1 = PB1, P_0P1 = 2 * PB1, P_0P0 = P_0P1 + PB0, P_1P2 = P_0P0 + PB0;
constexpr int PW = P_1P2 + PB1;

constexpr int O_W1 = 0;
constexpr int O_P = 98304;
constexpr int O_RING = O_P + 8 * PW;
constexpr int O_W0S = O_P + CH * 16, O_WRS = O_W0S + 65536;
constexpr int O_BCNT = O_WRS + 20480, O_NCNT = O_BCNT + 544, O_NC2 = O_NCNT + 320, O_NCUR = O_NC2 + 320;
constexpr int O_BOFF = O_NCUR + 320, O_KEY = O_BOFF + 544, O_SORT = O_KEY + 320, O_NOFF = O_SORT + 320;
constexpr int O_TRASH = O_RING + 5 * SLOT;
constexpr int O_WBA = O_TRASH + 512, O_WBB = O_WBA + 8, O_WBC = O_WBA + 16, O_NODE = O_WBA + 32;
constexpr int O_SUM = O_NODE + 64, O_MB = O_SUM + 16;
constexpr int SMEM_BYTES = O_MB + 256;
constexpr int O_L = O_P - 24576;
constexpr int CAPT = (O_W0S - O_L) / 256;
constexpr int NTILE = NE / 8 + G * (NLOC + 5) + 1;
static_assert(SMEM_BYTES <= 232448 && NSLOT == 5 && CH * 10 <= 24576 && CAPT % 2 == 0 && NTILE < 65536, "smem");
static_assert(O_W0S % 1024 == 0 && O_BCNT >= O_RING + 4 * SLOT && O_NOFF + 640 <= O_RING + 4 * SLOT + S_A, "layout");
static_assert(G * CH >= NE && NE % 8 == 0 && CH < 4096, "chunks");
static_assert(SEGW * (NT / 32) == G, "segments");
static_assert(NLOC % 4 == 0 && NLOC <= 80 && NLOC * 4 <= NT && NN < META_END && NPRIV >= 24, "scan width");

struct __align__(128) Scratch {
    uint4 list[NTILE * 16];
    uint4 outbox[G * CH];
    uint32_t hdr[G * HSTR];
    uint32_t info[G * NPOOL];
    unsigned epoch, done, pad0[30], pub, pad1[31], ticket;
};
__device__ Scratch g_scratch;
#define TS(i)
#define TSW(i)

constexpr int SPIN_LIMIT = 1 << 24;

__device__ __forceinline__ void mbar_init(uint32_t a, int c) { asm volatile("mbarrier.init.shared::cta.b64 [%0], %1;" ::"r"(a), "r"(c) : "memory"); }
__device__ __forceinline__ void mbar_expect(uint32_t a, int b) { asm volatile("mbarrier.arrive.expect_tx.shared::cta.b64 _, [%0], %1;" ::"r"(a), "r"(b) : "memory"); }
__device__ __forceinline__ void mbar_arrive(uint32_t a) { asm volatile("mbarrier.arrive.shared::cta.b64 _, [%0];" ::"r"(a) : "memory"); }
__device__ __forceinline__ void mbar_wait(uint32_t a, uint32_t ph) {
    asm volatile("{\n.reg .pred p, q;\n.reg .u32 it;\n"
                 "mbarrier.try_wait.parity.shared::cta.b64 p, [%0], %1;\n"
                 "@p bra DONE;\n"
                 "mov.u32 it, 0;\n"
                 "LOOP:\n"
                 "mbarrier.try_wait.parity.shared::cta.b64 p, [%0], %1;\n"
                 "@p bra DONE;\n"
                 "add.u32 it, it, 1;\n"
                 "setp.gt.u32 q, it, %2;\n"
                 "@q trap;\n"
                 "bra LOOP;\n"
                 "DONE:\n}" ::"r"(a), "r"(ph), "n"(SPIN_LIMIT) : "memory");
}
__device__ __forceinline__ void spin_check(int it) {
    asm volatile("{\n.reg .pred q;\nsetp.gt.s32 q, %0, %1;\n@q trap;\n}" ::"r"(it), "n"(SPIN_LIMIT));
}
__device__ __forceinline__ void tma2d(uint32_t dst, const CUtensorMap* m, int c0, int c1, uint32_t bar) {
    asm volatile("cp.async.bulk.tensor.2d.shared::cluster.global.mbarrier::complete_tx::bytes [%0], [%1, {%3, %4}], [%2];"
                 ::"r"(dst), "l"(m), "r"(bar), "r"(c0), "r"(c1) : "memory");
}
__device__ __forceinline__ uint32_t mbar_test(uint32_t a, uint32_t ph) {
    uint32_t ok;
    asm volatile("{\n.reg .pred p;\nmbarrier.test_wait.parity.shared::cta.b64 p, [%1], %2;\nselp.u32 %0, 1, 0, p;\n}" : "=r"(ok) : "r"(a), "r"(ph) : "memory");
    return ok;
}
__device__ __forceinline__ void cpa16z(uint32_t d, const void* g, uint32_t v) {
    asm volatile("{\n.reg .pred p;\nsetp.eq.u32 p, %2, 0;\ncp.async.cg.shared.global [%0], [%1], 16, p;\n}" ::"r"(d), "l"(g), "r"(v) : "memory");
}
__device__ __forceinline__ void ldsm4(uint32_t* r, uint32_t a) { asm volatile("ldmatrix.sync.aligned.m8n8.x4.shared.b16 {%0,%1,%2,%3}, [%4];" : "=r"(r[0]), "=r"(r[1]), "=r"(r[2]), "=r"(r[3]) : "r"(a) : "memory"); }
__device__ __forceinline__ void ldsm4t(uint32_t* r, uint32_t a) { asm volatile("ldmatrix.sync.aligned.m8n8.x4.trans.shared.b16 {%0,%1,%2,%3}, [%4];" : "=r"(r[0]), "=r"(r[1]), "=r"(r[2]), "=r"(r[3]) : "r"(a) : "memory"); }
__device__ __forceinline__ void stsm4t(uint32_t a, uint32_t r0, uint32_t r1, uint32_t r2, uint32_t r3) { asm volatile("stmatrix.sync.aligned.m8n8.x4.trans.shared.b16 [%0], {%1,%2,%3,%4};" ::"r"(a), "r"(r0), "r"(r1), "r"(r2), "r"(r3) : "memory"); }
__device__ __forceinline__ void stsm2t(uint32_t a, uint32_t r0, uint32_t r1) { asm volatile("stmatrix.sync.aligned.m8n8.x2.trans.shared.b16 [%0], {%1,%2};" ::"r"(a), "r"(r0), "r"(r1) : "memory"); }
__device__ __forceinline__ void mma16(float* d, const uint32_t* a, uint32_t b0, uint32_t b1) {
    asm("mma.sync.aligned.m16n8k16.row.col.f32.bf16.bf16.f32 {%0,%1,%2,%3}, {%4,%5,%6,%7}, {%8,%9}, {%0,%1,%2,%3};"
        : "+f"(d[0]), "+f"(d[1]), "+f"(d[2]), "+f"(d[3]) : "r"(a[0]), "r"(a[1]), "r"(a[2]), "r"(a[3]), "r"(b0), "r"(b1));
}
__device__ __forceinline__ void mma8(float* d, uint32_t a0, uint32_t a1, uint32_t b0) {
    asm("mma.sync.aligned.m16n8k8.row.col.f32.bf16.bf16.f32 {%0,%1,%2,%3}, {%4,%5}, {%6}, {%0,%1,%2,%3};"
        : "+f"(d[0]), "+f"(d[1]), "+f"(d[2]), "+f"(d[3]) : "r"(a0), "r"(a1), "r"(b0));
}
__device__ __forceinline__ void mma16z(float* d, const uint32_t* a, uint32_t b0, uint32_t b1) {
    asm("mma.sync.aligned.m16n8k16.row.col.f32.bf16.bf16.f32 {%0,%1,%2,%3}, {%4,%5,%6,%7}, {%8,%9}, {%10,%10,%10,%10};"
        : "=f"(d[0]), "=f"(d[1]), "=f"(d[2]), "=f"(d[3]) : "r"(a[0]), "r"(a[1]), "r"(a[2]), "r"(a[3]), "r"(b0), "r"(b1), "f"(0.f));
}
__device__ __forceinline__ uint32_t pack(float lo, float hi) { uint32_t r; asm("cvt.rn.bf16x2.f32 %0, %1, %2;" : "=r"(r) : "f"(hi), "f"(lo)); return r; }
__device__ __forceinline__ uint32_t hmul(uint32_t a, uint32_t b) { uint32_t r; asm("mul.rn.bf16x2 %0, %1, %2;" : "=r"(r) : "r"(a), "r"(b)); return r; }
__device__ __forceinline__ uint32_t hfma(uint32_t a, uint32_t b, uint32_t c) { uint32_t r; asm("fma.rn.bf16x2 %0, %1, %2, %3;" : "=r"(r) : "r"(a), "r"(b), "r"(c)); return r; }
__device__ __forceinline__ uint4 lds128(uint32_t a) { uint4 v; asm volatile("ld.shared.v4.u32 {%0,%1,%2,%3}, [%4];" : "=r"(v.x), "=r"(v.y), "=r"(v.z), "=r"(v.w) : "r"(a) : "memory"); return v; }
__device__ __forceinline__ void sts128(uint32_t a, uint4 v) { asm volatile("st.shared.v4.u32 [%0], {%1,%2,%3,%4};" ::"r"(a), "r"(v.x), "r"(v.y), "r"(v.z), "r"(v.w) : "memory"); }
__device__ __forceinline__ int lds32(uint32_t a) { int v; asm volatile("ld.shared.u32 %0, [%1];" : "=r"(v) : "r"(a) : "memory"); return v; }
__device__ __forceinline__ void sts32(uint32_t a, int v) { asm volatile("st.shared.u32 [%0], %1;" ::"r"(a), "r"(v) : "memory"); }
__device__ __forceinline__ int atoms_add(uint32_t a, int v) { int r; asm volatile("atom.shared.add.u32 %0, [%1], %2;" : "=r"(r) : "r"(a), "r"(v) : "memory"); return r; }
__device__ __forceinline__ uint32_t ld_acq(const void* p) { uint32_t v; asm volatile("ld.acquire.gpu.global.u32 %0, [%1];" : "=r"(v) : "l"(p) : "memory"); return v; }
__device__ __forceinline__ uint32_t ld_rlx(const void* p) { uint32_t v; asm volatile("ld.relaxed.gpu.global.u32 %0, [%1];" : "=r"(v) : "l"(p) : "memory"); return v; }
__device__ __forceinline__ uint4 ld_rlx128(const void* p) {
    uint64_t a, b;
    asm volatile("ld.relaxed.gpu.global.v2.b64 {%0,%1}, [%2];" : "=l"(a), "=l"(b) : "l"(p) : "memory");
    return make_uint4((uint32_t)a, (uint32_t)(a >> 32), (uint32_t)b, (uint32_t)(b >> 32));
}
__device__ __forceinline__ void st_rlx128(void* p, uint4 v) {
    asm volatile("st.relaxed.gpu.global.v2.b64 [%0], {%1,%2};" ::"l"(p), "l"(v.x | ((uint64_t)v.y << 32)), "l"(v.z | ((uint64_t)v.w << 32)) : "memory");
}
__device__ __forceinline__ void bulk(uint32_t dst, const void* g, int n, uint32_t bar) {
    asm volatile("cp.async.bulk.shared::cluster.global.mbarrier::complete_tx::bytes [%0], [%1], %2, [%3];" ::"r"(dst), "l"(g), "r"(n), "r"(bar) : "memory");
}
__device__ __forceinline__ uint2 lds64(uint32_t a) { uint2 v; asm volatile("ld.shared.v2.u32 {%0,%1}, [%2];" : "=r"(v.x), "=r"(v.y) : "r"(a) : "memory"); return v; }
__device__ __forceinline__ void sts64(uint32_t a, uint32_t x, uint32_t y) { asm volatile("st.shared.v2.u32 [%0], {%1,%2};" ::"r"(a), "r"(x), "r"(y) : "memory"); }
__device__ __forceinline__ uint64_t madw(uint32_t a, uint32_t b, uint64_t c) { uint64_t r; asm("mad.wide.u32 %0, %1, %2, %3;" : "=l"(r) : "r"(a), "r"(b), "l"(c)); return r; }
__device__ __forceinline__ uint32_t opaque(uint32_t v, int lane) { return __shfl_sync(0xffffffffu, v, lane); }
__device__ __forceinline__ void bar_sync(int id, int n) { asm volatile("bar.sync %0, %1;" ::"r"(id), "r"(n) : "memory"); }

__device__ __forceinline__ void wg_rs16(float* d, const uint32_t* a, uint64_t db, int sc) {
    asm volatile("{.reg .pred p; setp.ne.b32 p, %13, 0;\n"
                 "wgmma.mma_async.sync.aligned.m64n16k16.f32.bf16.bf16 {%0,%1,%2,%3,%4,%5,%6,%7}, {%8,%9,%10,%11}, %12, p, 1, 1, 0;}"
                 : "+f"(d[0]), "+f"(d[1]), "+f"(d[2]), "+f"(d[3]), "+f"(d[4]), "+f"(d[5]), "+f"(d[6]), "+f"(d[7])
                 : "r"(a[0]), "r"(a[1]), "r"(a[2]), "r"(a[3]), "l"(db), "r"(sc));
}
__device__ __forceinline__ void wg_ss48(float* d, uint64_t da, uint64_t db, int sc) {
    asm volatile("{.reg .pred p; setp.ne.b32 p, %26, 0;\n"
                 "wgmma.mma_async.sync.aligned.m64n48k16.f32.bf16.bf16 {%0,%1,%2,%3,%4,%5,%6,%7,%8,%9,%10,%11,%12,%13,%14,%15,%16,%17,%18,%19,%20,%21,%22,%23}, %24, %25, p, 1, 1, 1, 0;}"
                 : "+f"(d[0]), "+f"(d[1]), "+f"(d[2]), "+f"(d[3]), "+f"(d[4]), "+f"(d[5]), "+f"(d[6]), "+f"(d[7]),
                   "+f"(d[8]), "+f"(d[9]), "+f"(d[10]), "+f"(d[11]), "+f"(d[12]), "+f"(d[13]), "+f"(d[14]), "+f"(d[15]),
                   "+f"(d[16]), "+f"(d[17]), "+f"(d[18]), "+f"(d[19]), "+f"(d[20]), "+f"(d[21]), "+f"(d[22]), "+f"(d[23])
                 : "l"(da), "l"(db), "r"(sc));
}

__device__ __forceinline__ int warp_incl(int v, int lane) {
#pragma unroll
    for (int o = 1; o < 32; o <<= 1) { int u = __shfl_up_sync(0xffffffffu, v, o); if (lane >= o) v += u; }
    return v;
}

template <bool B> struct Bool { static constexpr bool value = B; };
struct Acc {
    uint32_t p00[4], p110[4], p10[3][4];
    float t01[4], m[3][4];
};

__device__ __forceinline__ void flush(const Acc& A, uint32_t ax, uint32_t ayz, const uint32_t (*oh)[2], const uint32_t* eb) {
    float y[4], z[4];
    const uint32_t mp[4] = {pack(A.m[0][0], A.m[0][1]), pack(A.m[0][2], A.m[0][3]), pack(A.m[1][0], A.m[1][1]), pack(A.m[1][2], A.m[1][3])};
    mma16z(y, A.p10[0], oh[0][0], oh[0][1]);
    mma16z(z, A.p110, oh[3][0], oh[3][1]);
    mma16(y, A.p10[1], oh[1][0], oh[1][1]);
    mma16(z, mp, eb[0], eb[1]);
    mma16(y, A.p10[2], oh[2][0], oh[2][1]);
    mma8(z, pack(A.m[2][0], A.m[2][1]), pack(A.m[2][2], A.m[2][3]), eb[2]);
    mma16(y, A.p00, oh[3][0], oh[3][1]);
    stsm2t(ax, pack(A.t01[0], A.t01[1]), pack(A.t01[2], A.t01[3]));
    stsm4t(ayz, pack(y[0], y[1]), pack(y[2], y[3]), pack(z[0], z[1]), pack(z[2], z[3]));
}

__global__ void __launch_bounds__(NT, 1)
tp_kernel(const int4* __restrict__ dst, const char* __restrict__ src, const char* __restrict__ rhat, Scratch* __restrict__ gs,
          const char* __restrict__ x, const char* __restrict__ ea, const __nv_bfloat16* __restrict__ eps, char* __restrict__ out,
          const __grid_constant__ CUtensorMap m_wr, const __grid_constant__ CUtensorMap m_w0, const __grid_constant__ CUtensorMap m_w1) {
    extern __shared__ __align__(1024) char smem_raw[];
    const uint32_t sm = (uint32_t)__cvta_generic_to_shared(smem_raw);
    const int t = threadIdx.x, w = t >> 5, lane = t & 31, b = blockIdx.x;

    const int e0 = b * CH + t * 4;
    const bool act[2] = {t < CH / 8, t < CH / 8 && e0 + CH / 2 < NE};
    int d[8];
#pragma unroll
    for (int k = 0; k < 2; k++)
        if (act[k]) *(int4*)&d[4 * k] = __ldg(dst + e0 / 4 + k * (CH / 8));
    if (t == NT - 1) {
        const int ne = min(CH, NE - b * CH);
        mbar_init(sm + O_WBA, 1); mbar_init(sm + O_WBB, 1); mbar_init(sm + O_WBC, 1);
        asm volatile("fence.proxy.async.shared::cta;" ::: "memory");
        mbar_expect(sm + O_WBC, ne * 10);
        bulk(sm + O_L, src + b * (CH * 4), ne * 4, sm + O_WBC);
        bulk(sm + O_L + CH * 4, rhat + b * (CH * 6), ne * 6, sm + O_WBC);
        mbar_expect(sm + O_WBA, 86016); mbar_expect(sm + O_WBB, 98304);
        tma2d(sm + O_W0S, &m_w0, 0, 0, sm + O_WBA);
        tma2d(sm + O_W0S + 32768, &m_w0, 64, 0, sm + O_WBA);
        for (int j = 0; j < 10; j++) tma2d(sm + O_WRS + j * 2048, &m_wr, 64 * j, 0, sm + O_WBA);
        for (int j = 0; j < 3; j++) tma2d(sm + O_W1 + j * 24576, &m_w1, 64 * (j >> 1), 192 * (j & 1), sm + O_WBB);
    }
    uint32_t epoch = ld_rlx(&gs->epoch);
    sts32(sm + O_BCNT + 4 * t, 0);
    if (t < 68) sts32(sm + O_SUM + 4 * t, 0);
    __syncthreads();
    int rk[8];
#pragma unroll
    for (int k = 0; k < 2; k++)
        if (act[k]) {
#pragma unroll
            for (int i = 4 * k; i < 4 * k + 4; i++) {
                int loc = d[i] / G, own = d[i] - loc * G;
                d[i] = own | (loc << 16);
                rk[i] = atoms_add(sm + O_BCNT + 4 * own, 1);
            }
        }
    TS(0);
    __syncthreads();
    {
        int v[5], sum = 0;
#pragma unroll
        for (int i = 0; i < 5; i++) { v[i] = (lane * 5 + i < G) ? lds32(sm + O_BCNT + 4 * (lane * 5 + i)) : 0; sum += v[i]; }
        int e = warp_incl(sum, lane) - sum;
#pragma unroll
        for (int i = 0; i < 5; i++) { if (lane * 5 + i < G) sts32(sm + O_BOFF + 4 * (lane * 5 + i), e); e += v[i]; }
        __syncwarp();
    }
    asm volatile("" : "+r"(epoch));
    const uint32_t tag = (epoch + 1) << 24;
    if ((unsigned)(t - 320) < 34u) {
        const uint4 o = lds128(sm + O_BOFF + 16 * (t - 320)), c = lds128(sm + O_BCNT + 16 * (t - 320));
        st_rlx128(&gs->hdr[b * HSTR + 4 * (t - 320)], make_uint4(tag | o.x << 12 | c.x, tag | o.y << 12 | c.y, tag | o.z << 12 | c.z, tag | o.w << 12 | c.w));
    }
#pragma unroll
    for (int k = 0; k < 2; k++)
        if (act[k]) {
#pragma unroll
            for (int i = 4 * k; i < 4 * k + 4; i++) rk[i] += lds32(sm + O_BOFF + 4 * (d[i] & 0xffff));
        }
    mbar_wait(sm + O_WBC, 0);
    TS(11);
#pragma unroll
    for (int k = 0; k < 2; k++)
        if (act[k]) {
            const uint4 s4 = lds128(sm + O_L + (k * (CH / 8) + t) * 16);
            const uint32_t s[4] = {s4.x, s4.y, s4.z, s4.w};
            uint32_t y[6];
#pragma unroll
            for (int i = 0; i < 3; i++) *(uint2*)&y[2 * i] = lds64(sm + O_L + CH * 4 + (k * (CH / 8) + t) * 24 + i * 8);
#pragma unroll
            for (int i = 0; i < 4; i++) {
                uint32_t lo, hi, id = e0 + k * (CH / 2) + i + 1;
                if (i & 1) { lo = __byte_perm(y[(3 * i) / 2], y[(3 * i) / 2 + 1], 0x5432); hi = y[(3 * i) / 2 + 1] >> 16; }
                else { lo = y[(3 * i) / 2]; hi = y[(3 * i) / 2 + 1] & 0xffffu; }
                sts128(sm + O_P + rk[4 * k + i] * 16, make_uint4((s[i] + 1) | (id << 16), (id >> 16) | (d[4 * k + i] & 0xffff0000u) | tag, lo, hi | tag));
            }
        }
    const uint32_t* hp = &gs->hdr[(w * SEGW + min(lane, SEGW - 1)) * HSTR + b];
    uint32_t hv = ld_rlx(hp);
    __syncthreads();
    TS(12);
    {
        constexpr int K = CH / NT;
        uint64_t v[K + 1][2];
        uint4* op = &gs->outbox[b * CH + t];
#pragma unroll
        for (int k = 0; k <= K; k++) asm volatile("ld.shared.v2.b64 {%0,%1}, [%2];" : "=l"(v[k][0]), "=l"(v[k][1]) : "r"(sm + O_P + (t + k * NT) * 16) : "memory");
#pragma unroll
        for (int k = 0; k <= K; k++)
            asm volatile("{.reg .pred p; setp.lt.s32 p, %3, %4; @p st.relaxed.gpu.global.v2.b64 [%0], {%1,%2};}"
                         ::"l"(op + k * NT), "l"(v[k][0]), "l"(v[k][1]), "r"(k < K ? 0 : t), "n"(CH - K * NT) : "memory");
    }
    TS(1);

    for (int it = 0; __any_sync(0xffffffffu, (hv ^ tag) >> 24); it++) { hv = ld_rlx(hp); spin_check(it); }
    TS(3);
    const uint4* ob = gs->outbox + w * SEGW * CH + lane;
    uint64_t ea_[SEGW], eb_[SEGW];
    uint32_t have = 0;
#pragma unroll
    for (int j = 0; j < SEGW; j++) {
        const uint32_t h = __shfl_sync(0xffffffffu, hv, j);
        asm volatile("{.reg .pred p; setp.lt.u32 p, %4, %5; mov.b64 %0, 0; mov.b64 %1, 0;\n"
                     "@p ld.relaxed.gpu.global.v2.b64 {%0,%1}, [%3]; @p or.b32 %2, %2, %6;}"
                     : "=l"(ea_[j]), "=l"(eb_[j]), "+r"(have) : "l"(ob + j * CH + ((h >> 12) & 0xfff)), "r"(lane), "r"(h & 0xfff), "r"(1 << j) : "memory");
    }
    {
        int so = __reduce_add_sync(0xffffffffu, lane < SEGW ? (hv >> 12) & 0xfff : 0);
        if (lane == 0) atoms_add(sm + O_SUM, so);
    }
    const int g = lane >> 2, q = lane & 3, mat = lane >> 3, r = lane & 7;
    const uint32_t sw = (uint32_t)(((2 * (w & 3) + (mat & 1)) ^ r) * 16 + ((mat >> 1) * 8 + r) * 128);
    uint32_t wr[5][4], w0[16][4];
    if (w < 8) {
        mbar_wait(sm + O_WBA, 0);
#pragma unroll
        for (int k = 0; k < 16; k++) ldsm4t(w0[k], sm + O_W0S + (w >> 2) * 32768 + k * 2048 + sw);
    }
    TS(2);
    for (int it = 0;; it++) {
        uint32_t pend = 0;
#pragma unroll
        for (int j = 0; j < SEGW; j++)
            if ((((uint32_t)(ea_[j] >> 32) ^ tag) | ((uint32_t)(eb_[j] >> 32) ^ tag)) >> 24) pend |= 1u << j;
        pend &= have;
        if (!__any_sync(0xffffffffu, pend)) break;
        spin_check(it);
#pragma unroll
        for (int j = 0; j < SEGW; j++) {
            const uint32_t h = __shfl_sync(0xffffffffu, hv, j);
            asm volatile("{.reg .pred p; setp.ne.u32 p, %3, 0; @p ld.relaxed.gpu.global.v2.b64 {%0,%1}, [%2];}"
                         : "+l"(ea_[j]), "+l"(eb_[j]) : "l"(ob + j * CH + ((h >> 12) & 0xfff)), "r"(pend & (1u << j)) : "memory");
        }
    }
    TS(13);
    uint4 en[SEGW];
#pragma unroll
    for (int j = 0; j < SEGW; j++) {
        en[j] = make_uint4((uint32_t)ea_[j], (uint32_t)(ea_[j] >> 32), (uint32_t)eb_[j], (uint32_t)(eb_[j] >> 32));
        uint32_t rank;
        asm volatile("{.reg .pred p; setp.ne.u32 p, %2, 0; mov.u32 %0, 0; @p atom.shared.add.u32 %0, [%1], 1;}"
                     : "=r"(rank) : "r"(sm + O_NCNT + ((en[j].y >> 14) & 0x3fc)), "r"(have & (1u << j)) : "memory");
        en[j].w = __byte_perm(en[j].w, rank, 0x5410);
    }
    auto fresh = [&](const uint4& e) { return (((e.y ^ tag) | (e.w ^ tag)) >> 24) == 0; };
    const bool longseg = __any_sync(0xffffffffu, (hv & 0xfff) > 32);
    if (longseg) {
        for (int j = 0; j < SEGW; j++) {
            const uint32_t h = __shfl_sync(0xffffffffu, hv, j);
            for (int i = 32; i + lane < (h & 0xfff); i += 32) {
                uint4 e;
                int it = 0;
                do { e = ld_rlx128(ob + j * CH + ((h >> 12) & 0xfff) + i); spin_check(it++); } while (!fresh(e));
                atoms_add(sm + O_NC2 + ((e.y >> 14) & 0x3fc), 1);
            }
        }
    }
    __syncthreads();
    TS(4);
    if (t < 80) sts32(sm + O_KEY + 4 * t, t < NLOC ? (lds32(sm + O_NCNT + 4 * t) + lds32(sm + O_NC2 + 4 * t)) << 7 | (127 - t) : 0);
    __syncthreads();
    {
        const int key = lds32(sm + O_KEY + min(t & ~3, 316));
        int rank = 0;
#pragma unroll
        for (int i = 0; i < 5; i++) {
            const uint4 k = lds128(sm + O_KEY + q * 80 + i * 16);
            rank += ((int)k.x > key) + ((int)k.y > key) + ((int)k.z > key) + ((int)k.w > key);
        }
        rank += __shfl_xor_sync(0xffffffffu, rank, 1);
        rank += __shfl_xor_sync(0xffffffffu, rank, 2);
        if (t < NLOC * 4) sts32(sm + O_SORT + 4 * rank, key);
    }
    __syncthreads();
    int total, pos, end;
    const int gbase = (lds32(sm + O_SUM) >> 3) + (NLOC + 5) * b + 1;
    {
        const bool on = lane < NLOC / 4;
        const uint4 k4 = lds128(sm + O_SORT + 16 * (on ? lane : 0));
        const uint32_t k[4] = {k4.x, k4.y, k4.z, k4.w};
        const int n0 = on ? max(1u, (k[0] + 896) >> 10) : 0, n1 = on ? max(1u, (k[2] + 896) >> 10) : 0;
        int e = warp_incl(n0 + n1, lane);
        total = __shfl_sync(0xffffffffu, e, 31);
        end = gbase + __shfl_sync(0xffffffffu, NPRIV & 1 ? e - n1 : e, (NPRIV - 1) / 2);
        pos = gbase;
        e -= n0 + n1;
#pragma unroll
        for (int i = 0; i < 4; i++) {
            const int l = 127 - (k[i] & 127), node = l * G + b;
            if (on) sts64(sm + O_NOFF + 8 * l, (e + (i >> 1) * n0) * 16 + (i & 1) * 8, ((i >> 1 ? n1 : n0) - 1) | (node < NN ? node + 1 : 0) << 16);
        }
        if (w == 0 && on) {
            if (2 * lane >= NPRIV) gs->info[b * NPOOL + 2 * lane - NPRIV] = (gbase + e) | (gbase + e + n0) << 16;
            if (2 * lane + 1 >= NPRIV) gs->info[b * NPOOL + 2 * lane + 1 - NPRIV] = (gbase + e + n0) | (gbase + e + n0 + n1) << 16;
        }
        __syncwarp();
    }
    const bool big = total > CAPT;
    auto place = [&](uint4 e, uint2 o, int rank, bool on) {
        e.w = __byte_perm(e.w, rank == (int)(o.y & 0xffff) * 8 ? o.y : 0u, 0x7610);
        const int idx = o.x + rank + (rank & ~7);
        if (on && !big) sts128(sm + O_L + idx * 16, e);
        if (on && big) {
            unsigned short* p = (unsigned short*)(gs->list + (gbase * 2 + (idx >> 3)) * 8);
            const int c = idx & 7, c2 = 8 + (c >> 1) * 4 + (c & 1);
            p[c] = e.x; p[c2] = e.x >> 16; p[c2 + 2] = e.y;
            p[32 + c] = e.z; p[40 + c] = e.z >> 16; p[48 + c] = e.w; p[56 + c] = e.w >> 16;
        }
    };
    {
        uint2 o[SEGW];
#pragma unroll
        for (int j = 0; j < SEGW; j++) o[j] = lds64(sm + O_NOFF + ((en[j].y >> 13) & 0x3f8));
        if (!big) {
#pragma unroll
            for (int j = 0; j < SEGW; j++) place(en[j], o[j], en[j].w >> 16, have >> j & 1);
        } else {
#pragma unroll
            for (int j = 0; j < SEGW; j++) place(en[j], o[j], en[j].w >> 16, have >> j & 1);
        }
    }
    if (t < NLOC * 4) {
        const uint2 o = lds64(sm + O_NOFF + 8 * (t >> 2));
#pragma unroll 1
        for (int p = (lds32(sm + O_KEY + (t & ~3)) >> 7) + q; p < (int)(o.y & 0xffff) * 8 + 8; p += 4) place(make_uint4(0, 0, 0, 0), o, p, true);
    }
    if (longseg) {
        for (int j = 0; j < SEGW; j++) {
            const uint32_t h = __shfl_sync(0xffffffffu, hv, j);
            for (int i = 32; i + lane < (h & 0xfff); i += 32) {
                const uint4 e = ld_rlx128(ob + j * CH + ((h >> 12) & 0xfff) + i);
                const int l = (e.y >> 16) & 0xff;
                place(e, lds64(sm + O_NOFF + 8 * l), lds32(sm + O_NCNT + 4 * l) + atoms_add(sm + O_NCUR + 4 * l, 1), true);
            }
        }
    }
    if (w < 8) {
#pragma unroll
        for (int p = 0; p < 5; p++) ldsm4t(wr[p], sm + O_WRS + (2 * p + (w >> 2)) * 2048 + sw);
    }
    __syncthreads();
    TS(5);
    if (t >= NT - NSLOT) {
        const uint32_t sb = sm + O_RING + (NT - 1 - t) * SLOT;
        sts128(sb + S_C + 64, make_uint4(0, 0, 0, 0));
        mbar_init(sb + S_FULL, 32); mbar_init(sb + S_EMPTY, 8);
    }
    if (!big) {
        uint32_t* lp = (uint32_t*)(gs->list + gbase * 16) + (g == 1 || g == 2 ? q * 2 + g + 3 : lane);
        for (int c = w; c * 2 < total; c += 48) {
            uint32_t v[4][4];
#pragma unroll
            for (int k = 0; k < 4; k++) if ((c + 12 * k) * 2 < total) ldsm4t(v[k], sm + O_L + (c + 12 * k) * 512 + lane * 16);
#pragma unroll
            for (int k = 0; k < 4; k++)
                if ((c + 12 * k) * 2 < total) {
#pragma unroll
                    for (int i = 0; i < 4; i++) lp[((c + 12 * k) * 4 + i) * 32] = v[k][i];
                }
        }
    }
    __syncthreads();
    TS(6);

    if (w >= 8) {
        asm volatile("setmaxnreg.dec.sync.aligned.u32 " STR(PREG) ";");
        const int h = __reduce_max_sync(0xffffffffu, w & 3);
        const uint32_t ring = sm + O_RING;
        const int hp16 = r < 2 ? r * 8 : r < 4 ? r - 1 : r + 5;
        if (r < 6 && h + 4 * mat < NSLOT) cpa16z(ring + (h + 4 * mat) * SLOT + S_H + r * 16, gs->list + (pos + h + 4 * mat) * 16 + hp16, 1);
        if (t == NT - 1) {
            asm volatile("fence.proxy.async.shared::cta;" ::: "memory");
            tma2d(sm + O_L, &m_w1, 64, 192, sm + O_WBB);
            asm volatile("red.release.gpu.global.add.u32 [%0], 1;" ::"l"(&gs->pub) : "memory");
        }
        const uint32_t xoff = opaque(mat * 4096 + ((r ^ (4 * (mat & 1))) * 16), lane);
        const uint32_t aoff = opaque(S_A + (lane >> 1) * 32 + (((lane ^ mat) & 1) * 16), lane);
        const uint32_t moff = opaque(mat < 2 ? (r < 4 ? S_C + mat * 80 + r * 16 : 0) : (mat == 2 && r < 6) ? S_H + r * 16 : 0, lane);
        const uint32_t hoff = opaque(S_H + mat * 8, lane), hoff2 = opaque(S_H + 32 + g * 8, lane);
        const uint32_t psel = opaque((lane & 2) ? 0x7632 : 0x5410, lane);
        const uint64_t xl = __shfl_sync(0xffffffffu, (uint64_t)(x - 1024 + r * 16), lane);
        const uint64_t al = __shfl_sync(0xffffffffu, (uint64_t)(ea - 32 + (lane & 1) * 16), lane);
        const uint64_t ml = __shfl_sync(0xffffffffu, (uint64_t)(gs->list + (mat < 2 ? mat * 8 + 4 + r : hp16)), lane);
        int cur = __reduce_max_sync(0xffffffffu, pos) + h;
        pos = cur + NSLOT; end = __reduce_max_sync(0xffffffffu, end);

        int ev = h ? end : end - 12, state = h ? 2 : 0, tk = 0, nr = 0, prv = pos - 1;
        uint32_t inf = 0;
        auto take = [&]() {
            int v = 0;
            asm volatile("{.reg .pred p; setp.eq.s32 p, %2, 0; @p atom.relaxed.gpu.global.add.u32 %0, [%1], 1;}" : "+r"(v) : "l"(&gs->ticket), "r"(lane) : "memory");
            return v;
        };
        auto resolve = [&]() {
            const int k = __reduce_max_sync(0xffffffffu, tk);
            inf = 0;
            if (k < G * NPOOL) { const int l = k / G; inf = __ldcg(&gs->info[(k - l * G) * NPOOL + l]); tk = take(); }
        };
        uint32_t so = ring + h * SLOT, ph = 1;
        asm volatile("cp.async.wait_all;" ::: "memory");
        __syncwarp();
        while (true) {
            const uint32_t mi = max(moff >= S_H ? pos : cur, 0);
            const char* gm = (const char*)madw(mi, 256, ml);
            const uint32_t d0 = so + xoff;
            mbar_wait(so + S_EMPTY, ph);
            if (cur <= 0) break;
            const uint2 e = lds64(so + hoff), e2 = lds64(so + hoff2);
            const uint32_t s[4] = {e.x & 0xffffu, e.x >> 16, e.y & 0xffffu, e.y >> 16};
            const uint32_t id = __byte_perm(e2.x, e2.y, psel);
            cpa16z(so + aoff, (const char*)madw(id, 32, al), id);
            if (moff) cpa16z(so + moff, gm, mi);
#pragma unroll
            for (int j = 0; j < 4; j++) {
                const char* gx = (const char*)madw(s[j], 1024, xl);
#pragma unroll
                for (int k = 0; k < 8; k++) cpa16z((d0 ^ (j * 16)) + j * 1024 + k * 128, gx + k * 128, s[j]);
            }
            asm volatile("cp.async.mbarrier.arrive.noinc.shared::cta.b64 [%0];" ::"r"(so + S_FULL) : "memory");
            if (so == ring) so += 4 * SLOT; else { so -= SLOT; ph ^= 1; }
            cur = prv;
            pos += 4; prv = pos - 1;
            if (pos >= ev) {
                if (state == 0) { ev = end - 6; state = 1; tk = take(); }
                else if (state == 1) {
                    for (int it = 0; __any_sync(0xffffffffu, ld_acq(&gs->pub) < (unsigned)G); it++) spin_check(it);
                    resolve();
                    ev = end; state = 2;
                } else {
                    do {
                        const uint32_t mb = sm + O_MB + (nr & 31) * 8;
                        uint32_t rg;
                        nr++;
                        if (h == 0) {
                            rg = __reduce_max_sync(0xffffffffu, inf);
                            asm volatile("st.release.cta.shared.b64 [%0], %1;" ::"r"(mb), "l"(rg | (uint64_t)nr << 32) : "memory");
                            if (rg) resolve();
                        } else {
                            uint64_t m;
                            for (int it = 0;; it++) {
                                asm volatile("ld.acquire.cta.shared.b64 %0, [%1];" : "=l"(m) : "r"(mb) : "memory");
                                if (__all_sync(0xffffffffu, (int)(m >> 32) == nr)) break;
                                spin_check(it);
                            }
                            rg = __reduce_max_sync(0xffffffffu, (uint32_t)m);
                        }
                        const int ov = pos - end;
                        pos = rg ? (rg & 0xffff) + ov : -(1 << 30);
                        if (ov) prv = pos - 1;
                        end = rg >> 16;
                    } while (pos >= end);
                    ev = end;
                }
            }
        }
        TSW(8 + (h & 1));
        if (lane == 0) sts32(so + S_C + 48, META_END);
        mbar_arrive(so + S_FULL);
        asm volatile("cp.async.wait_all;" ::: "memory");
    } else {
        asm volatile("setmaxnreg.inc.sync.aligned.u32 " STR(CREG) ";");
        const uint32_t xa = opaque(((mat >> 1) * 8 + r) * 1024 + (w >> 2) * 128 + (((2 * (w & 3) + (mat & 1)) ^ r) * 16), lane);
        const uint32_t aa = opaque(S_A + ((mat >> 1) * 8 + r) * 32 + (((mat & 1) ^ (r >> 2)) * 16), lane);
        const uint32_t ya = opaque(S_C + (mat & 1) * 80 + (mat >> 1) * 16, lane);
        const uint32_t yc = opaque(S_C + (mat < 2 ? mat * 80 + 32 : (r >> 2) == (mat & 1) ? (mat & 1) * 80 + (r & 3) * 16 : 64), lane);
        const uint32_t mm = opaque((lane & 15) == 12 ? 0xffffu : 0u, lane);
        const uint32_t na = opaque(mm ? sm + O_NODE + (lane >> 4) * 4 : sm + O_TRASH, lane);
        const uint32_t pw = sm + O_P + w * PW;
        const uint32_t fx = opaque((q < 3 ? pw + P_1P0 + 2 * q * PSBO + (mat & 1) * 128 : sm + O_TRASH + ((pw - sm - O_TRASH + 96) & 127)) + (r >> 2) * 16, lane);
        const uint32_t fyz = opaque(pw + (q < 3 ? (mat < 2 ? P_1P1 : P_1P2) + 2 * q * PSBO : mat < 2 ? P_0P0 : P_0P1) + (mat & 1) * 128 + (r >> 2) * 16, lane);
        uint32_t oh[4][2], eb[3];
#pragma unroll
        for (int c = 0; c < 8; c++) oh[c & 3][c >> 2] = opaque(g == c ? 0x3F803F80u : 0u, lane);
#pragma unroll
        for (int k = 0; k < 3; k++) {
            const unsigned short* ep = (const unsigned short*)eps + (g & 3) * 9 + (q & 1) * 6 + k;
            eb[k] = 0;
            if ((g & 3) < 3 && (q >> 1) == (g >> 2)) eb[k] = ep[0] | ((q & 1) ? 0u : (uint32_t)ep[3] << 16);
        }
        const bool l0 = opaque(lane == 0, lane);
        Acc A;
#pragma unroll
        for (int i = 0; i < 4; i++) { A.p00[i] = A.p110[i] = A.p10[0][i] = A.p10[1][i] = A.p10[2][i] = 0; A.t01[i] = A.m[0][i] = A.m[1][i] = A.m[2][i] = 0.f; }
        int slot = 0;
        bool w1ok = false;
        uint32_t so = sm + O_RING, ph = 0, a[4], ok, mt = 0;
        auto tile = [&](auto first) {
            constexpr bool F = decltype(first)::value;
            uint32_t yb[8], f[4][4], R[5][4];
            ldsm4t(f[0], so + xa);
            ldsm4(yb + 4, so + yc);
#pragma unroll
            for (int m = 1; m < 4; m++) ldsm4t(f[m], so + xa + m * 256);
            ldsm4(yb, so + ya);
            if (l0) mbar_arrive(so + S_EMPTY);
            so += SLOT;
            if (so == sm + O_RING + NSLOT * SLOT) { so = sm + O_RING; ph ^= 1; }
            if (F) {
                const uint32_t sof = (slot & 7) * 16 + (slot >> 3) * PSBO;
                sts32(na + 4 * slot, mt);
                flush(A, fx + sof, fyz + sof, oh, eb);
                slot += 2;
            }
#pragma unroll
            for (int p = 0; p < 5; p++) {
                float c[4];
                mma16z(c, wr[p], a[0], a[1]); R[p][0] = pack(c[0], c[1]); R[p][1] = pack(c[2], c[3]);
                mma16z(c, wr[p], a[2], a[3]); R[p][2] = pack(c[0], c[1]); R[p][3] = pack(c[2], c[3]);
            }
            asm volatile("{\n.reg .pred p;\nmbarrier.test_wait.parity.shared::cta.b64 p, [%5], %6;\nselp.u32 %4, 1, 0, p;\n"
                         "@p ldmatrix.sync.aligned.m8n8.x4.shared.b16 {%0,%1,%2,%3}, [%7];\n}"
                         : "+r"(a[0]), "+r"(a[1]), "+r"(a[2]), "+r"(a[3]), "=r"(ok) : "r"(so + S_FULL), "r"(ph), "r"(so + aa) : "memory");
            asm("lop3.b32 %0, %1, %2, %3, 0xa8;" : "=r"(mt) : "r"(yb[6]), "r"(yb[7]), "r"(mm));
            uint32_t u[4];
#pragma unroll
            for (int i = 0; i < 4; i++) {
                A.p00[i] = F ? hmul(f[0][i], R[0][i]) : hfma(f[0][i], R[0][i], A.p00[i]);
                u[i] = hmul(f[0][i], R[2][i]);
            }
            if (F) mma16z(A.t01, u, yb[6], yb[7]); else mma16(A.t01, u, yb[6], yb[7]);
#pragma unroll
            for (int k = 0; k < 3; k++) {
#pragma unroll
                for (int i = 0; i < 4; i++) {
                    A.p10[k][i] = F ? hmul(f[1 + k][i], R[3][i]) : hfma(f[1 + k][i], R[3][i], A.p10[k][i]);
                    u[i] = hmul(f[1 + k][i], R[4][i]);
                }
                if (F) mma16z(A.m[k], u, yb[6], yb[7]); else mma16(A.m[k], u, yb[6], yb[7]);
            }
#pragma unroll
            for (int i = 0; i < 4; i++) {
                uint32_t sdot = hfma(f[3][i], yb[4 + (i >> 1)], hfma(f[2][i], yb[2 + (i >> 1)], hmul(f[1][i], yb[i >> 1])));
                A.p110[i] = F ? hmul(sdot, R[1][i]) : hfma(sdot, R[1][i], A.p110[i]);
            }
            return __any_sync(0xffffffffu, mt != 0);
        };
        mbar_wait(so + S_FULL, 0);
        ldsm4(a, so + aa);
        TS(7);
        bool last = false;
        while (true) {
            while (!last) {
                last = tile(Bool<false>());
                if (!ok) { mbar_wait(so + S_FULL, ph); ldsm4(a, so + aa); }
            }
            last = tile(Bool<true>());
            if (slot == 16 || last) {
                const bool fin = __any_sync(0xffffffffu, mt == META_END);
                if (slot == 16 || fin) {
                    if (!w1ok) { mbar_wait(sm + O_WBB, 0); w1ok = true; }
                    asm volatile("fence.proxy.async.shared::cta;" ::: "memory");
                    bar_sync(1, 256);
                    float d0[8], d1[24];
                    const uint64_t db = (uint64_t)(((sm + O_P) >> 4) & 0x3fff) | (8ull << 16) | ((uint64_t)(PSBO / 16) << 32);
                    const uint64_t da = (uint64_t)(((sm + O_W1 + (w >> 2) * 49152) >> 4) & 0x3fff) | (1ull << 16) | (64ull << 32) | (1ull << 62);
                    asm volatile("wgmma.fence.sync.aligned;" ::: "memory");
#pragma unroll
                    for (int k = 0; k < 16; k++) wg_rs16(d0, w0[k], db + (((k & 7) * PW + ((k >> 3) ? P_0P1 : P_0P0)) >> 4), k);
                    asm volatile("wgmma.commit_group.sync.aligned;" ::: "memory");
#pragma unroll
                    for (int k = 0; k < 24; k++)
                        wg_ss48(d1, da + k * 128, db + (((k & 7) * PW + ((k >> 3) == 0 ? P_1P0 : (k >> 3) == 1 ? P_1P1 : P_1P2)) >> 4), k);
                    asm volatile("wgmma.commit_group.sync.aligned;" ::: "memory");
                    int nd[4];
#pragma unroll
                    for (int it = 0; it < 4; it++) nd[it] = lds32(sm + O_NODE + 4 * (it * 4 + mat));
                    asm volatile("wgmma.wait_group.sync.aligned 1;" ::: "memory");
#pragma unroll
                    for (int i = 0; i < 8; i++) asm volatile("" : "+f"(d0[i])::"memory");
                    uint32_t o[4][4];
                    float gt[8];
#pragma unroll
                    for (int i = 0; i < 8; i++) gt[i] = __fdividef(1.f, 1.f + __expf(-d0[i]));
#pragma unroll
                    for (int i = 0; i < 4; i++) o[0][i] = pack(d0[2 * i], d0[2 * i + 1]);
#pragma unroll
                    for (int i = 0; i < 8; i++) asm volatile("" : "+f"(gt[i])::"memory");
                    asm volatile("wgmma.wait_group.sync.aligned 0;" ::: "memory");
#pragma unroll
                    for (int i = 0; i < 24; i++) asm volatile("" : "+f"(d1[i])::"memory");
                    bar_sync(1, 256);
#pragma unroll
                    for (int i = 0; i < 4; i++)
#pragma unroll
                        for (int j = 0; j < 3; j++) o[1 + j][i] = pack(d1[8 * j + 2 * i] * gt[2 * i], d1[8 * j + 2 * i + 1] * gt[2 * i + 1]);
                    const uint32_t sg = sm + O_P + (w & 4) * PW + ((mat >> 1) * 8 + r) * 128 + (((2 * (w & 3) + (mat & 1)) ^ r) * 16);
#pragma unroll
                    for (int j = 0; j < 4; j++) stsm4t(sg + j * PW, o[j][0], o[j][1], o[j][2], o[j][3]);
                    bar_sync(2 + (w >> 2), 128);
                    uint4 v[4];
#pragma unroll
                    for (int it = 0; it < 4; it++) v[it] = lds128(pw + (it * 4 + mat) * 128 + ((r ^ ((it * 4 + mat) & 7)) * 16));
                    char* op = out - 1024 + (w & 3) * 256 + (w >> 2) * 128 + r * 16;
#pragma unroll
                    for (int it = 0; it < 4; it++) if (it * 4 + mat < slot && nd[it]) *(uint4*)(op + (size_t)nd[it] * 1024) = v[it];
                    __syncwarp();
                    slot = 0;
                }
                if (fin) break;
            }
            if (!ok) { mbar_wait(so + S_FULL, ph); ldsm4(a, so + aa); }
        }
        TS(10);
        if (t == 0) {
            __threadfence();
            if (atomicInc(&gs->done, G - 1) == G - 1) { gs->pub = 0; gs->ticket = 0; gs->epoch = epoch + 1; }
        }
    }
}

typedef CUresult (*EncFn)(CUtensorMap*, CUtensorMapDataType, cuuint32_t, void*, const cuuint64_t*, const cuuint64_t*,
                          const cuuint32_t*, const cuuint32_t*, CUtensorMapInterleave, CUtensorMapSwizzle,
                          CUtensorMapL2promotion, CUtensorMapFloatOOBfill);

void make_map(EncFn fn, CUtensorMap* m, void* p, int rows, int cols, int brows) {
    cuuint64_t dims[2] = {(cuuint64_t)cols, (cuuint64_t)rows}, strides[1] = {(cuuint64_t)cols * 2};
    cuuint32_t box[2] = {64, (cuuint32_t)brows}, es[2] = {1, 1};
    fn(m, CU_TENSOR_MAP_DATA_TYPE_BFLOAT16, 2, p, dims, strides, box, es, CU_TENSOR_MAP_INTERLEAVE_NONE,
       CU_TENSOR_MAP_SWIZZLE_128B, CU_TENSOR_MAP_L2_PROMOTION_NONE, CU_TENSOR_MAP_FLOAT_OOB_FILL_NONE);
}

}

extern "C" void kernel_launch(void* const* d_in, const int* in_sizes, int n_in, void* d_out, int out_size) {
    static EncFn enc = nullptr;
    static void* scratch = nullptr;
    if (!enc) {
        void* fn = nullptr;
        cudaDriverEntryPointQueryResult qr;
        cudaGetDriverEntryPoint("cuTensorMapEncodeTiled", &fn, cudaEnableDefault, &qr);
        enc = (EncFn)fn;
        cudaGetSymbolAddress(&scratch, g_scratch);
        cudaFuncSetAttribute(tp_kernel, cudaFuncAttributeMaxDynamicSharedMemorySize, SMEM_BYTES);
    }
    CUtensorMap m_wr, m_w0, m_w1;
    make_map(enc, &m_wr, d_in[5], 16, 640, 16);
    make_map(enc, &m_w0, d_in[6], 256, 128, 256);
    make_map(enc, &m_w1, d_in[7], 384, 128, 192);
    tp_kernel<<<G, NT, SMEM_BYTES>>>((const int4*)d_in[4], (const char*)d_in[3], (const char*)d_in[1], (Scratch*)scratch,
                                     (const char*)d_in[0], (const char*)d_in[2], (const __nv_bfloat16*)d_in[8], (char*)d_out,
                                     m_wr, m_w0, m_w1);
}
```

```cpp
#include <cuda_runtime.h>
#include <cuda_bf16.h>
#include <cuda.h>
#include <stdint.h>

namespace {

constexpr int NN = 10000;
constexpr int NE = 320000;
constexpr int G = 132;
constexpr int NT = 384;
constexpr int CH = 2432;
constexpr int NLOC = (NN + G - 1) / G;
#define NPOOL 5
constexpr int NPAIR = NLOC / 2, NPRIV = NPAIR - NPOOL;
constexpr int SEGW = 11;
constexpr int HSTR = 160;
constexpr uint32_t META_END = 0x3fff;

#define NSLOT 5
#define PREFETCH 0
#define W1EARLY 1
#define CREG 216
#define PREG 72
#define STR2(x) #x
#define STR(x) STR2(x)

constexpr int S_A = 16384, S_C = S_A + 512, S_FULL = S_C + 144, S_EMPTY = S_FULL + 8, S_H = S_C + 160, SLOT = 17152;

constexpr int PSBO = 272;
constexpr int PB1 = 5 * PSBO + 256, PB0 = PSBO + 256;
constexpr int P_1P0 = 0, P_1P1 = PB1, P_0P1 = 2 * PB1, P_0P0 = P_0P1 + PB0, P_1P2 = P_0P0 + PB0;
constexpr int PW = P_1P2 + PB1;

constexpr int O_W1 = 0;
constexpr int O_P = 98304;
constexpr int O_RING = O_P + 8 * PW;
constexpr int O_W0S = O_P + CH * 16, O_WRS = O_W0S + 65536;
constexpr int O_BCNT = O_WRS + 20480, O_NCNT = O_BCNT + 544, O_NC2 = O_NCNT + 320, O_NCUR = O_NC2 + 320;
constexpr int O_BOFF = O_NCUR + 320, O_KEY = O_BOFF + 544, O_SORT = O_KEY + 320, O_NOFF = O_SORT + 320;
constexpr int O_TRASH = O_RING + 5 * SLOT;
constexpr int O_WBA = O_TRASH + 512, O_WBB = O_WBA + 8, O_WBC = O_WBA + 16, O_NODE = O_WBA + 32;
constexpr int O_SUM = O_NODE + 64, O_MB = O_SUM + 16;
constexpr int SMEM_BYTES = O_MB + 256;
constexpr int O_L = O_P - 24576;
constexpr int O_PERM = O_L + CH * 6, O_KT = O_PERM + CH * 8;
constexpr int CAPT = (O_W0S - O_L) / 256;
constexpr int NTILE = NE / 8 + G * (NLOC + 5) + 1;
static_assert(SMEM_BYTES <= 232448 && NSLOT == 5 && O_KT + NT * 32 <= O_W0S && CAPT % 2 == 0 && NTILE < 65536, "smem");
static_assert(O_W0S % 1024 == 0 && O_BCNT >= O_RING + 4 * SLOT && O_NOFF + 640 <= O_RING + 4 * SLOT + S_A, "layout");
static_assert(G * CH >= NE && NE % 8 == 0 && CH < 4096, "chunks");
static_assert(SEGW * (NT / 32) == G, "segments");
static_assert(NLOC % 4 == 0 && NLOC <= 80 && NLOC * 4 <= NT && NN < META_END && NPRIV >= 24, "scan width");

struct __align__(128) Scratch {
    uint4 list[NTILE * 16];
    uint4 outbox[G * CH];
    uint4 keys[G * G * 4];
    uint32_t hdr[G * HSTR];
    uint32_t info[G * NPOOL];
    unsigned epoch, done, pad0[30], pub, pad1[31], ticket;
};
__device__ Scratch g_scratch;
#define TS(i)
#define TSW(i)

constexpr int SPIN_LIMIT = 1 << 24;

__device__ __forceinline__ void mbar_init(uint32_t a, int c) { asm volatile("mbarrier.init.shared::cta.b64 [%0], %1;" ::"r"(a), "r"(c) : "memory"); }
__device__ __forceinline__ void mbar_expect(uint32_t a, int b) { asm volatile("mbarrier.arrive.expect_tx.shared::cta.b64 _, [%0], %1;" ::"r"(a), "r"(b) : "memory"); }
__device__ __forceinline__ void mbar_arrive(uint32_t a) { asm volatile("mbarrier.arrive.shared::cta.b64 _, [%0];" ::"r"(a) : "memory"); }
__device__ __forceinline__ void mbar_wait(uint32_t a, uint32_t ph) {
    asm volatile("{\n.reg .pred p, q;\n.reg .u32 it;\n"
                 "mbarrier.try_wait.parity.shared::cta.b64 p, [%0], %1;\n"
                 "@p bra DONE;\n"
                 "mov.u32 it, 0;\n"
                 "LOOP:\n"
                 "mbarrier.try_wait.parity.shared::cta.b64 p, [%0], %1;\n"
                 "@p bra DONE;\n"
                 "add.u32 it, it, 1;\n"
                 "setp.gt.u32 q, it, %2;\n"
                 "@q trap;\n"
                 "bra LOOP;\n"
                 "DONE:\n}" ::"r"(a), "r"(ph), "n"(SPIN_LIMIT) : "memory");
}
__device__ __forceinline__ void spin_check(int it) {
    asm volatile("{\n.reg .pred q;\nsetp.gt.s32 q, %0, %1;\n@q trap;\n}" ::"r"(it), "n"(SPIN_LIMIT));
}
__device__ __forceinline__ void tma2d(uint32_t dst, const CUtensorMap* m, int c0, int c1, uint32_t bar) {
    asm volatile("cp.async.bulk.tensor.2d.shared::cluster.global.mbarrier::complete_tx::bytes [%0], [%1, {%3, %4}], [%2];"
                 ::"r"(dst), "l"(m), "r"(bar), "r"(c0), "r"(c1) : "memory");
}
__device__ __forceinline__ void cpa16z(uint32_t d, const void* g, uint32_t v) {
    asm volatile("{\n.reg .pred p;\nsetp.eq.u32 p, %2, 0;\ncp.async.cg.shared.global [%0], [%1], 16, p;\n}" ::"r"(d), "l"(g), "r"(v) : "memory");
}
__device__ __forceinline__ void ldsm4(uint32_t* r, uint32_t a) { asm volatile("ldmatrix.sync.aligned.m8n8.x4.shared.b16 {%0,%1,%2,%3}, [%4];" : "=r"(r[0]), "=r"(r[1]), "=r"(r[2]), "=r"(r[3]) : "r"(a) : "memory"); }
__device__ __forceinline__ void ldsm4t(uint32_t* r, uint32_t a) { asm volatile("ldmatrix.sync.aligned.m8n8.x4.trans.shared.b16 {%0,%1,%2,%3}, [%4];" : "=r"(r[0]), "=r"(r[1]), "=r"(r[2]), "=r"(r[3]) : "r"(a) : "memory"); }
__device__ __forceinline__ void stsm4t(uint32_t a, uint32_t r0, uint32_t r1, uint32_t r2, uint32_t r3) { asm volatile("stmatrix.sync.aligned.m8n8.x4.trans.shared.b16 [%0], {%1,%2,%3,%4};" ::"r"(a), "r"(r0), "r"(r1), "r"(r2), "r"(r3) : "memory"); }
__device__ __forceinline__ void stsm2t(uint32_t a, uint32_t r0, uint32_t r1) { asm volatile("stmatrix.sync.aligned.m8n8.x2.trans.shared.b16 [%0], {%1,%2};" ::"r"(a), "r"(r0), "r"(r1) : "memory"); }
__device__ __forceinline__ void mma16(float* d, const uint32_t* a, uint32_t b0, uint32_t b1) {
    asm("mma.sync.aligned.m16n8k16.row.col.f32.bf16.bf16.f32 {%0,%1,%2,%3}, {%4,%5,%6,%7}, {%8,%9}, {%0,%1,%2,%3};"
        : "+f"(d[0]), "+f"(d[1]), "+f"(d[2]), "+f"(d[3]) : "r"(a[0]), "r"(a[1]), "r"(a[2]), "r"(a[3]), "r"(b0), "r"(b1));
}
__device__ __forceinline__ void mma8(float* d, uint32_t a0, uint32_t a1, uint32_t b0) {
    asm("mma.sync.aligned.m16n8k8.row.col.f32.bf16.bf16.f32 {%0,%1,%2,%3}, {%4,%5}, {%6}, {%0,%1,%2,%3};"
        : "+f"(d[0]), "+f"(d[1]), "+f"(d[2]), "+f"(d[3]) : "r"(a0), "r"(a1), "r"(b0));
}
__device__ __forceinline__ void mma16z(float* d, const uint32_t* a, uint32_t b0, uint32_t b1) {
    asm("mma.sync.aligned.m16n8k16.row.col.f32.bf16.bf16.f32 {%0,%1,%2,%3}, {%4,%5,%6,%7}, {%8,%9}, {%10,%10,%10,%10};"
        : "=f"(d[0]), "=f"(d[1]), "=f"(d[2]), "=f"(d[3]) : "r"(a[0]), "r"(a[1]), "r"(a[2]), "r"(a[3]), "r"(b0), "r"(b1), "f"(0.f));
}
__device__ __forceinline__ uint32_t pack(float lo, float hi) { uint32_t r; asm("cvt.rn.bf16x2.f32 %0, %1, %2;" : "=r"(r) : "f"(hi), "f"(lo)); return r; }
__device__ __forceinline__ uint32_t hmul(uint32_t a, uint32_t b) { uint32_t r; asm("mul.rn.bf16x2 %0, %1, %2;" : "=r"(r) : "r"(a), "r"(b)); return r; }
__device__ __forceinline__ uint32_t hfma(uint32_t a, uint32_t b, uint32_t c) { uint32_t r; asm("fma.rn.bf16x2 %0, %1, %2, %3;" : "=r"(r) : "r"(a), "r"(b), "r"(c)); return r; }
__device__ __forceinline__ uint4 lds128(uint32_t a) { uint4 v; asm volatile("ld.shared.v4.u32 {%0,%1,%2,%3}, [%4];" : "=r"(v.x), "=r"(v.y), "=r"(v.z), "=r"(v.w) : "r"(a) : "memory"); return v; }
__device__ __forceinline__ void sts128(uint32_t a, uint4 v) { asm volatile("st.shared.v4.u32 [%0], {%1,%2,%3,%4};" ::"r"(a), "r"(v.x), "r"(v.y), "r"(v.z), "r"(v.w) : "memory"); }
__device__ __forceinline__ int lds32(uint32_t a) { int v; asm volatile("ld.shared.u32 %0, [%1];" : "=r"(v) : "r"(a) : "memory"); return v; }
__device__ __forceinline__ void sts32(uint32_t a, int v) { asm volatile("st.shared.u32 [%0], %1;" ::"r"(a), "r"(v) : "memory"); }
__device__ __forceinline__ int atoms_add(uint32_t a, int v) { int r; asm volatile("atom.shared.add.u32 %0, [%1], %2;" : "=r"(r) : "r"(a), "r"(v) : "memory"); return r; }
__device__ __forceinline__ uint32_t ld_acq(const void* p) { uint32_t v; asm volatile("ld.acquire.gpu.global.u32 %0, [%1];" : "=r"(v) : "l"(p) : "memory"); return v; }
__device__ __forceinline__ uint32_t ld_rlx(const void* p) { uint32_t v; asm volatile("ld.relaxed.gpu.global.u32 %0, [%1];" : "=r"(v) : "l"(p) : "memory"); return v; }
__device__ __forceinline__ uint4 ld_rlx128(const void* p) {
    uint64_t a, b;
    asm volatile("ld.relaxed.gpu.global.v2.b64 {%0,%1}, [%2];" : "=l"(a), "=l"(b) : "l"(p) : "memory");
    return make_uint4((uint32_t)a, (uint32_t)(a >> 32), (uint32_t)b, (uint32_t)(b >> 32));
}
__device__ __forceinline__ void st_rlx128(void* p, uint4 v) {
    asm volatile("st.relaxed.gpu.global.v2.b64 [%0], {%1,%2};" ::"l"(p), "l"(v.x | ((uint64_t)v.y << 32)), "l"(v.z | ((uint64_t)v.w << 32)) : "memory");
}
__device__ __forceinline__ void bulk(uint32_t dst, const void* g, int n, uint32_t bar) {
    asm volatile("cp.async.bulk.shared::cluster.global.mbarrier::complete_tx::bytes [%0], [%1], %2, [%3];" ::"r"(dst), "l"(g), "r"(n), "r"(bar) : "memory");
}
__device__ __forceinline__ uint2 lds64(uint32_t a) { uint2 v; asm volatile("ld.shared.v2.u32 {%0,%1}, [%2];" : "=r"(v.x), "=r"(v.y) : "r"(a) : "memory"); return v; }
__device__ __forceinline__ void sts64(uint32_t a, uint32_t x, uint32_t y) { asm volatile("st.shared.v2.u32 [%0], {%1,%2};" ::"r"(a), "r"(x), "r"(y) : "memory"); }
__device__ __forceinline__ void sts16(uint32_t a, uint32_t v) { asm volatile("st.shared.u16 [%0], %1;" ::"r"(a), "h"((unsigned short)v) : "memory"); }
__device__ __forceinline__ uint32_t ld_rlx16(const void* p) { uint32_t v; asm volatile("ld.relaxed.gpu.global.u16 %0, [%1];" : "=r"(v) : "l"(p) : "memory"); return v; }
__device__ __forceinline__ void tma3d(uint32_t dst, const CUtensorMap* m, uint32_t bar) {
    asm volatile("cp.async.bulk.tensor.3d.shared::cluster.global.mbarrier::complete_tx::bytes [%0], [%1, {%3, %3, %3}], [%2];"
                 ::"r"(dst), "l"(m), "r"(bar), "r"(0) : "memory");
}
__device__ __forceinline__ uint64_t madw(uint32_t a, uint32_t b, uint64_t c) { uint64_t r; asm("mad.wide.u32 %0, %1, %2, %3;" : "=l"(r) : "r"(a), "r"(b), "l"(c)); return r; }
__device__ __forceinline__ uint32_t opaque(uint32_t v, int lane) { return __shfl_sync(0xffffffffu, v, lane); }
__device__ __forceinline__ void bar_sync(int id, int n) { asm volatile("bar.sync %0, %1;" ::"r"(id), "r"(n) : "memory"); }

__device__ __forceinline__ void wg_rs16(float* d, const uint32_t* a, uint64_t db, int sc) {
    asm volatile("{.reg .pred p; setp.ne.b32 p, %13, 0;\n"
                 "wgmma.mma_async.sync.aligned.m64n16k16.f32.bf16.bf16 {%0,%1,%2,%3,%4,%5,%6,%7}, {%8,%9,%10,%11}, %12, p, 1, 1, 0;}"
                 : "+f"(d[0]), "+f"(d[1]), "+f"(d[2]), "+f"(d[3]), "+f"(d[4]), "+f"(d[5]), "+f"(d[6]), "+f"(d[7])
                 : "r"(a[0]), "r"(a[1]), "r"(a[2]), "r"(a[3]), "l"(db), "r"(sc));
}
__device__ __forceinline__ void wg_ss48(float* d, uint64_t da, uint64_t db, int sc) {
    asm volatile("{.reg .pred p; setp.ne.b32 p, %26, 0;\n"
                 "wgmma.mma_async.sync.aligned.m64n48k16.f32.bf16.bf16 {%0,%1,%2,%3,%4,%5,%6,%7,%8,%9,%10,%11,%12,%13,%14,%15,%16,%17,%18,%19,%20,%21,%22,%23}, %24, %25, p, 1, 1, 1, 0;}"
                 : "+f"(d[0]), "+f"(d[1]), "+f"(d[2]), "+f"(d[3]), "+f"(d[4]), "+f"(d[5]), "+f"(d[6]), "+f"(d[7]),
                   "+f"(d[8]), "+f"(d[9]), "+f"(d[10]), "+f"(d[11]), "+f"(d[12]), "+f"(d[13]), "+f"(d[14]), "+f"(d[15]),
                   "+f"(d[16]), "+f"(d[17]), "+f"(d[18]), "+f"(d[19]), "+f"(d[20]), "+f"(d[21]), "+f"(d[22]), "+f"(d[23])
                 : "l"(da), "l"(db), "r"(sc));
}

__device__ __forceinline__ int warp_incl(int v, int lane) {
#pragma unroll
    for (int o = 1; o < 32; o <<= 1) { int u = __shfl_up_sync(0xffffffffu, v, o); if (lane >= o) v += u; }
    return v;
}

template <bool B> struct Bool { static constexpr bool value = B; };
struct Acc {
    uint32_t p00[4], p110[4], p10[3][4];
    float t01[4], m[3][4];
};

__device__ __forceinline__ void flush(const Acc& A, uint32_t ax, uint32_t ayz, const uint32_t (*oh)[2], const uint32_t* eb) {
    float y[4], z[4];
    const uint32_t mp[4] = {pack(A.m[0][0], A.m[0][1]), pack(A.m[0][2], A.m[0][3]), pack(A.m[1][0], A.m[1][1]), pack(A.m[1][2], A.m[1][3])};
    mma16z(y, A.p10[0], oh[0][0], oh[0][1]);
    mma16z(z, A.p110, oh[3][0], oh[3][1]);
    mma16(y, A.p10[1], oh[1][0], oh[1][1]);
    mma16(z, mp, eb[0], eb[1]);
    mma16(y, A.p10[2], oh[2][0], oh[2][1]);
    mma8(z, pack(A.m[2][0], A.m[2][1]), pack(A.m[2][2], A.m[2][3]), eb[2]);
    mma16(y, A.p00, oh[3][0], oh[3][1]);
    stsm2t(ax, pack(A.t01[0], A.t01[1]), pack(A.t01[2], A.t01[3]));
    stsm4t(ayz, pack(y[0], y[1]), pack(y[2], y[3]), pack(z[0], z[1]), pack(z[2], z[3]));
}

__global__ void __launch_bounds__(NT, 1)
tp_kernel(const int4* __restrict__ dst, const int4* __restrict__ src, const char* __restrict__ rhat, Scratch* __restrict__ gs,
          const char* __restrict__ x, const char* __restrict__ ea, const __nv_bfloat16* __restrict__ eps, char* __restrict__ out,
          const __grid_constant__ CUtensorMap m_wr, const __grid_constant__ CUtensorMap m_w0, const __grid_constant__ CUtensorMap m_w1) {
    extern __shared__ __align__(1024) char smem_raw[];
    const uint32_t sm = (uint32_t)__cvta_generic_to_shared(smem_raw);
    const int t = threadIdx.x, w = t >> 5, lane = t & 31, b = blockIdx.x;

    const int e0 = b * CH + t * 4;
    const bool act[2] = {t < CH / 8, t < CH / 8 && e0 + CH / 2 < NE};
    int d[8], s[8];
#pragma unroll
    for (int k = 0; k < 2; k++)
        if (act[k]) *(int4*)&d[4 * k] = __ldg(dst + e0 / 4 + k * (CH / 8));
#pragma unroll
    for (int k = 0; k < 2; k++)
        if (act[k]) *(int4*)&s[4 * k] = __ldg(src + e0 / 4 + k * (CH / 8));
    uint32_t epoch = ld_rlx(&gs->epoch);
    if (t == NT - 1) {
        const int ne = min(CH, NE - b * CH);
        mbar_init(sm + O_WBA, 1); mbar_init(sm + O_WBB, 1); mbar_init(sm + O_WBC, 1);
        asm volatile("fence.proxy.async.shared::cta;" ::: "memory");
        mbar_expect(sm + O_WBC, ne * 6);
        bulk(sm + O_L, rhat + b * (CH * 6), ne * 6, sm + O_WBC);
    }
    sts32(sm + O_BCNT + 4 * t, 0);
    sts128(sm + O_KT + 16 * t, make_uint4(0, 0, 0, 0));
    if (t < G * 4 - NT) sts128(sm + O_KT + 16 * (t + NT), make_uint4(0, 0, 0, 0));
    if (t < 68) sts32(sm + O_SUM + 4 * t, 0);
    __syncthreads();
    if (t == NT - 1) {
        mbar_expect(sm + O_WBA, 86016); mbar_expect(sm + O_WBB, 98304);
        tma3d(sm + O_W0S, &m_w0, sm + O_WBA);
        tma3d(sm + O_WRS, &m_wr, sm + O_WBA);
        for (int j = 0; j < 3; j++) tma2d(sm + O_W1 + j * 24576, &m_w1, 64 * (j >> 1), 192 * (j & 1), sm + O_WBB);
    }
    int rk[8];
#pragma unroll
    for (int k = 0; k < 2; k++)
        if (act[k]) {
#pragma unroll
            for (int i = 4 * k; i < 4 * k + 4; i++) {
                int loc = d[i] / G, own = d[i] - loc * G;
                d[i] = own | (loc << 16);
                rk[i] = atoms_add(sm + O_BCNT + 4 * own, 1);
            }
#pragma unroll
            for (int i = 4 * k; i < 4 * k + 4; i++)
                if (rk[i] < 32) sts16(sm + O_KT + (d[i] & 0xffff) * 64 + rk[i] * 2, (d[i] >> 16) + 1);
        }
    TS(0);
    __syncthreads();
    asm volatile("" : "+r"(epoch));
    const uint32_t tag = (0x80u | (epoch & 63) << 1) << 24;
    {
        const uint32_t tk = tag | tag >> 16;
        const uint4 u = lds128(sm + O_KT + 16 * t), v = lds128(sm + O_KT + 16 * (t + NT));
        st_rlx128(&gs->keys[b * (G * 4) + t], make_uint4(u.x | tk, u.y | tk, u.z | tk, u.w | tk));
        if (t < G * 4 - NT) st_rlx128(&gs->keys[b * (G * 4) + t + NT], make_uint4(v.x | tk, v.y | tk, v.z | tk, v.w | tk));
    }
    {
        int v[5], sum = 0;
#pragma unroll
        for (int i = 0; i < 5; i++) { v[i] = (lane * 5 + i < G) ? lds32(sm + O_BCNT + 4 * (lane * 5 + i)) : 0; sum += v[i]; }
        int e = warp_incl(sum, lane) - sum;
#pragma unroll
        for (int i = 0; i < 5; i++) { if (lane * 5 + i < G) sts32(sm + O_BOFF + 4 * (lane * 5 + i), e); e += v[i]; }
        __syncwarp();
    }
    auto header = [&](uint32_t tg) {
        if ((unsigned)(t - 320) < 34u) {
            const uint4 o = lds128(sm + O_BOFF + 16 * (t - 320)), c = lds128(sm + O_BCNT + 16 * (t - 320));
            st_rlx128(&gs->hdr[b * HSTR + 4 * (t - 320)], make_uint4(tg | o.x << 12 | c.x, tg | o.y << 12 | c.y, tg | o.z << 12 | c.z, tg | o.w << 12 | c.w));
        }
    };
    header(tag);
#pragma unroll
    for (int k = 0; k < 2; k++)
        if (act[k]) {
#pragma unroll
            for (int i = 4 * k; i < 4 * k + 4; i++) rk[i] += lds32(sm + O_BOFF + 4 * (d[i] & 0xffff));
#pragma unroll
            for (int i = 4 * k; i < 4 * k + 4; i++) {
                const uint32_t id = e0 + k * (CH / 2 - 4) + i + 1;
                sts64(sm + O_PERM + rk[i] * 8, (s[i] + 1) | (id << 16), (id >> 16) | (d[i] & 0xffff0000u) | tag);
            }
        }
    __syncthreads();
    TS(11);
    const uint32_t* hp = &gs->hdr[(w * SEGW + min(lane, SEGW - 1)) * HSTR + b];
    const unsigned short* kp = (const unsigned short*)&gs->keys[(w * SEGW * G + b) * 4] + lane;
    uint32_t hv, kr[SEGW];
    {
        constexpr int K = CH / NT + 1;
        uint2 pe[K];
        uint32_t ya[K], y0[K], y1[K];
#pragma unroll
        for (int k = 0; k < K; k++) pe[k] = lds64(sm + O_PERM + (t + k * NT) * 8);
#pragma unroll
        for (int k = 0; k < K; k++) ya[k] = (((pe[k].x >> 16) - (b * CH + 1)) & 0xfff) * 6;
        mbar_wait(sm + O_WBC, 0);
        TS(12);
        hv = ld_rlx(hp);
#pragma unroll
        for (int j = 0; j < SEGW; j++) kr[j] = ld_rlx16(kp + j * (G * 32));
#pragma unroll
        for (int k = 0; k < K; k++) { y0[k] = lds32(sm + O_L + (ya[k] & ~3u)); y1[k] = lds32(sm + O_L + (ya[k] & ~3u) + 4); }
        uint4* op = &gs->outbox[b * CH + t];
#pragma unroll
        for (int k = 0; k < K; k++) {
            const uint32_t lo = __funnelshift_r(y0[k], y1[k], ya[k] * 8), hi = __byte_perm(__funnelshift_r(y1[k], 0, ya[k] * 8), tag, 0x7610);
            asm volatile("{.reg .pred p; .reg .b64 u, v; setp.lt.s32 p, %5, %6; mov.b64 u, {%1,%2}; mov.b64 v, {%3,%4};\n"
                         "@p st.relaxed.gpu.global.v2.b64 [%0], {u, v};}"
                         ::"l"(op + k * NT), "r"(pe[k].x), "r"(pe[k].y), "r"(lo), "r"(hi), "r"(k < K - 1 ? 0 : t), "n"(CH % NT) : "memory");
        }
    }
    if (w < 10) asm volatile("bar.arrive 4, %0;" ::"n"(NT) : "memory");
    else { bar_sync(4, NT); header(tag | 1u << 24); }
    TS(1);

    for (int it = 0;; it++) {
        uint32_t bad = (hv ^ tag) >> 25;
#pragma unroll
        for (int j = 0; j < SEGW; j++) bad |= (kr[j] ^ (tag >> 16)) >> 8;
        if (!__any_sync(0xffffffffu, bad)) break;
        spin_check(it);
        hv = ld_rlx(hp);
#pragma unroll
        for (int j = 0; j < SEGW; j++) kr[j] = ld_rlx16(kp + j * (G * 32));
    }
    TS(3);
    uint32_t have = 0;
#pragma unroll
    for (int j = 0; j < SEGW; j++) {
        uint32_t rank;
        kr[j] &= 0xff;
        asm volatile("{.reg .pred p; setp.ne.u32 p, %3, 0; mov.u32 %0, 0; @p atom.shared.add.u32 %0, [%2], 1; @p or.b32 %1, %1, %4;}"
                     : "=r"(rank), "+r"(have) : "r"(sm + O_NCNT - 4 + kr[j] * 4), "r"(kr[j]), "r"(1 << j) : "memory");
        kr[j] |= rank << 16;
    }
    {
        int so = __reduce_add_sync(0xffffffffu, lane < SEGW ? (hv >> 12) & 0xfff : 0);
        if (lane == 0) atoms_add(sm + O_SUM, so);
    }
    const uint4* ob = gs->outbox + w * SEGW * CH + lane;
    auto fresh = [&](const uint4& e) { return (((e.y ^ tag) | (e.w ^ tag)) >> 24) == 0; };
    const bool longseg = __any_sync(0xffffffffu, (hv & 0xfff) > 32);
    if (longseg) {
        for (int j = 0; j < SEGW; j++) {
            const uint32_t h = __shfl_sync(0xffffffffu, hv, j);
            for (int i = 32; i + lane < (h & 0xfff); i += 32) {
                uint4 e;
                int it = 0;
                do { e = ld_rlx128(ob + j * CH + ((h >> 12) & 0xfff) + i); spin_check(it++); } while (!fresh(e));
                atoms_add(sm + O_NC2 + ((e.y >> 14) & 0x3fc), 1);
            }
        }
    }
    hv = ld_rlx(hp);
    __syncthreads();
    TS(4);
    const int g = lane >> 2, q = lane & 3, mat = lane >> 3, r = lane & 7;
    if (t < 80) sts32(sm + O_KEY + 4 * t, t < NLOC ? (lds32(sm + O_NCNT + 4 * t) + lds32(sm + O_NC2 + 4 * t)) << 7 | (127 - t) : 0);
    __syncthreads();
    {
        const int key = lds32(sm + O_KEY + min(t & ~3, 316));
        int rank = 0;
#pragma unroll
        for (int i = 0; i < 5; i++) {
            const uint4 k = lds128(sm + O_KEY + q * 80 + i * 16);
            rank += ((int)k.x > key) + ((int)k.y > key) + ((int)k.z > key) + ((int)k.w > key);
        }
        rank += __shfl_xor_sync(0xffffffffu, rank, 1);
        rank += __shfl_xor_sync(0xffffffffu, rank, 2);
        if (t < NLOC * 4) sts32(sm + O_SORT + 4 * rank, key);
    }
    uint64_t ea_[SEGW], eb_[SEGW];
    uint32_t pend = have;
#pragma unroll
    for (int j = 0; j < SEGW; j++) ea_[j] = eb_[j] = 0;
    auto fetch = [&]() {
        const uint32_t go = pend & __ballot_sync(0xffffffffu, hv >> 24 & 1);
#pragma unroll
        for (int j = 0; j < SEGW; j++) {
            const uint32_t h = __shfl_sync(0xffffffffu, hv, j);
            asm volatile("{.reg .pred p; setp.ne.u32 p, %3, 0; @p ld.relaxed.gpu.global.v2.b64 {%0,%1}, [%2];}"
                         : "+l"(ea_[j]), "+l"(eb_[j]) : "l"(ob + j * CH + ((h >> 12) & 0xfff)), "r"(go & (1u << j)) : "memory");
        }
        hv = ld_rlx(hp);
    };
    fetch();
    __syncthreads();
    TS(2);
    int total, pos, end;
    const int gbase = (lds32(sm + O_SUM) >> 3) + (NLOC + 5) * b + 1;
    {
        const bool on = lane < NLOC / 4;
        const uint4 k4 = lds128(sm + O_SORT + 16 * (on ? lane : 0));
        const uint32_t k[4] = {k4.x, k4.y, k4.z, k4.w};
        const int n0 = on ? max(1u, (k[0] + 896) >> 10) : 0, n1 = on ? max(1u, (k[2] + 896) >> 10) : 0;
        int e = warp_incl(n0 + n1, lane);
        total = __shfl_sync(0xffffffffu, e, 31);
        end = gbase + __shfl_sync(0xffffffffu, NPRIV & 1 ? e - n1 : e, (NPRIV - 1) / 2);
        pos = gbase;
        e -= n0 + n1;
#pragma unroll
        for (int i = 0; i < 4; i++) {
            const int l = 127 - (k[i] & 127), node = l * G + b;
            if (on) sts64(sm + O_NOFF + 8 * l, (e + (i >> 1) * n0) * 16 + (i & 1) * 8, ((i >> 1 ? n1 : n0) - 1) | (node < NN ? node + 1 : 0) << 16);
        }
        if (w == 0 && on) {
            if (2 * lane >= NPRIV) gs->info[b * NPOOL + 2 * lane - NPRIV] = (gbase + e) | (gbase + e + n0) << 16;
            if (2 * lane + 1 >= NPRIV) gs->info[b * NPOOL + 2 * lane + 1 - NPRIV] = (gbase + e + n0) | (gbase + e + n0 + n1) << 16;
        }
        __syncwarp();
    }
    const bool big = total > CAPT;
    auto place = [&](uint4 e, uint2 o, int rank) {
        e.w = __byte_perm(e.w, rank == (int)(o.y & 0xffff) * 8 ? o.y : 0u, 0x7610);
        const int idx = o.x + rank + (rank & ~7);
        if (!big) sts128(sm + O_L + idx * 16, e);
        else {
            unsigned short* p = (unsigned short*)(gs->list + (gbase * 2 + (idx >> 3)) * 8);
            const int c = idx & 7, c2 = 8 + (c >> 1) * 4 + (c & 1);
            p[c] = e.x; p[c2] = e.x >> 16; p[c2 + 2] = e.y;
            p[32 + c] = e.z; p[40 + c] = e.z >> 16; p[48 + c] = e.w; p[56 + c] = e.w >> 16;
        }
    };
    if (!big) {
#pragma unroll
        for (int j = 0; j < SEGW; j++) {
            const uint2 o = lds64(sm + O_NOFF - 8 + (kr[j] & 0xff) * 8);
            const uint32_t rank = kr[j] >> 16;
            kr[j] = __byte_perm((o.x + rank + (rank & ~7u)) * 16, rank == (o.y & 0xffff) * 8 ? o.y : 0u, 0x7610);
        }
    }
    if (t < NLOC * 4) {
        const uint2 o = lds64(sm + O_NOFF + 8 * (t >> 2));
#pragma unroll 1
        for (int p = (lds32(sm + O_KEY + (t & ~3)) >> 7) + q; p < (int)(o.y & 0xffff) * 8 + 8; p += 4) place(make_uint4(0, 0, 0, 0), o, p);
    }
    const uint32_t sw = (uint32_t)(((2 * (w & 3) + (mat & 1)) ^ r) * 16 + ((mat >> 1) * 8 + r) * 128);
    uint32_t wr[5][4], w0[16][4];
    if (w < 8) {
        mbar_wait(sm + O_WBA, 0);
#pragma unroll
        for (int k = 0; k < 16; k++) ldsm4t(w0[k], sm + O_W0S + (w >> 2) * 32768 + k * 2048 + sw);
    }
    for (int it = 0;; it++) {
        uint32_t old = 0;
#pragma unroll
        for (int j = 0; j < SEGW; j++)
            if ((((uint32_t)(ea_[j] >> 32) ^ tag) | ((uint32_t)(eb_[j] >> 32) ^ tag)) >> 24) old |= 1u << j;
        pend &= old;
        if (!__any_sync(0xffffffffu, pend)) break;
        spin_check(it);
        fetch();
    }
    TS(13);
    if (!big) {
#pragma unroll
        for (int j = 0; j < SEGW; j++)
            asm volatile("{.reg .pred p; setp.ne.u32 p, %5, 0; @p st.shared.v4.u32 [%0], {%1,%2,%3,%4};}"
                         ::"r"(sm + O_L + (kr[j] & 0xffff)), "r"((uint32_t)ea_[j]), "r"((uint32_t)(ea_[j] >> 32)), "r"((uint32_t)eb_[j]),
                           "r"(__byte_perm((uint32_t)(eb_[j] >> 32), kr[j], 0x7610)), "r"(have & (1u << j)) : "memory");
    } else {
#pragma unroll
        for (int j = 0; j < SEGW; j++)
            if (have >> j & 1)
                place(make_uint4((uint32_t)ea_[j], (uint32_t)(ea_[j] >> 32), (uint32_t)eb_[j], (uint32_t)(eb_[j] >> 32)),
                      lds64(sm + O_NOFF - 8 + (kr[j] & 0xff) * 8), kr[j] >> 16);
    }
    if (longseg) {
        for (int j = 0; j < SEGW; j++) {
            const uint32_t h = __shfl_sync(0xffffffffu, hv, j);
            for (int i = 32; i + lane < (h & 0xfff); i += 32) {
                const uint4 e = ld_rlx128(ob + j * CH + ((h >> 12) & 0xfff) + i);
                const int l = (e.y >> 16) & 0xff;
                place(e, lds64(sm + O_NOFF + 8 * l), lds32(sm + O_NCNT + 4 * l) + atoms_add(sm + O_NCUR + 4 * l, 1));
            }
        }
    }
    if (w < 8) {
#pragma unroll
        for (int p = 0; p < 5; p++) ldsm4t(wr[p], sm + O_WRS + (2 * p + (w >> 2)) * 2048 + sw);
    }
    __syncthreads();
    TS(5);
    if (t >= NT - NSLOT) {
        const uint32_t sb = sm + O_RING + (NT - 1 - t) * SLOT;
        sts128(sb + S_C + 64, make_uint4(0, 0, 0, 0));
        mbar_init(sb + S_FULL, 32); mbar_init(sb + S_EMPTY, 8);
    }
    if (!big) {
        uint32_t* lp = (uint32_t*)(gs->list + gbase * 16) + (g == 1 || g == 2 ? q * 2 + g + 3 : lane);
        for (int c = w; c * 2 < total; c += 48) {
            uint32_t v[4][4];
#pragma unroll
            for (int k = 0; k < 4; k++) if ((c + 12 * k) * 2 < total) ldsm4t(v[k], sm + O_L + (c + 12 * k) * 512 + lane * 16);
#pragma unroll
            for (int k = 0; k < 4; k++)
                if ((c + 12 * k) * 2 < total) {
#pragma unroll
                    for (int i = 0; i < 4; i++) lp[((c + 12 * k) * 4 + i) * 32] = v[k][i];
                }
        }
    }
    __syncthreads();
    TS(6);

    if (w >= 8) {
        asm volatile("setmaxnreg.dec.sync.aligned.u32 " STR(PREG) ";");
        const int h = __reduce_max_sync(0xffffffffu, w & 3);
        const uint32_t ring = sm + O_RING;
        const int hp16 = r < 2 ? r * 8 : r < 4 ? r - 1 : r + 5;
        if (r < 6 && h + 4 * mat < NSLOT) cpa16z(ring + (h + 4 * mat) * SLOT + S_H + r * 16, gs->list + (pos + h + 4 * mat) * 16 + hp16, 1);
        if (t == NT - 1) {
            asm volatile("fence.proxy.async.shared::cta;" ::: "memory");
            tma2d(sm + O_L, &m_w1, 64, 192, sm + O_WBB);
            asm volatile("red.release.gpu.global.add.u32 [%0], 1;" ::"l"(&gs->pub) : "memory");
        }
        const uint32_t xoff = opaque(mat * 4096 + ((r ^ (4 * (mat & 1))) * 16), lane);
        const uint32_t aoff = opaque(S_A + (lane >> 1) * 32 + (((lane ^ mat) & 1) * 16), lane);
        const uint32_t moff = opaque(mat < 2 ? (r < 4 ? S_C + mat * 80 + r * 16 : 0) : (mat == 2 && r < 6) ? S_H + r * 16 : 0, lane);
        const uint32_t hoff = opaque(S_H + mat * 8, lane), hoff2 = opaque(S_H + 32 + g * 8, lane);
        const uint32_t psel = opaque((lane & 2) ? 0x7632 : 0x5410, lane);
        const uint64_t xl = __shfl_sync(0xffffffffu, (uint64_t)(x - 1024 + r * 16), lane);
        const uint64_t al = __shfl_sync(0xffffffffu, (uint64_t)(ea - 32 + (lane & 1) * 16), lane);
        const uint64_t ml = __shfl_sync(0xffffffffu, (uint64_t)(gs->list + (mat < 2 ? mat * 8 + 4 + r : hp16)), lane);
        int cur = __reduce_max_sync(0xffffffffu, pos) + h;
        pos = cur + NSLOT; end = __reduce_max_sync(0xffffffffu, end);

        int ev = h ? end : end - 12, state = h ? 2 : 0, tk = 0, nr = 0, prv = pos - 1;
        uint32_t inf = 0;
        auto take = [&]() {
            int v = 0;
            asm volatile("{.reg .pred p; setp.eq.s32 p, %2, 0; @p atom.relaxed.gpu.global.add.u32 %0, [%1], 1;}" : "+r"(v) : "l"(&gs->ticket), "r"(lane) : "memory");
            return v;
        };
        auto resolve = [&]() {
            const int k = __reduce_max_sync(0xffffffffu, tk);
            inf = 0;
            if (k < G * NPOOL) { const int l = k / G; inf = __ldcg(&gs->info[(k - l * G) * NPOOL + l]); tk = take(); }
        };
        uint32_t so = ring + h * SLOT, ph = 1;
        asm volatile("cp.async.wait_all;" ::: "memory");
        __syncwarp();
        while (true) {
            const uint32_t mi = max(moff >= S_H ? pos : cur, 0);
            const char* gm = (const char*)madw(mi, 256, ml);
            const uint32_t d0 = so + xoff;
            mbar_wait(so + S_EMPTY, ph);
            if (cur <= 0) break;
            const uint2 e = lds64(so + hoff), e2 = lds64(so + hoff2);
            const uint32_t s[4] = {e.x & 0xffffu, e.x >> 16, e.y & 0xffffu, e.y >> 16};
            const uint32_t id = __byte_perm(e2.x, e2.y, psel);
            cpa16z(so + aoff, (const char*)madw(id, 32, al), id);
            if (moff) cpa16z(so + moff, gm, mi);
#pragma unroll
            for (int j = 0; j < 4; j++) {
                const char* gx = (const char*)madw(s[j], 1024, xl);
#pragma unroll
                for (int k = 0; k < 8; k++) cpa16z((d0 ^ (j * 16)) + j * 1024 + k * 128, gx + k * 128, s[j]);
            }
            asm volatile("cp.async.mbarrier.arrive.noinc.shared::cta.b64 [%0];" ::"r"(so + S_FULL) : "memory");
            if (so == ring) so += 4 * SLOT; else { so -= SLOT; ph ^= 1; }
            cur = prv;
            pos += 4; prv = pos - 1;
            if (pos >= ev) {
                if (state == 0) { ev = end - 6; state = 1; tk = take(); }
                else if (state == 1) {
                    for (int it = 0; __any_sync(0xffffffffu, ld_acq(&gs->pub) < (unsigned)G); it++) spin_check(it);
                    resolve();
                    ev = end; state = 2;
                } else {
                    do {
                        const uint32_t mb = sm + O_MB + (nr & 31) * 8;
                        uint32_t rg;
                        nr++;
                        if (h == 0) {
                            rg = __reduce_max_sync(0xffffffffu, inf);
                            asm volatile("st.release.cta.shared.b64 [%0], %1;" ::"r"(mb), "l"(rg | (uint64_t)nr << 32) : "memory");
                            if (rg) resolve();
                        } else {
                            uint64_t m;
                            for (int it = 0;; it++) {
                                asm volatile("ld.acquire.cta.shared.b64 %0, [%1];" : "=l"(m) : "r"(mb) : "memory");
                                if (__all_sync(0xffffffffu, (int)(m >> 32) == nr)) break;
                                spin_check(it);
                            }
                            rg = __reduce_max_sync(0xffffffffu, (uint32_t)m);
                        }
                        const int ov = pos - end;
                        pos = rg ? (int)(rg & 0xffff) + ov : -(1 << 30);
                        if (ov) prv = pos - 1;
                        end = rg >> 16;
                    } while (pos >= end);
                    ev = end;
                }
            }
        }
        TSW(8 + (h & 1));
        if (lane == 0) sts32(so + S_C + 48, META_END);
        mbar_arrive(so + S_FULL);
        asm volatile("cp.async.wait_all;" ::: "memory");
    } else {
        asm volatile("setmaxnreg.inc.sync.aligned.u32 " STR(CREG) ";");
        const uint32_t xa = opaque(((mat >> 1) * 8 + r) * 1024 + (w >> 2) * 128 + (((2 * (w & 3) + (mat & 1)) ^ r) * 16), lane);
        const uint32_t aa = opaque(S_A + ((mat >> 1) * 8 + r) * 32 + (((mat & 1) ^ (r >> 2)) * 16), lane);
        const uint32_t ya = opaque(S_C + (mat & 1) * 80 + (mat >> 1) * 16, lane);
        const uint32_t yc = opaque(S_C + (mat < 2 ? mat * 80 + 32 : (r >> 2) == (mat & 1) ? (mat & 1) * 80 + (r & 3) * 16 : 64), lane);
        const uint32_t mm = opaque((lane & 15) == 12 ? 0xffffu : 0u, lane);
        const uint32_t na = opaque(mm ? sm + O_NODE + (lane >> 4) * 4 : sm + O_TRASH, lane);
        const uint32_t pw = sm + O_P + w * PW;
        const uint32_t fx = opaque((q < 3 ? pw + P_1P0 + 2 * q * PSBO + (mat & 1) * 128 : sm + O_TRASH + ((pw - sm - O_TRASH + 96) & 127)) + (r >> 2) * 16, lane);
        const uint32_t fyz = opaque(pw + (q < 3 ? (mat < 2 ? P_1P1 : P_1P2) + 2 * q * PSBO : mat < 2 ? P_0P0 : P_0P1) + (mat & 1) * 128 + (r >> 2) * 16, lane);
        uint32_t oh[4][2], eb[3];
#pragma unroll
        for (int c = 0; c < 8; c++) oh[c & 3][c >> 2] = opaque(g == c ? 0x3F803F80u : 0u, lane);
#pragma unroll
        for (int k = 0; k < 3; k++) {
            const unsigned short* ep = (const unsigned short*)eps + (g & 3) * 9 + (q & 1) * 6 + k;
            eb[k] = 0;
            if ((g & 3) < 3 && (q >> 1) == (g >> 2)) eb[k] = ep[0] | ((q & 1) ? 0u : (uint32_t)ep[3] << 16);
        }
        const bool l0 = opaque(lane == 0, lane);
        Acc A;
#pragma unroll
        for (int i = 0; i < 4; i++) { A.p00[i] = A.p110[i] = A.p10[0][i] = A.p10[1][i] = A.p10[2][i] = 0; A.t01[i] = A.m[0][i] = A.m[1][i] = A.m[2][i] = 0.f; }
        int slot = 0;
        bool w1ok = false;
        uint32_t so = sm + O_RING, ph = 0, a[4], ok, mt = 0;
        auto tile = [&](auto first) {
            constexpr bool F = decltype(first)::value;
            uint32_t yb[8], f[4][4], R[5][4];
            ldsm4t(f[0], so + xa);
            ldsm4(yb + 4, so + yc);
#pragma unroll
            for (int m = 1; m < 4; m++) ldsm4t(f[m], so + xa + m * 256);
            ldsm4(yb, so + ya);
            if (l0) mbar_arrive(so + S_EMPTY);
            so += SLOT;
            if (so == sm + O_RING + NSLOT * SLOT) { so = sm + O_RING; ph ^= 1; }
            if (F) {
                const uint32_t sof = (slot & 7) * 16 + (slot >> 3) * PSBO;
                sts32(na + 4 * slot, mt);
                flush(A, fx + sof, fyz + sof, oh, eb);
                slot += 2;
            }
#pragma unroll
            for (int p = 0; p < 5; p++) {
                float c[4];
                mma16z(c, wr[p], a[0], a[1]); R[p][0] = pack(c[0], c[1]); R[p][1] = pack(c[2], c[3]);
                mma16z(c, wr[p], a[2], a[3]); R[p][2] = pack(c[0], c[1]); R[p][3] = pack(c[2], c[3]);
            }
            asm volatile("{\n.reg .pred p;\nmbarrier.test_wait.parity.shared::cta.b64 p, [%5], %6;\nselp.u32 %4, 1, 0, p;\n"
                         "@p ldmatrix.sync.aligned.m8n8.x4.shared.b16 {%0,%1,%2,%3}, [%7];\n}"
                         : "+r"(a[0]), "+r"(a[1]), "+r"(a[2]), "+r"(a[3]), "=r"(ok) : "r"(so + S_FULL), "r"(ph), "r"(so + aa) : "memory");
            asm("lop3.b32 %0, %1, %2, %3, 0xa8;" : "=r"(mt) : "r"(yb[6]), "r"(yb[7]), "r"(mm));
            uint32_t u[4];
#pragma unroll
            for (int i = 0; i < 4; i++) {
                A.p00[i] = F ? hmul(f[0][i], R[0][i]) : hfma(f[0][i], R[0][i], A.p00[i]);
                u[i] = hmul(f[0][i], R[2][i]);
            }
            if (F) mma16z(A.t01, u, yb[6], yb[7]); else mma16(A.t01, u, yb[6], yb[7]);
#pragma unroll
            for (int k = 0; k < 3; k++) {
#pragma unroll
                for (int i = 0; i < 4; i++) {
                    A.p10[k][i] = F ? hmul(f[1 + k][i], R[3][i]) : hfma(f[1 + k][i], R[3][i], A.p10[k][i]);
                    u[i] = hmul(f[1 + k][i], R[4][i]);
                }
                if (F) mma16z(A.m[k], u, yb[6], yb[7]); else mma16(A.m[k], u, yb[6], yb[7]);
            }
#pragma unroll
            for (int i = 0; i < 4; i++) {
                uint32_t sdot = hfma(f[3][i], yb[4 + (i >> 1)], hfma(f[2][i], yb[2 + (i >> 1)], hmul(f[1][i], yb[i >> 1])));
                A.p110[i] = F ? hmul(sdot, R[1][i]) : hfma(sdot, R[1][i], A.p110[i]);
            }
            return __any_sync(0xffffffffu, mt != 0);
        };
        mbar_wait(so + S_FULL, 0);
        ldsm4(a, so + aa);
        TS(7);
        bool last = false;
        while (true) {
            while (!last) {
                last = tile(Bool<false>());
                if (!ok) { mbar_wait(so + S_FULL, ph); ldsm4(a, so + aa); }
            }
            last = tile(Bool<true>());
            if (slot == 16 || last) {
                const bool fin = __any_sync(0xffffffffu, mt == META_END);
                if (slot == 16 || fin) {
                    if (!w1ok) { mbar_wait(sm + O_WBB, 0); w1ok = true; }
                    asm volatile("fence.proxy.async.shared::cta;" ::: "memory");
                    bar_sync(1, 256);
                    float d0[8], d1[24];
                    const uint64_t db = (uint64_t)(((sm + O_P) >> 4) & 0x3fff) | (8ull << 16) | ((uint64_t)(PSBO / 16) << 32);
                    const uint64_t da = (uint64_t)(((sm + O_W1 + (w >> 2) * 49152) >> 4) & 0x3fff) | (1ull << 16) | (64ull << 32) | (1ull << 62);
                    asm volatile("wgmma.fence.sync.aligned;" ::: "memory");
#pragma unroll
                    for (int k = 0; k < 16; k++) wg_rs16(d0, w0[k], db + (((k & 7) * PW + ((k >> 3) ? P_0P1 : P_0P0)) >> 4), k);
                    asm volatile("wgmma.commit_group.sync.aligned;" ::: "memory");
#pragma unroll
                    for (int k = 0; k < 24; k++)
                        wg_ss48(d1, da + k * 128, db + (((k & 7) * PW + ((k >> 3) == 0 ? P_1P0 : (k >> 3) == 1 ? P_1P1 : P_1P2)) >> 4), k);
                    asm volatile("wgmma.commit_group.sync.aligned;" ::: "memory");
                    int nd[4];
#pragma unroll
                    for (int it = 0; it < 4; it++) nd[it] = lds32(sm + O_NODE + 4 * (it * 4 + mat));
                    asm volatile("wgmma.wait_group.sync.aligned 1;" ::: "memory");
#pragma unroll
                    for (int i = 0; i < 8; i++) asm volatile("" : "+f"(d0[i])::"memory");
                    uint32_t o[4][4];
                    float gt[8];
#pragma unroll
                    for (int i = 0; i < 8; i++) gt[i] = __fdividef(1.f, 1.f + __expf(-d0[i]));
#pragma unroll
                    for (int i = 0; i < 4; i++) o[0][i] = pack(d0[2 * i], d0[2 * i + 1]);
#pragma unroll
                    for (int i = 0; i < 8; i++) asm volatile("" : "+f"(gt[i])::"memory");
                    asm volatile("wgmma.wait_group.sync.aligned 0;" ::: "memory");
#pragma unroll
                    for (int i = 0; i < 24; i++) asm volatile("" : "+f"(d1[i])::"memory");
                    bar_sync(1, 256);
#pragma unroll
                    for (int i = 0; i < 4; i++)
#pragma unroll
                        for (int j = 0; j < 3; j++) o[1 + j][i] = pack(d1[8 * j + 2 * i] * gt[2 * i], d1[8 * j + 2 * i + 1] * gt[2 * i + 1]);
                    const uint32_t sg = sm + O_P + (w & 4) * PW + ((mat >> 1) * 8 + r) * 128 + (((2 * (w & 3) + (mat & 1)) ^ r) * 16);
#pragma unroll
                    for (int j = 0; j < 4; j++) stsm4t(sg + j * PW, o[j][0], o[j][1], o[j][2], o[j][3]);
                    bar_sync(2 + (w >> 2), 128);
                    uint4 v[4];
#pragma unroll
                    for (int it = 0; it < 4; it++) v[it] = lds128(pw + (it * 4 + mat) * 128 + ((r ^ ((it * 4 + mat) & 7)) * 16));
                    char* op = out - 1024 + (w & 3) * 256 + (w >> 2) * 128 + r * 16;
#pragma unroll
                    for (int it = 0; it < 4; it++) if (it * 4 + mat < slot && nd[it]) *(uint4*)(op + (size_t)nd[it] * 1024) = v[it];
                    __syncwarp();
                    slot = 0;
                }
                if (fin) break;
            }
            if (!ok) { mbar_wait(so + S_FULL, ph); ldsm4(a, so + aa); }
        }
        TS(10);
        if (t == 0) {
            __threadfence();
            if (atomicInc(&gs->done, G - 1) == G - 1) { gs->pub = 0; gs->ticket = 0; gs->epoch = epoch + 1; }
        }
    }
}

typedef CUresult (*EncFn)(CUtensorMap*, CUtensorMapDataType, cuuint32_t, void*, const cuuint64_t*, const cuuint64_t*,
                          const cuuint32_t*, const cuuint32_t*, CUtensorMapInterleave, CUtensorMapSwizzle,
                          CUtensorMapL2promotion, CUtensorMapFloatOOBfill);

void make_map(EncFn fn, CUtensorMap* m, void* p, int rows, int cols, int brows, int rank) {
    cuuint64_t dims[3] = {(cuuint64_t)(rank == 3 ? 64 : cols), (cuuint64_t)rows, (cuuint64_t)cols / 64}, strides[2] = {(cuuint64_t)cols * 2, 128};
    cuuint32_t box[3] = {64, (cuuint32_t)brows, (cuuint32_t)cols / 64}, es[3] = {1, 1, 1};
    fn(m, CU_TENSOR_MAP_DATA_TYPE_BFLOAT16, rank, p, dims, strides, box, es, CU_TENSOR_MAP_INTERLEAVE_NONE,
       CU_TENSOR_MAP_SWIZZLE_128B, CU_TENSOR_MAP_L2_PROMOTION_NONE, CU_TENSOR_MAP_FLOAT_OOB_FILL_NONE);
}

}

extern "C" void kernel_launch(void* const* d_in, const int* in_sizes, int n_in, void* d_out, int out_size) {
    static EncFn enc = nullptr;
    static void* scratch = nullptr;
    if (!enc) {
        void* fn = nullptr;
        cudaDriverEntryPointQueryResult qr;
        cudaGetDriverEntryPoint("cuTensorMapEncodeTiled", &fn, cudaEnableDefault, &qr);
        enc = (EncFn)fn;
        cudaGetSymbolAddress(&scratch, g_scratch);
        cudaFuncSetAttribute(tp_kernel, cudaFuncAttributeMaxDynamicSharedMemorySize, SMEM_BYTES);
    }
    CUtensorMap m_wr, m_w0, m_w1;
    make_map(enc, &m_wr, d_in[5], 16, 640, 16, 3);
    make_map(enc, &m_w0, d_in[6], 256, 128, 256, 3);
    make_map(enc, &m_w1, d_in[7], 384, 128, 192, 2);
    tp_kernel<<<G, NT, SMEM_BYTES>>>((const int4*)d_in[4], (const int4*)d_in[3], (const char*)d_in[1], (Scratch*)scratch,
                                     (const char*)d_in[0], (const char*)d_in[2], (const __nv_bfloat16*)d_in[8], (char*)d_out,
                                     m_wr, m_w0, m_w1);
}
```

```cpp
#include <cuda_runtime.h>
#include <cuda_bf16.h>
#include <cuda.h>
#include <stdint.h>
#include <stddef.h>

namespace {

constexpr int NN = 10000;
constexpr int NE = 320000;
constexpr int G = 132;
constexpr int NT = 384;
constexpr int CH = 2432;
constexpr int NLOC = (NN + G - 1) / G;
#define NPOOL 5
constexpr int NPAIR = NLOC / 2, NPRIV = NPAIR - NPOOL;
constexpr int SEGW = 11;
constexpr uint32_t META_END = 0x3fff;

#define NSLOT 5
#define PFA 16
#define PFB 20
#define PFC 20
#define PFD 20
#define STAG (2 * (b & 7))
#define NULLP(v) v
#define CREG 216
#define PREG 72
#define STR2(x) #x
#define STR(x) STR2(x)

constexpr int S_A = 16384, S_C = S_A + 512, S_FULL = S_C + 144, S_EMPTY = S_FULL + 8, S_H = S_C + 160, SLOT = 17152;

constexpr int PSBO = 272;
constexpr int PB1 = 5 * PSBO + 256, PB0 = PSBO + 256;
constexpr int P_1P0 = 0, P_1P1 = PB1, P_0P1 = 2 * PB1, P_0P0 = P_0P1 + PB0, P_1P2 = P_0P0 + PB0;
constexpr int PW = P_1P2 + PB1;

constexpr int O_W1 = 0;
constexpr int O_P = 98304;
constexpr int O_RING = O_P + 8 * PW;
constexpr int O_TRASH = O_RING + 5 * SLOT;
constexpr int O_WBA = O_TRASH + 512, O_WBB = O_WBA + 8, O_WBC = O_WBA + 16, O_WBD = O_WBA + 24, O_NODE = O_WBA + 48;
constexpr int O_SUM = O_NODE + 64, O_MB = O_SUM + 16;
constexpr int SMEM_BYTES = O_MB + 256;
constexpr int CAPT = 240, LH = CAPT * 128;
constexpr int O_L = 0, LZ = 2 * LH / (NT * 16), O_W0S = O_L + 2 * LH, O_OUT = O_W0S + 65536, O_RH = O_OUT + CH * 8;
constexpr int O_KT = O_RING + SLOT, O_SRC = O_RING + 2 * SLOT;
constexpr int O_BCNT = O_SRC + CH * 4, O_NCUR = O_BCNT + 640, O_NCNT = O_NCUR + 320;
constexpr int O_BOFF = O_NCNT + 512, O_SORT = O_BOFF + 640, O_NOFF = O_SORT + 320;
constexpr int O_WR0 = (O_RING + 3 * SLOT + 1023) / 1024 * 1024, O_WR1 = (O_RING + 4 * SLOT + 1023) / 1024 * 1024;
constexpr int TBIG = G * CAPT + 8, NTILE = TBIG + NE / 8 + G * (NLOC + 5);
static_assert(SMEM_BYTES <= 232448 && NSLOT == 5 && CAPT % 16 == 0 && NTILE < (1 << 18), "smem");
static_assert(LZ * NT * 16 == 2 * LH && O_W0S % 1024 == 0 && O_RH + CH * 6 <= O_RING + S_C && G * 128 <= S_C && O_NOFF + 512 <= O_SRC + S_C, "staging");
static_assert(O_RING % 128 == 0 && SLOT % 128 == 0 && 2 * LH <= O_P, "layout");
static_assert(G * CH >= NE && NE % 8 == 0 && CH < 4096 && CH / 8 <= 320 && NE < (1 << 21), "chunks");
static_assert(SEGW * (NT / 32) == G && G <= 160 && G % 4 == 0, "segments");
static_assert(NLOC % 4 == 0 && NLOC < 80 && NLOC * 4 <= 320 && NN < META_END && NPRIV >= 30, "scan width");

struct __align__(128) Scratch {
    uint32_t keys[G * G * 32];
    uint64_t vals[G * CH];
    uint32_t more[G * CH];
    uint32_t epoch[G * 32];
    uint32_t info[G * NPOOL];
    unsigned done, pad0[31], ticket, pad1[31 + 32 - G * NPOOL % 32];
    uint4 list[2 * NTILE * 8];
};
static_assert(offsetof(Scratch, list) % 128 == 0, "list");
__device__ Scratch g_scratch;
#define TS(i)
#define TSW(i)
#define TV(i, v)

constexpr int SPIN_LIMIT = 1 << 24;

__device__ __forceinline__ void mbar_init(uint32_t a, int c) { asm volatile("mbarrier.init.shared::cta.b64 [%0], %1;" ::"r"(a), "r"(c) : "memory"); }
__device__ __forceinline__ void mbar_expect(uint32_t a, int b) { asm volatile("mbarrier.arrive.expect_tx.shared::cta.b64 _, [%0], %1;" ::"r"(a), "r"(b) : "memory"); }
__device__ __forceinline__ void mbar_arrive(uint32_t a) { asm volatile("mbarrier.arrive.shared::cta.b64 _, [%0];" ::"r"(a) : "memory"); }
__device__ __forceinline__ void mbar_wait(uint32_t a, uint32_t ph) {
    asm volatile("{\n.reg .pred p, q;\n.reg .u32 it;\n"
                 "mbarrier.try_wait.parity.shared::cta.b64 p, [%0], %1;\n"
                 "@p bra DONE;\n"
                 "mov.u32 it, 0;\n"
                 "LOOP:\n"
                 "mbarrier.try_wait.parity.shared::cta.b64 p, [%0], %1;\n"
                 "@p bra DONE;\n"
                 "add.u32 it, it, 1;\n"
                 "setp.gt.u32 q, it, %2;\n"
                 "@q trap;\n"
                 "bra LOOP;\n"
                 "DONE:\n}" ::"r"(a), "r"(ph), "n"(SPIN_LIMIT) : "memory");
}
__device__ __forceinline__ void spin_check(int it) {
    asm volatile("{\n.reg .pred q;\nsetp.gt.s32 q, %0, %1;\n@q trap;\n}" ::"r"(it), "n"(SPIN_LIMIT));
}
__device__ __forceinline__ void tma2d(uint32_t dst, const CUtensorMap* m, int c0, int c1, uint32_t bar) {
    asm volatile("cp.async.bulk.tensor.2d.shared::cluster.global.mbarrier::complete_tx::bytes [%0], [%1, {%3, %4}], [%2];"
                 ::"r"(dst), "l"(m), "r"(bar), "r"(c0), "r"(c1) : "memory");
}
__device__ __forceinline__ void cpa16z(uint32_t d, const void* g, uint32_t v) {
    asm volatile("{\n.reg .pred p;\nsetp.eq.u32 p, %2, 0;\ncp.async.cg.shared.global [%0], [%1], 16, p;\n}" ::"r"(d), "l"(g), "r"(v) : "memory");
}
__device__ __forceinline__ void ldsm4(uint32_t* r, uint32_t a) { asm volatile("ldmatrix.sync.aligned.m8n8.x4.shared.b16 {%0,%1,%2,%3}, [%4];" : "=r"(r[0]), "=r"(r[1]), "=r"(r[2]), "=r"(r[3]) : "r"(a) : "memory"); }
__device__ __forceinline__ void ldsm4t(uint32_t* r, uint32_t a) { asm volatile("ldmatrix.sync.aligned.m8n8.x4.trans.shared.b16 {%0,%1,%2,%3}, [%4];" : "=r"(r[0]), "=r"(r[1]), "=r"(r[2]), "=r"(r[3]) : "r"(a) : "memory"); }
__device__ __forceinline__ void stsm4t(uint32_t a, uint32_t r0, uint32_t r1, uint32_t r2, uint32_t r3) { asm volatile("stmatrix.sync.aligned.m8n8.x4.trans.shared.b16 [%0], {%1,%2,%3,%4};" ::"r"(a), "r"(r0), "r"(r1), "r"(r2), "r"(r3) : "memory"); }
__device__ __forceinline__ void stsm2t(uint32_t a, uint32_t r0, uint32_t r1) { asm volatile("stmatrix.sync.aligned.m8n8.x2.trans.shared.b16 [%0], {%1,%2};" ::"r"(a), "r"(r0), "r"(r1) : "memory"); }
__device__ __forceinline__ void mma16(float* d, const uint32_t* a, uint32_t b0, uint32_t b1) {
    asm("mma.sync.aligned.m16n8k16.row.col.f32.bf16.bf16.f32 {%0,%1,%2,%3}, {%4,%5,%6,%7}, {%8,%9}, {%0,%1,%2,%3};"
        : "+f"(d[0]), "+f"(d[1]), "+f"(d[2]), "+f"(d[3]) : "r"(a[0]), "r"(a[1]), "r"(a[2]), "r"(a[3]), "r"(b0), "r"(b1));
}
__device__ __forceinline__ void mma8(float* d, uint32_t a0, uint32_t a1, uint32_t b0) {
    asm("mma.sync.aligned.m16n8k8.row.col.f32.bf16.bf16.f32 {%0,%1,%2,%3}, {%4,%5}, {%6}, {%0,%1,%2,%3};"
        : "+f"(d[0]), "+f"(d[1]), "+f"(d[2]), "+f"(d[3]) : "r"(a0), "r"(a1), "r"(b0));
}
__device__ __forceinline__ void mma16z(float* d, const uint32_t* a, uint32_t b0, uint32_t b1) {
    asm("mma.sync.aligned.m16n8k16.row.col.f32.bf16.bf16.f32 {%0,%1,%2,%3}, {%4,%5,%6,%7}, {%8,%9}, {%10,%10,%10,%10};"
        : "=f"(d[0]), "=f"(d[1]), "=f"(d[2]), "=f"(d[3]) : "r"(a[0]), "r"(a[1]), "r"(a[2]), "r"(a[3]), "r"(b0), "r"(b1), "f"(0.f));
}
__device__ __forceinline__ uint32_t pack(float lo, float hi) { uint32_t r; asm("cvt.rn.bf16x2.f32 %0, %1, %2;" : "=r"(r) : "f"(hi), "f"(lo)); return r; }
__device__ __forceinline__ uint32_t hmul(uint32_t a, uint32_t b) { uint32_t r; asm("mul.rn.bf16x2 %0, %1, %2;" : "=r"(r) : "r"(a), "r"(b)); return r; }
__device__ __forceinline__ uint32_t hfma(uint32_t a, uint32_t b, uint32_t c) { uint32_t r; asm("fma.rn.bf16x2 %0, %1, %2, %3;" : "=r"(r) : "r"(a), "r"(b), "r"(c)); return r; }
__device__ __forceinline__ uint4 lds128(uint32_t a) { uint4 v; asm volatile("ld.shared.v4.u32 {%0,%1,%2,%3}, [%4];" : "=r"(v.x), "=r"(v.y), "=r"(v.z), "=r"(v.w) : "r"(a) : "memory"); return v; }
__device__ __forceinline__ void sts128(uint32_t a, uint4 v) { asm volatile("st.shared.v4.u32 [%0], {%1,%2,%3,%4};" ::"r"(a), "r"(v.x), "r"(v.y), "r"(v.z), "r"(v.w) : "memory"); }
__device__ __forceinline__ int lds32(uint32_t a) { int v; asm volatile("ld.shared.u32 %0, [%1];" : "=r"(v) : "r"(a) : "memory"); return v; }
__device__ __forceinline__ void sts32(uint32_t a, int v) { asm volatile("st.shared.u32 [%0], %1;" ::"r"(a), "r"(v) : "memory"); }
__device__ __forceinline__ int atoms_add(uint32_t a, int v) { int r; asm volatile("atom.shared.add.u32 %0, [%1], %2;" : "=r"(r) : "r"(a), "r"(v) : "memory"); return r; }
__device__ __forceinline__ uint32_t ld_rlx(const void* p) { uint32_t v; asm volatile("ld.relaxed.gpu.global.u32 %0, [%1];" : "=r"(v) : "l"(p) : "memory"); return v; }
__device__ __forceinline__ void st_rlx(void* p, uint32_t v) { asm volatile("st.relaxed.gpu.global.u32 [%0], %1;" ::"l"(p), "r"(v) : "memory"); }
__device__ __forceinline__ void bulk(uint32_t dst, const void* g, int n, uint32_t bar) {
    asm volatile("cp.async.bulk.shared::cluster.global.mbarrier::complete_tx::bytes [%0], [%1], %2, [%3];" ::"r"(dst), "l"(g), "r"(n), "r"(bar) : "memory");
}
__device__ __forceinline__ void bulk_st(void* g, uint32_t src, int n) {
    asm volatile("cp.async.bulk.global.shared::cta.bulk_group [%0], [%1], %2;\ncp.async.bulk.commit_group;" ::"l"(g), "r"(src), "r"(n) : "memory");
}
__device__ __forceinline__ uint2 lds64(uint32_t a) { uint2 v; asm volatile("ld.shared.v2.u32 {%0,%1}, [%2];" : "=r"(v.x), "=r"(v.y) : "r"(a) : "memory"); return v; }
__device__ __forceinline__ void sts64(uint32_t a, uint32_t x, uint32_t y) { asm volatile("st.shared.v2.u32 [%0], {%1,%2};" ::"r"(a), "r"(x), "r"(y) : "memory"); }
__device__ __forceinline__ void tma3d(uint32_t dst, const CUtensorMap* m, int c2, uint32_t bar) {
    asm volatile("cp.async.bulk.tensor.3d.shared::cluster.global.mbarrier::complete_tx::bytes [%0], [%1, {%3, %3, %4}], [%2];"
                 ::"r"(dst), "l"(m), "r"(bar), "r"(0), "r"(c2) : "memory");
}
__device__ __forceinline__ void pf_l2(const void* g, int n) {
    asm volatile("{.reg .pred p; setp.gt.s32 p, %1, 0; @p cp.async.bulk.prefetch.L2.global [%0], %1;}" ::"l"(g), "r"(n) : "memory");
}
__device__ __forceinline__ void fence_async() { asm volatile("fence.proxy.async.shared::cta;" ::: "memory"); }
__device__ __forceinline__ uint64_t madw(uint32_t a, uint32_t b, uint64_t c) { uint64_t r; asm("mad.wide.u32 %0, %1, %2, %3;" : "=l"(r) : "r"(a), "r"(b), "l"(c)); return r; }
__device__ __forceinline__ uint32_t opaque(uint32_t v, int lane) { return __shfl_sync(0xffffffffu, v, lane); }
__device__ __forceinline__ void bar_sync(int id, int n) { asm volatile("bar.sync %0, %1;" ::"r"(id), "r"(n) : "memory"); }

__device__ __forceinline__ void wg_rs16(float* d, const uint32_t* a, uint64_t db, int sc) {
    asm volatile("{.reg .pred p; setp.ne.b32 p, %13, 0;\n"
                 "wgmma.mma_async.sync.aligned.m64n16k16.f32.bf16.bf16 {%0,%1,%2,%3,%4,%5,%6,%7}, {%8,%9,%10,%11}, %12, p, 1, 1, 0;}"
                 : "+f"(d[0]), "+f"(d[1]), "+f"(d[2]), "+f"(d[3]), "+f"(d[4]), "+f"(d[5]), "+f"(d[6]), "+f"(d[7])
                 : "r"(a[0]), "r"(a[1]), "r"(a[2]), "r"(a[3]), "l"(db), "r"(sc));
}
__device__ __forceinline__ void wg_ss48(float* d, uint64_t da, uint64_t db, int sc) {
    asm volatile("{.reg .pred p; setp.ne.b32 p, %26, 0;\n"
                 "wgmma.mma_async.sync.aligned.m64n48k16.f32.bf16.bf16 {%0,%1,%2,%3,%4,%5,%6,%7,%8,%9,%10,%11,%12,%13,%14,%15,%16,%17,%18,%19,%20,%21,%22,%23}, %24, %25, p, 1, 1, 1, 0;}"
                 : "+f"(d[0]), "+f"(d[1]), "+f"(d[2]), "+f"(d[3]), "+f"(d[4]), "+f"(d[5]), "+f"(d[6]), "+f"(d[7]),
                   "+f"(d[8]), "+f"(d[9]), "+f"(d[10]), "+f"(d[11]), "+f"(d[12]), "+f"(d[13]), "+f"(d[14]), "+f"(d[15]),
                   "+f"(d[16]), "+f"(d[17]), "+f"(d[18]), "+f"(d[19]), "+f"(d[20]), "+f"(d[21]), "+f"(d[22]), "+f"(d[23])
                 : "l"(da), "l"(db), "r"(sc));
}

__device__ __forceinline__ int warp_incl(int v) {
#pragma unroll
    for (int o = 1; o < 32; o <<= 1)
        asm volatile("{.reg .pred p; .reg .b32 u; shfl.sync.up.b32 u|p, %0, %1, 0, 0xffffffff; @p add.s32 %0, %0, u;}" : "+r"(v) : "r"(o));
    return v;
}
__device__ __forceinline__ void ldg128(uint32_t* r, const void* p, bool on) {
    asm volatile("{.reg .pred p; setp.ne.u32 p, %5, 0; @p ld.global.nc.v4.u32 {%0,%1,%2,%3}, [%4];}"
                 : "=r"(r[0]), "=r"(r[1]), "=r"(r[2]), "=r"(r[3]) : "l"(p), "r"((uint32_t)on));
}

template <bool B> struct Bool { static constexpr bool value = B; };
struct Acc {
    uint32_t p00[4], p110[4], p10[3][4];
    float t01[4], m[3][4];
};

__device__ __forceinline__ void flush(const Acc& A, uint32_t ax, uint32_t ayz, const uint32_t (*oh)[2], const uint32_t* eb) {
    float y[4], z[4];
    const uint32_t mp[4] = {pack(A.m[0][0], A.m[0][1]), pack(A.m[0][2], A.m[0][3]), pack(A.m[1][0], A.m[1][1]), pack(A.m[1][2], A.m[1][3])};
    mma16z(y, A.p10[0], oh[0][0], oh[0][1]);
    mma16z(z, A.p110, oh[3][0], oh[3][1]);
    mma16(y, A.p10[1], oh[1][0], oh[1][1]);
    mma16(z, mp, eb[0], eb[1]);
    mma16(y, A.p10[2], oh[2][0], oh[2][1]);
    mma8(z, pack(A.m[2][0], A.m[2][1]), pack(A.m[2][2], A.m[2][3]), eb[2]);
    mma16(y, A.p00, oh[3][0], oh[3][1]);
    stsm2t(ax, pack(A.t01[0], A.t01[1]), pack(A.t01[2], A.t01[3]));
    stsm4t(ayz, pack(y[0], y[1]), pack(y[2], y[3]), pack(z[0], z[1]), pack(z[2], z[3]));
}

__global__ void __launch_bounds__(NT, 1)
tp_kernel(const int4* __restrict__ dst, const int4* __restrict__ src, const char* __restrict__ rhat, Scratch* __restrict__ gs,
          const char* __restrict__ x, const char* __restrict__ ea, const __nv_bfloat16* __restrict__ eps, char* __restrict__ out,
          const __grid_constant__ CUtensorMap m_wr, const __grid_constant__ CUtensorMap m_w0, const __grid_constant__ CUtensorMap m_w1) {
    extern __shared__ __align__(1024) char smem_raw[];
    const uint32_t sm = (uint32_t)__cvta_generic_to_shared(smem_raw);
    int t;
    asm volatile("mov.u32 %0, %%tid.x;" : "=r"(t));
    const int w = t >> 5, lane = t & 31, b = blockIdx.x;

    const int g = lane >> 2, q = lane & 3, mat = lane >> 3, r = lane & 7;
    const int e0 = b * CH + t * 8, ne = min(CH, NE - b * CH);
    const bool act = t * 8 < ne;
    uint32_t d[8];
#pragma unroll
    for (int k = 0; k < 2; k++) ldg128(d + 4 * k, dst + e0 / 4 + k, act);
    uint32_t tag = ld_rlx(&gs->epoch[b * 32]), epl;
    asm volatile("ld.global.nc.u16 %0, [%1];" : "=r"(epl) : "l"(eps + min(lane, 26)));
    if (t < 60) sts128(sm + O_BCNT + 16 * t, make_uint4(0, 0, 0, 0));
    if (t == NT - 1) {
#pragma unroll
        for (int i = 0; i < 4; i++) mbar_init(sm + O_WBA + 8 * i, 1);
        fence_async();
        mbar_expect(sm + O_WBC, ne * 10); mbar_expect(sm + O_WBA, 20480); mbar_expect(sm + O_WBB, 98304); mbar_expect(sm + O_WBD, 65536);
        spin_check(tag);
        bulk(sm + O_RH, rhat + b * (CH * 6), ne * 6, sm + O_WBC);
        bulk(sm + O_SRC, src + b * (CH / 4), ne * 4, sm + O_WBC);
        tma3d(sm + O_WR0, &m_wr, 0, sm + O_WBA);
        tma3d(sm + O_WR1, &m_wr, 5, sm + O_WBA);
        tma3d(sm + O_W0S, &m_w0, 0, sm + O_WBD);
    }
    if (t == 320) {
#pragma unroll
        for (int i = 0; i < NSLOT; i++) {
            sts128(sm + O_RING + i * SLOT + S_C + 64, make_uint4(0, 0, 0, 0));
            mbar_init(sm + O_RING + i * SLOT + S_FULL, 32); mbar_init(sm + O_RING + i * SLOT + S_EMPTY, 8);
        }
    }
#pragma unroll
    for (int k = 0; k < LZ; k++) sts128(sm + O_L + 16 * (t + k * NT), make_uint4(0, 0, 0, 0));
    if (t < 80) sts32(sm + O_NCNT + 4 * t, t <= NLOC ? 4 * t : 0);
    if (t < 84) sts32(sm + O_NODE + 4 * t, 0);
    uint32_t ba[8], rk[8];
    auto pfx = [&](int r0, int n) {
        if (n) pf_l2(x + (b * NLOC + r0) * 1024, min(n, NN - b * NLOC - r0) * 1024);
    };
    if (w < 10) bar_sync(1, 320);
    tag = (tag + 1) << 30;
    if (act) {
#pragma unroll
        for (int i = 0; i < 8; i++) {
            const uint32_t l = __umulhi(d[i], (uint32_t)((1ull << 32) / G + 1));
            ba[i] = d[i] * 4 - l * (4 * G);
            d[i] = l * 4 + (tag + ((e0 + i + 1) << 9) + 4);
            rk[i] = atoms_add(sm + O_BCNT + ba[i], 4);
        }
#pragma unroll
        for (int i = 0; i < 8; i++)
            asm volatile("{.reg .pred p; setp.lt.u32 p, %2, 124; @p st.shared.u32 [%0], %1;}"
                         ::"r"(sm + O_KT + ba[i] * 32 + ((ba[i] + rk[i]) & 127)), "r"(d[i]), "r"(rk[i]) : "memory");
    }
    TS(0);
    __syncthreads();
    {
        int v[5], sum = 0;
#pragma unroll
        for (int i = 0; i < 5; i++) { v[i] = lds32(sm + O_BCNT + 4 * (lane * 5 + i)); sum += v[i]; }
        int e = warp_incl(sum) - sum;
        if (w == 10) {
#pragma unroll
            for (int i = 0; i < 5; i++) {
                const int k = lane * 5 + i;
                if (k < G) sts32(sm + O_KT + k * 128 + ((k * 4 + 124) & 127), tag | v[i] << 10 | e >> 2);
                e += v[i];
            }
            __syncwarp();
            if (lane == 0) {
                fence_async();
                bulk_st(&gs->keys[b * (G * 32)], sm + O_KT, G * 128);
                pfx(0, PFA);
            }
        } else {
#pragma unroll
            for (int i = 0; i < 5; i++) { sts32(sm + O_BOFF + 4 * (lane * 5 + i), e); e += v[i]; }
        }
        __syncwarp();
    }
    TS(11);
    const uint32_t sw = (uint32_t)(((2 * (w & 3) + (mat & 1)) ^ r) * 16 + ((mat >> 1) * 8 + r) * 128);
    uint32_t wr[5][4];
    const uint32_t* kp = &gs->keys[(w * SEGW * G + b) * 32 + ((lane + b) & 31)];
    uint32_t kv[SEGW + 1], ho[SEGW + 1], nk[SEGW + 1], old;
    if (act) {
        uint32_t mx = 0;
#pragma unroll
        for (int i = 0; i < 8; i++) { mx = max(mx, rk[i]); ba[i] = rk[i] + lds32(sm + O_BOFF + ba[i]); }
        if (mx >= 124) {
#pragma unroll
            for (int i = 0; i < 8; i++)
                if (rk[i] >= 124) st_rlx(&gs->more[b * CH + (ba[i] >> 2)], d[i]);
        }
    }
    if (w < 8) {
        mbar_wait(sm + O_WBA, 0);
#pragma unroll
        for (int p = 0; p < 5; p++) {
            const int c = 2 * p + (w >> 2);
            ldsm4t(wr[p], sm + (c < 5 ? O_WR0 : O_WR1 - 5 * 2048) + c * 2048 + sw);
        }
    }
    TS(21);
    mbar_wait(sm + O_WBC, 0);
    TS(22);
    if (act) {
        uint32_t s[8], y[12];
#pragma unroll
        for (int k = 0; k < 3; k++) *(uint4*)&y[4 * k] = lds128(sm + O_RH + t * 48 + k * 16);
#pragma unroll
        for (int k = 0; k < 2; k++) *(uint4*)&s[4 * k] = lds128(sm + O_SRC + t * 32 + k * 16);
#pragma unroll
        for (int i = 0; i < 8; i++) {
            const int k = 3 * i / 2;
            sts64(sm + O_OUT + ba[i] * 2, i & 1 ? __byte_perm(y[k], y[k + 1], 0x5432) : y[k],
                  __byte_perm(y[k + 1], s[i] + (tag >> 16) + 1, i & 1 ? 0x5432 : 0x5410));
        }
    }
    TS(12);
    if (w < 10) asm volatile("bar.arrive 4, 352;" ::: "memory");
    if (w == 11) {
        bar_sync(4, 352);
        if (lane == 0) { fence_async(); bulk_st(&gs->vals[b * CH], sm + O_OUT, ne * 8); pfx(PFA, PFB); }
        __syncwarp();
    }

    const uint32_t am = lane < 31 ? 511 : 0, none = tag | (320 + 4 * lane);
    auto check = [&]() {
        old = 0;
#pragma unroll
        for (int j = 0; j < SEGW; j++) {
            ho[j] = __shfl_sync(0xffffffffu, kv[j], 31);
            kv[j] = ho[j] >= (lane < 31 ? tag + ((lane + 1) << 12) : 0u) ? kv[j] : none;
            old |= kv[j] ^ tag;
        }
        return __any_sync(0xffffffffu, old >> 30);
    };
#pragma unroll
    for (int j = 0; j < SEGW; j++) kv[j] = ld_rlx(kp + j * (G * 32));
    TS(1);
    TV(19, 0);
    for (int it = 0; check(); it++) {
        spin_check(it);
        if (it == 0) TS(20);
        TV(19, (it + 1) * 100);
#pragma unroll
        for (int j = 0; j < SEGW; j++)
            if (__any_sync(0xffffffffu, (kv[j] ^ tag) >> 30)) kv[j] = ld_rlx(kp + j * (G * 32));
    }
    TS(3);
    kv[SEGW] = none; ho[SEGW] = 0;
    bool slow = false;
    const bool more = __any_sync(0xffffffffu, lane == 31 && (old & 0xfe0000));
    if (more) {
        int c = lane;
#pragma unroll
        for (int j = 0; j < SEGW; j++) {
            const int n = max((int)(ho[j] >> 12 & 0xfff) - 31, 0);
            if ((unsigned)c < (unsigned)n) ho[SEGW] = j * CH + (ho[j] & 0xfff) + 31 + c - lane;
            c -= n;
        }
        slow = lane == 31 && c < 0;
        if (c < 0 && lane < 31)
            for (int it = 0; ((kv[SEGW] = ld_rlx(&gs->more[w * SEGW * CH + lane + ho[SEGW]])) ^ tag) >> 30; it++) spin_check(it);
        __syncwarp();
    }
    uint32_t na_[SEGW + 1];
#pragma unroll
    for (int j = 0; j <= SEGW; j++) {
        na_[j] = (kv[j] & am) | (none & 511 & ~am);
        nk[j] = atoms_add(sm + O_NCNT + na_[j], 512);
    }
    auto visit = [&](auto f) {
#pragma unroll 1
        for (int j = 0; j < SEGW; j++) {
            const uint32_t* kl = &gs->keys[((w * SEGW + j) * G + b) * 32];
            const uint32_t h = ld_rlx(kl + ((31 + b) & 31));
#pragma unroll 1
            for (int i = lane; i < (h >> 12 & 0xfff); i += 32) {
                const int o = (w * SEGW + j) * CH + (h & 0xfff) + i;
                uint32_t k;
                int it = 0;
                do { k = ld_rlx(i < 31 ? kl + ((i + b) & 31) : &gs->more[o]); spin_check(it++); } while ((k ^ tag) >> 30);
                f(k, o, i);
            }
        }
    };
    slow = __syncthreads_or(slow);
    if (slow) {
        if (t < 80) sts32(sm + O_NCNT + 4 * t, t <= NLOC ? 4 * t : 0);
        __syncthreads();
        visit([&](uint32_t k, int, int) { atoms_add(sm + O_NCNT + (k & 511), 512); });
        __syncthreads();
    }
    TS(4);
    if (t == 352) pfx(PFA + PFB, PFC);
    if (w < 10) {
        const uint32_t key = lds32(sm + O_NCNT + 4 + (t & ~3));
        uint4 k[5];
#pragma unroll
        for (int i = 0; i < 5; i++) k[i] = lds128(sm + O_NCNT + q * 80 + i * 16);
        uint32_t c[4] = {0, 0, 0, 0};
#pragma unroll
        for (int i = 0; i < 5; i++) { c[0] += (key - k[i].x) >> 31; c[1] += (key - k[i].y) >> 31; c[2] += (key - k[i].z) >> 31; c[3] += (key - k[i].w) >> 31; }
        int rank = c[0] + c[1] + c[2] + c[3];
        rank += __shfl_xor_sync(0xffffffffu, rank, 1);
        rank += __shfl_xor_sync(0xffffffffu, rank, 2);
        if (t < NLOC * 4) sts32(sm + O_SORT + 4 * rank, key);
    }
    __syncthreads();
    TS(2);
    const bool on = lane < NLOC / 4;
    const uint4 k4 = lds128(sm + O_SORT + 16 * (on ? lane : 0));
    const uint32_t ks[4] = {k4.x, k4.y, k4.z, k4.w};
    const int n0 = on ? max(1u, (ks[0] + 3584) >> 12) : 0, n1 = on ? max(1u, (ks[2] + 3584) >> 12) : 0;
    const int u2 = warp_incl(n0 + n1), u1 = u2 - n1, u0 = u1 - n0;
    const int total = __shfl_sync(0xffffffffu, u2, 31);
    slow |= total > CAPT;
    int gbase = b * CAPT + 1;
    if (on) {
#pragma unroll
        for (int i = 0; i < 4; i++)
            sts32(sm + O_NOFF + (ks[i] & 511), (i >> 1 ? u1 : u0) * 128 + (i & 1 ? (slow ? 1 << 30 : LH) : 0) - ((ks[i] & 511) >> 5));
    }
    __syncwarp();
    auto mark = [&](int i) { const int node = (ks[i] & 511) * (G / 4) - G + b; return node < NN ? node + 1 : 0; };
    if (!slow) {
        const uint64_t vp = (uint64_t)&gs->vals[w * SEGW * CH + lane];
        uint64_t vv[SEGW + 1], va[SEGW + 1];
#pragma unroll
        for (int j = 0; j <= SEGW; j++) {
            nk[j] = lds32(sm + O_NOFF + na_[j]) + (nk[j] >> 5);
            va[j] = madw(j < SEGW ? ho[j] & 0xfff : ho[j], 8, vp) + (j < SEGW ? j * CH * 8 : 0);
            vv[j] = (uint64_t)tag << 32;
        }
        if (t == 352) asm volatile("cp.async.bulk.wait_group.read 0;" ::: "memory");
        __syncthreads();
        TS(13);
        if (t == 352) pfx(PFA + PFB + PFC, PFD);
        for (int it = 0;; it++) {
#pragma unroll
            for (int j = 0; j <= SEGW; j++)
                asm volatile("{.reg .pred p; setp.lt.u32 p, %2, 320; @p ld.relaxed.gpu.global.b64 %0, [%1];}" : "+l"(vv[j]) : "l"(va[j]), "r"(na_[j]) : "memory");
            old = 0;
#pragma unroll
            for (int j = 0; j <= SEGW; j++) old |= (uint32_t)(vv[j] >> 32) ^ tag;
            if (!__any_sync(0xffffffffu, old >> 30)) break;
            spin_check(it);
        }
#pragma unroll
        for (int j = 0; j <= SEGW; j++)
            asm volatile("{.reg .pred p; setp.ne.u32 p, %4, %5; @p st.shared.v4.u32 [%0], {%1,%2,%3,%4};}"
                         ::"r"(sm + O_L + nk[j]), "r"(kv[j]), "r"(0), "r"((uint32_t)vv[j]), "r"((uint32_t)(vv[j] >> 32)), "r"(tag) : "memory");
        if (na_[SEGW] < 320) gs->more[w * SEGW * CH + lane + ho[SEGW]] = 0;
    } else {
        int so = 0;
#pragma unroll
        for (int j = 0; j < SEGW; j++) so += ho[j] & 0xfff;
        if (lane == 0) atoms_add(sm + O_SUM, so);
        if (t == 352) asm volatile("cp.async.bulk.wait_group.read 0;" ::: "memory");
        __syncthreads();
        gbase = TBIG + (lds32(sm + O_SUM) >> 3) + (NLOC + 5) * b;
        auto put = [&](uint32_t k, uint64_t e, uint32_t a, int rank) {
            const uint32_t v = lds32(sm + O_NOFF + a) + (a >> 5) + rank * 16;
            unsigned short* p = (unsigned short*)(gs->list + (gbase + (v >> 7 & 0x7fffff) + (v >> 30) * NTILE) * 8);
            const int c = v >> 4 & 7, c2 = 8 + (c >> 1) * 4 + (c & 1);
            p[c] = e >> 48; p[c2] = k; p[c2 + 2] = k >> 16;
            p[32 + c] = e; p[40 + c] = e >> 16; p[48 + c] = e >> 32; p[56 + c] = 0;
        };
        visit([&](uint32_t k, int o, int i) {
            uint64_t e;
            int it = 0;
            do {
                asm volatile("ld.relaxed.gpu.global.b64 %0, [%1];" : "=l"(e) : "l"(&gs->vals[o]) : "memory");
                spin_check(it++);
            } while (((uint32_t)(e >> 32) ^ tag) >> 30);
            if (i >= 31) gs->more[o] = 0;
            put(k, e, k & 511, atoms_add(sm + O_NCUR + (k & 511), 1));
        });
#pragma unroll 1
        for (int i = 0; i < 4; i++) {
            const uint32_t k = i == 0 ? ks[0] : i == 1 ? ks[1] : i == 2 ? ks[2] : ks[3];
#pragma unroll 1
            for (int p = (k >> 9) + w; p < (i >> 1 ? n1 : n0) * 8; p += NT / 32) put(0, 0, k & 511, p);
        }
        __syncthreads();
        if (w == 0 && on) {
#pragma unroll
            for (int i = 0; i < 4; i++) *(unsigned short*)(gs->list + (gbase + (i >> 1 ? u2 : u1) + (i & 1) * NTILE) * 8 - 1) = mark(i);
        }
        __threadfence();
    }
    int pos = gbase, end = gbase + __shfl_sync(0xffffffffu, NPRIV & 1 ? u1 : u2, (NPRIV - 1) / 2);
    __syncthreads();
    TS(5);

    if (w >= 8) {
        asm volatile("setmaxnreg.dec.sync.aligned.u32 " STR(PREG) ";");
        const int h = __reduce_max_sync(0xffffffffu, w & 3);
        const uint32_t ring = sm + O_RING;
        const int hp16 = r < 2 ? r * (NTILE * 8) : r < 4 ? r - 1 : NTILE * 8 + r - 3;
        uint32_t v0[3][4];
        if (!slow) {
            if (on) {
#pragma unroll
                for (int i = 0; i < 4; i++) sts32(sm + O_L - 124 + (i >> 1 ? u2 : u1) * 128 + (i & 1) * LH, mark(i));
            }
            __syncwarp();
#pragma unroll
            for (int k = 0; k < 3; k++) ldsm4t(v0[k], sm + O_L + (mat & 1) * LH + (h + 4 * k + (mat >> 1) * NSLOT) * 128 + r * 16);
        } else {
            if (r < 6 && h + 4 * mat < NSLOT) cpa16z(ring + (h + 4 * mat) * SLOT + S_H + r * 16, gs->list + (pos + h + 4 * mat) * 8 + hp16, 1);
            asm volatile("cp.async.wait_all;" ::: "memory");
        }
        const uint32_t xoff = opaque(mat * 4096 + ((r ^ (4 * (mat & 1))) * 16), lane);
        const uint32_t aoff = opaque(S_A + (lane >> 1) * 32 + (((lane ^ mat) & 1) * 16), lane);
        const uint32_t moff = opaque(mat < 2 ? (r < 4 ? S_C + mat * 80 + r * 16 : 0) : (mat == 2 && r < 6) ? S_H + r * 16 : 0, lane);
        const uint32_t hoff = opaque(S_H + mat * 8, lane), hoff2 = opaque(S_H + 32 + g * 8, lane);
        const uint32_t psel = opaque((lane & 2) ? 0x7632 : 0x5410, lane);
        const uint64_t xl = __shfl_sync(0xffffffffu, (uint64_t)(x - 1024 + r * 16) - (tag >> 6), lane);
        const uint64_t al = __shfl_sync(0xffffffffu, (uint64_t)(ea - 32 + (lane & 1) * 16) - (tag >> 4), lane);
        const uint64_t ml = __shfl_sync(0xffffffffu, (uint64_t)(gs->list + (mat < 2 ? mat * (NTILE * 8) + 4 + r : hp16)), lane);
        int cur = __reduce_max_sync(0xffffffffu, pos) + h;
        pos = cur + NSLOT; end = __reduce_max_sync(0xffffffffu, end);

        int ev = h ? end : end - 12, state = h ? 2 : 0, tk = 0, nr = 0, prv = pos - 1;
        uint32_t inf = 0;
        int ii = 0;
        auto take = [&]() {
            int v = 0;
            asm volatile("{.reg .pred p; setp.eq.s32 p, %2, 0; @p atom.relaxed.gpu.global.add.u32 %0, [%1], 1;}" : "+r"(v) : "l"(&gs->ticket), "r"(lane) : "memory");
            return v;
        };
        auto resolve = [&]() {
            const int k = __reduce_max_sync(0xffffffffu, tk);
            inf = tag;
            if (k < G * NPOOL) { const int l = k / G; ii = (k - l * G) * NPOOL + l; inf = ld_rlx(&gs->info[ii]); tk = take(); }
        };
        uint32_t so = ring + h * SLOT, ph = 1;
        auto fill = [&](auto first, const uint32_t* v) {
            constexpr bool F = decltype(first)::value;
            const uint32_t mi = max(moff >= S_H ? pos : cur, 0);
            const char* gm = (const char*)madw(mi, 128, ml);
            const uint32_t d0 = so + xoff;
            const uint32_t pa = so + (g == 7 ? S_H + q * 4 : g < 2 ? S_H + 32 + q * 8 + g * 4 : g == 2 ? S_C + 48 + q * 4 : S_C - 64 + lane * 4);
            const uint32_t ps = g == 7 ? 16 : g < 2 ? 32 : 80;
            mbar_wait(so + S_EMPTY, ph);
            if (F) {
                if (g != 3) { sts32(pa, v[0]); sts32(pa + ps, v[1]); }
                __syncwarp();
            } else if (cur <= 0) return false;
            const uint2 e = lds64(so + hoff), e2 = lds64(so + hoff2);
            const uint32_t s[4] = {e.x & 0xffffu, e.x >> 16, e.y & 0xffffu, e.y >> 16};
            const uint32_t id = __byte_perm(e2.x, e2.y, psel) >> 9;
            cpa16z(so + aoff, (const char*)madw(id, 32, al), id);
            if (F) {
                __syncwarp();
                if (ps != 80) { sts32(pa, v[2]); sts32(pa + ps, v[3]); }
            } else if (moff) cpa16z(so + moff, gm, mi);
#pragma unroll
            for (int j = 0; j < 4; j++) {
                const char* gx = (const char*)madw(s[j], 1024, xl);
#pragma unroll
                for (int k = 0; k < 8; k++) cpa16z((d0 ^ (j * 16)) + j * 1024 + k * 128, gx + k * 128, NULLP(s[j]));
            }
            asm volatile("cp.async.mbarrier.arrive.noinc.shared::cta.b64 [%0];" ::"r"(so + S_FULL) : "memory");
            if (so == ring) so += 4 * SLOT; else { so -= SLOT; ph ^= 1; }
            cur = prv;
            pos += 4; prv = pos - 1;
            return true;
        };
#pragma unroll 1
        for (int k = 0; k < 3; k++) {
            if (!slow) fill(Bool<true>(), v0[0]);
            if (k == 0) {
                asm volatile("bar.arrive 7, %0;" ::"n"(NT) : "memory");
                if (h == 3) {
                    bar_sync(5, 288);
                    if (lane == 0 && !slow) {
                        fence_async();
                        bulk_st(gs->list + gbase * 8, sm + O_L, total * 128);
                        bulk_st(gs->list + (gbase + NTILE) * 8, sm + O_L + LH, total * 128);
                    }
                    __syncwarp();
                }
            }
#pragma unroll
            for (int i = 0; i < 4; i++) { v0[0][i] = v0[1][i]; v0[1][i] = v0[2][i]; }
        }
        if (h == 3) {
            if (lane == 0) {
                asm volatile("cp.async.bulk.wait_group 0;\nfence.proxy.async;" ::: "memory");
                for (int j = 0; j < 4; j++) tma2d(sm + O_W1 + j * 24576, &m_w1, 64 * (j >> 1), 192 * (j & 1), sm + O_WBB);
            }
            __syncwarp();
            if (on && 2 * lane >= NPRIV) st_rlx(&gs->info[b * NPOOL + 2 * lane - NPRIV], tag | (gbase + u0) << 12 | n0);
            if (on && 2 * lane + 1 >= NPRIV) st_rlx(&gs->info[b * NPOOL + 2 * lane + 1 - NPRIV], tag | (gbase + u1) << 12 | n1);
        }
        bar_sync(6, 128);
        while (fill(Bool<false>(), nullptr)) {
            if (pos >= ev) {
                if (state == 0) { ev = end - 6; state = 1; tk = take(); }
                else if (state == 1) { resolve(); ev = end; state = 2; }
                else {
                    do {
                        const uint32_t mb = sm + O_MB + (nr & 31) * 8;
                        uint32_t rg;
                        nr++;
                        if (h == 0) {
                            for (int it = 0; (rg = __reduce_max_sync(0xffffffffu, inf ^ tag)) >> 30; it++) { spin_check(it); inf = ld_rlx(&gs->info[ii]); }
                            asm volatile("st.release.cta.shared.b64 [%0], %1;" ::"r"(mb), "l"(rg | (uint64_t)nr << 32) : "memory");
                            if (rg) resolve();
                        } else {
                            uint64_t m;
                            for (int it = 0;; it++) {
                                asm volatile("ld.acquire.cta.shared.b64 %0, [%1];" : "=l"(m) : "r"(mb) : "memory");
                                if (__all_sync(0xffffffffu, (int)(m >> 32) == nr)) break;
                                spin_check(it);
                            }
                            rg = __reduce_max_sync(0xffffffffu, (uint32_t)m);
                        }
                        const int ov = pos - end;
                        pos = rg ? (int)(rg >> 12) + ov : -(1 << 30);
                        if (ov) prv = pos - 1;
                        end = (rg >> 12) + (rg & 0xfff);
                    } while (pos >= end);
                    ev = end;
                }
            }
        }
        TSW(8 + (h & 1));
        if (lane == 0) sts32(so + S_C + 48, META_END);
        mbar_arrive(so + S_FULL);
        if (t == 256) {
            gs->epoch[b * 32] = (tag >> 30) % 3;
            if (atomicInc(&gs->done, G - 1) == G - 1) gs->ticket = 0;
        }
        asm volatile("cp.async.wait_all;" ::: "memory");
    } else {
        asm volatile("setmaxnreg.inc.sync.aligned.u32 " STR(CREG) ";");
        const uint32_t xa = opaque(((mat >> 1) * 8 + r) * 1024 + (w >> 2) * 128 + (((2 * (w & 3) + (mat & 1)) ^ r) * 16), lane);
        const uint32_t aa = opaque(S_A + ((mat >> 1) * 8 + r) * 32 + (((mat & 1) ^ (r >> 2)) * 16), lane);
        const uint32_t ya = opaque(S_C + (mat & 1) * 80 + (mat >> 1) * 16, lane);
        const uint32_t yc = opaque(S_C + (mat < 2 ? mat * 80 + 32 : (r >> 2) == (mat & 1) ? (mat & 1) * 80 + (r & 3) * 16 : 64), lane);
        const uint32_t mm = opaque((lane & 15) == 12 ? 0xffffu : 0u, lane);
        const uint32_t na = opaque(mm ? sm + O_NODE + (lane >> 4) * 4 : sm + O_TRASH, lane);
        const uint32_t pw = sm + O_P + w * PW;
        const uint32_t fx = opaque((q < 3 ? pw + P_1P0 + 2 * q * PSBO + (mat & 1) * 128 : sm + O_TRASH + ((pw - sm - O_TRASH + 96) & 127)) + (r >> 2) * 16, lane);
        const uint32_t fyz = opaque(pw + (q < 3 ? (mat < 2 ? P_1P1 : P_1P2) + 2 * q * PSBO : mat < 2 ? P_0P0 : P_0P1) + (mat & 1) * 128 + (r >> 2) * 16, lane);
        uint32_t oh[4][2];
#pragma unroll
        for (int c = 0; c < 8; c++) oh[c & 3][c >> 2] = opaque(g == c ? 0x3F803F80u : 0u, lane);
        uint32_t eb[3];
#pragma unroll
        for (int k = 0; k < 3; k++) {
            const int i = (g & 3) * 9 + (q & 1) * 6 + k;
            const uint32_t lo = __shfl_sync(0xffffffffu, epl, i), hi = __shfl_sync(0xffffffffu, epl, i + 3);
            eb[k] = (g & 3) < 3 && (q >> 1) == (g >> 2) ? (q & 1 ? lo : lo | hi << 16) : 0u;
        }
        const bool l0 = opaque(lane == 0, lane);
        uint32_t w0[16][4];
        bar_sync(7, NT);
        if (!slow) {
            uint32_t la = sm + O_L + (w & 1) * LH + (w >> 1) * 512;
            const uint32_t lo = (g < 2 ? 4 + q * 2 + g : g == 2 ? 28 + q : g == 7 ? q : lane) * 4;
#pragma unroll 1
            for (int c = total - 4 * (w >> 1); c > 0; c -= 48, la += 6144) {
                uint32_t v[3][4];
#pragma unroll
                for (int k = 0; k < 3; k++) ldsm4t(v[k], la + k * 2048 + lane * 16);
#pragma unroll
                for (int k = 0; k < 12; k++) sts32(la + lo + (k >> 2) * 2048 + (k & 3) * 128, v[k >> 2][k & 3]);
            }
        }
        mbar_wait(sm + O_WBD, 0);
#pragma unroll
        for (int k = 0; k < 16; k++) ldsm4t(w0[k], sm + O_W0S + (w >> 2) * 32768 + k * 2048 + sw);
        bar_sync(5, 288);
        TS(6);
        Acc A;
#pragma unroll
        for (int i = 0; i < 4; i++) { A.p00[i] = A.p110[i] = A.p10[0][i] = A.p10[1][i] = A.p10[2][i] = 0; A.t01[i] = A.m[0][i] = A.m[1][i] = A.m[2][i] = 0.f; }
        int slot = STAG;
        bool w1ok = false;
        uint32_t so = sm + O_RING, ph = 0, a[4], ok, mt = 0;
        auto tile = [&](auto first) {
            constexpr bool F = decltype(first)::value;
            uint32_t yb[8], f[4][4], R[5][4];
            ldsm4t(f[0], so + xa);
            ldsm4(yb + 4, so + yc);
#pragma unroll
            for (int m = 1; m < 4; m++) ldsm4t(f[m], so + xa + m * 256);
            ldsm4(yb, so + ya);
            if (l0) mbar_arrive(so + S_EMPTY);
            so += SLOT;
            if (so == sm + O_RING + NSLOT * SLOT) { so = sm + O_RING; ph ^= 1; }
            if (F) {
                const uint32_t sof = (slot & 7) * 16 + (slot >> 3) * PSBO;
                sts32(na + 4 * slot, mt);
                flush(A, fx + sof, fyz + sof, oh, eb);
                slot += 2;
            }
#pragma unroll
            for (int p = 0; p < 5; p++) {
                float c[4];
                mma16z(c, wr[p], a[0], a[1]); R[p][0] = pack(c[0], c[1]); R[p][1] = pack(c[2], c[3]);
                mma16z(c, wr[p], a[2], a[3]); R[p][2] = pack(c[0], c[1]); R[p][3] = pack(c[2], c[3]);
            }
            asm volatile("{\n.reg .pred p;\nmbarrier.test_wait.parity.shared::cta.b64 p, [%5], %6;\nselp.u32 %4, 1, 0, p;\n"
                         "@p ldmatrix.sync.aligned.m8n8.x4.shared.b16 {%0,%1,%2,%3}, [%7];\n}"
                         : "+r"(a[0]), "+r"(a[1]), "+r"(a[2]), "+r"(a[3]), "=r"(ok) : "r"(so + S_FULL), "r"(ph), "r"(so + aa) : "memory");
            asm("lop3.b32 %0, %1, %2, %3, 0xa8;" : "=r"(mt) : "r"(yb[6]), "r"(yb[7]), "r"(mm));
            uint32_t u[4];
#pragma unroll
            for (int i = 0; i < 4; i++) {
                A.p00[i] = F ? hmul(f[0][i], R[0][i]) : hfma(f[0][i], R[0][i], A.p00[i]);
                u[i] = hmul(f[0][i], R[2][i]);
            }
            if (F) mma16z(A.t01, u, yb[6], yb[7]); else mma16(A.t01, u, yb[6], yb[7]);
#pragma unroll
            for (int k = 0; k < 3; k++) {
#pragma unroll
                for (int i = 0; i < 4; i++) {
                    A.p10[k][i] = F ? hmul(f[1 + k][i], R[3][i]) : hfma(f[1 + k][i], R[3][i], A.p10[k][i]);
                    u[i] = hmul(f[1 + k][i], R[4][i]);
                }
                if (F) mma16z(A.m[k], u, yb[6], yb[7]); else mma16(A.m[k], u, yb[6], yb[7]);
            }
#pragma unroll
            for (int i = 0; i < 4; i++) {
                uint32_t sdot = hfma(f[3][i], yb[4 + (i >> 1)], hfma(f[2][i], yb[2 + (i >> 1)], hmul(f[1][i], yb[i >> 1])));
                A.p110[i] = F ? hmul(sdot, R[1][i]) : hfma(sdot, R[1][i], A.p110[i]);
            }
            return __any_sync(0xffffffffu, mt != 0);
        };
        mbar_wait(so + S_FULL, 0);
        ldsm4(a, so + aa);
        TS(7);
        bool last = false;
        while (true) {
            while (!last) {
                last = tile(Bool<false>());
                if (!ok) { mbar_wait(so + S_FULL, ph); ldsm4(a, so + aa); }
            }
            last = tile(Bool<true>());
            if (slot == 16 || last) {
                const bool fin = __any_sync(0xffffffffu, mt == META_END);
                if (slot == 16 || fin) {
                    if (!w1ok) { mbar_wait(sm + O_WBB, 0); w1ok = true; }
                    asm volatile("fence.proxy.async.shared::cta;" ::: "memory");
                    bar_sync(1, 256);
                    float d0[8], d1[24];
                    const uint64_t db = (uint64_t)(((sm + O_P) >> 4) & 0x3fff) | (8ull << 16) | ((uint64_t)(PSBO / 16) << 32);
                    const uint64_t da = (uint64_t)(((sm + O_W1 + (w >> 2) * 49152) >> 4) & 0x3fff) | (1ull << 16) | (64ull << 32) | (1ull << 62);
                    asm volatile("wgmma.fence.sync.aligned;" ::: "memory");
#pragma unroll
                    for (int k = 0; k < 16; k++) wg_rs16(d0, w0[k], db + (((k & 7) * PW + ((k >> 3) ? P_0P1 : P_0P0)) >> 4), k);
                    asm volatile("wgmma.commit_group.sync.aligned;" ::: "memory");
#pragma unroll
                    for (int k = 0; k < 24; k++)
                        wg_ss48(d1, da + k * 128, db + (((k & 7) * PW + ((k >> 3) == 0 ? P_1P0 : (k >> 3) == 1 ? P_1P1 : P_1P2)) >> 4), k);
                    asm volatile("wgmma.commit_group.sync.aligned;" ::: "memory");
                    int nd[4];
#pragma unroll
                    for (int it = 0; it < 4; it++) nd[it] = lds32(sm + O_NODE + 4 * (it * 4 + mat));
                    asm volatile("wgmma.wait_group.sync.aligned 1;" ::: "memory");
#pragma unroll
                    for (int i = 0; i < 8; i++) asm volatile("" : "+f"(d0[i])::"memory");
                    uint32_t o[4][4];
                    float gt[8];
#pragma unroll
                    for (int i = 0; i < 8; i++) gt[i] = __fdividef(1.f, 1.f + __expf(-d0[i]));
#pragma unroll
                    for (int i = 0; i < 4; i++) o[0][i] = pack(d0[2 * i], d0[2 * i + 1]);
#pragma unroll
                    for (int i = 0; i < 8; i++) asm volatile("" : "+f"(gt[i])::"memory");
                    asm volatile("wgmma.wait_group.sync.aligned 0;" ::: "memory");
#pragma unroll
                    for (int i = 0; i < 24; i++) asm volatile("" : "+f"(d1[i])::"memory");
                    bar_sync(1, 256);
#pragma unroll
                    for (int i = 0; i < 4; i++)
#pragma unroll
                        for (int j = 0; j < 3; j++) o[1 + j][i] = pack(d1[8 * j + 2 * i] * gt[2 * i], d1[8 * j + 2 * i + 1] * gt[2 * i + 1]);
                    const uint32_t sg = sm + O_P + (w & 4) * PW + ((mat >> 1) * 8 + r) * 128 + (((2 * (w & 3) + (mat & 1)) ^ r) * 16);
#pragma unroll
                    for (int j = 0; j < 4; j++) stsm4t(sg + j * PW, o[j][0], o[j][1], o[j][2], o[j][3]);
                    bar_sync(2 + (w >> 2), 128);
                    uint4 v[4];
#pragma unroll
                    for (int it = 0; it < 4; it++) v[it] = lds128(pw + (it * 4 + mat) * 128 + ((r ^ ((it * 4 + mat) & 7)) * 16));
                    char* op = out - 1024 + (w & 3) * 256 + (w >> 2) * 128 + r * 16;
#pragma unroll
                    for (int it = 0; it < 4; it++) if (it * 4 + mat < slot && nd[it]) *(uint4*)(op + (size_t)nd[it] * 1024) = v[it];
                    __syncwarp();
                    slot = 0;
                }
                if (fin) break;
            }
            if (!ok) { mbar_wait(so + S_FULL, ph); ldsm4(a, so + aa); }
        }
        TS(10);
    }
}

typedef CUresult (*EncFn)(CUtensorMap*, CUtensorMapDataType, cuuint32_t, void*, const cuuint64_t*, const cuuint64_t*,
                          const cuuint32_t*, const cuuint32_t*, CUtensorMapInterleave, CUtensorMapSwizzle,
                          CUtensorMapL2promotion, CUtensorMapFloatOOBfill);

void make_map(EncFn fn, CUtensorMap* m, void* p, int rows, int cols, int brows, int rank, int bblk, CUtensorMapSwizzle swz) {
    cuuint64_t dims[3] = {(cuuint64_t)(rank == 3 ? 64 : cols), (cuuint64_t)rows, (cuuint64_t)cols / 64}, strides[2] = {(cuuint64_t)cols * 2, 128};
    cuuint32_t box[3] = {64, (cuuint32_t)brows, (cuuint32_t)bblk}, es[3] = {1, 1, 1};
    fn(m, CU_TENSOR_MAP_DATA_TYPE_BFLOAT16, rank, p, dims, strides, box, es, CU_TENSOR_MAP_INTERLEAVE_NONE,
       swz, CU_TENSOR_MAP_L2_PROMOTION_NONE, CU_TENSOR_MAP_FLOAT_OOB_FILL_NONE);
}

}

extern "C" void kernel_launch(void* const* d_in, const int* in_sizes, int n_in, void* d_out, int out_size) {
    static EncFn enc = nullptr;
    static void* scratch = nullptr;
    if (!enc) {
        void* fn = nullptr;
        cudaDriverEntryPointQueryResult qr;
        cudaGetDriverEntryPoint("cuTensorMapEncodeTiled", &fn, cudaEnableDefault, &qr);
        enc = (EncFn)fn;
        cudaGetSymbolAddress(&scratch, g_scratch);
        cudaFuncSetAttribute(tp_kernel, cudaFuncAttributeMaxDynamicSharedMemorySize, SMEM_BYTES);
    }
    CUtensorMap m_wr, m_w0, m_w1;
    make_map(enc, &m_wr, d_in[5], 16, 640, 16, 3, 5, CU_TENSOR_MAP_SWIZZLE_128B);
    make_map(enc, &m_w0, d_in[6], 256, 128, 256, 3, 2, CU_TENSOR_MAP_SWIZZLE_128B);
    make_map(enc, &m_w1, d_in[7], 384, 128, 192, 2, 1, CU_TENSOR_MAP_SWIZZLE_128B);
    tp_kernel<<<G, NT, SMEM_BYTES>>>((const int4*)d_in[4], (const int4*)d_in[3], (const char*)d_in[1], (Scratch*)scratch,
                                     (const char*)d_in[0], (const char*)d_in[2], (const __nv_bfloat16*)d_in[8], (char*)d_out,
                                     m_wr, m_w0, m_w1);
}
```

```cpp
#include <cuda_runtime.h>
#include <cuda_bf16.h>
#include <cuda.h>
#include <stdint.h>
#include <stddef.h>

namespace {

constexpr int NN = 10000;
constexpr int NE = 320000;
constexpr int G = 132;
constexpr int NT = 384;
constexpr int CH = 2432;
constexpr int NLOC = (NN + G - 1) / G;
#define NPOOL 5
constexpr int NPAIR = NLOC / 2, NPRIV = NPAIR - NPOOL;
constexpr int SEGW = 11;

#define NSLOT 5
#define PFA 16
#define PFB 20
#define PFC 20
#define PFD 20
#define STAG (b & 7)
#define NULLP(v) v
#define CREG 216
#define PREG 72
#define STR2(x) #x
#define STR(x) STR2(x)

constexpr int S_A = 16384, S_C = S_A + 512, S_FULL = S_C + 144, S_EMPTY = S_FULL + 8, S_H = S_C + 160, SLOT = 17152;

constexpr int PSBO = 272;
constexpr int PB1 = 5 * PSBO + 256, PB0 = PSBO + 256;
constexpr int P_1P0 = 0, P_1P1 = PB1, P_0P1 = 2 * PB1, P_0P0 = P_0P1 + PB0, P_1P2 = P_0P0 + PB0;
constexpr int PW = P_1P2 + PB1;

constexpr int O_W1 = 0;
constexpr int O_P = 98304;
constexpr int O_RING = O_P + 8 * PW;
constexpr int O_TRASH = O_RING + 5 * SLOT;
constexpr int O_WBA = O_TRASH + 512, O_WBB = O_WBA + 8, O_WBC = O_WBA + 16, O_WBD = O_WBA + 24, O_NODE = O_WBA + 48;
constexpr int O_SUM = O_NODE + 128, O_MB = O_SUM + 16;
constexpr int SMEM_BYTES = O_MB + 256;
constexpr int CAPT = 240, LH = CAPT * 128;
constexpr int O_L = 0, LZ = 2 * LH / (NT * 16), O_W0S = O_L + 2 * LH, O_OUT = O_W0S + 65536, O_RH = O_OUT + CH * 8;
constexpr int O_KT = O_RING + SLOT, O_SRC = O_RING + 2 * SLOT;
constexpr int O_BCNT = O_SRC + CH * 4, O_NCUR = O_BCNT + 640, O_NCNT = O_NCUR + 320;
constexpr int O_BOFF = O_NCNT + 512, O_SORT = O_BOFF + 640, O_NOFF = O_SORT + 320;
constexpr int O_WR0 = (O_RING + 3 * SLOT + 1023) / 1024 * 1024, O_WR1 = (O_RING + 4 * SLOT + 1023) / 1024 * 1024;
constexpr int TBIG = G * CAPT + 8, NTILE = TBIG + NE / 8 + G * (NLOC + 5);
static_assert(SMEM_BYTES <= 232448 && NSLOT == 5 && CAPT % 16 == 0 && NTILE < (1 << 18), "smem");
static_assert(LZ * NT * 16 == 2 * LH && O_W0S % 1024 == 0 && O_RH + CH * 6 <= O_RING + S_C && G * 128 <= S_C && O_NOFF + 512 <= O_SRC + S_C, "staging");
static_assert(O_RING % 128 == 0 && SLOT % 128 == 0 && 2 * LH <= O_P, "layout");
static_assert(G * CH >= NE && NE % 8 == 0 && CH < 4096 && CH / 8 <= 320 && NE < (1 << 21), "chunks");
static_assert(SEGW * (NT / 32) == G && G <= 160 && G % 4 == 0, "segments");
static_assert(NLOC % 4 == 0 && NLOC < 80 && NLOC * 4 <= 320 && NN < 0xffff && NE / 8 < 0xffff && NPRIV >= 30, "scan width");

struct __align__(128) Scratch {
    uint32_t keys[G * G * 32];
    uint64_t vals[G * CH];
    uint32_t more[G * CH];
    uint32_t epoch[G * 32];
    uint32_t info[G * NPOOL];
    unsigned done, pad0[31], ticket, pad1[31 + 32 - G * NPOOL % 32];
    uint4 list[2 * NTILE * 8];
};
static_assert(offsetof(Scratch, list) % 128 == 0, "list");
__device__ Scratch g_scratch;
#define TS(i)
#define TSW(i)
#define TV(i, v)

constexpr int SPIN_LIMIT = 1 << 24;

__device__ __forceinline__ void mbar_init(uint32_t a, int c) { asm volatile("mbarrier.init.shared::cta.b64 [%0], %1;" ::"r"(a), "r"(c) : "memory"); }
__device__ __forceinline__ void mbar_expect(uint32_t a, int b) { asm volatile("mbarrier.arrive.expect_tx.shared::cta.b64 _, [%0], %1;" ::"r"(a), "r"(b) : "memory"); }
__device__ __forceinline__ void mbar_arrive(uint32_t a) { asm volatile("mbarrier.arrive.shared::cta.b64 _, [%0];" ::"r"(a) : "memory"); }
__device__ __forceinline__ void mbar_wait(uint32_t a, uint32_t ph) {
    asm volatile("{\n.reg .pred p, q;\n.reg .u32 it;\n"
                 "mbarrier.try_wait.parity.shared::cta.b64 p, [%0], %1;\n"
                 "@p bra DONE;\n"
                 "mov.u32 it, 0;\n"
                 "LOOP:\n"
                 "mbarrier.try_wait.parity.shared::cta.b64 p, [%0], %1;\n"
                 "@p bra DONE;\n"
                 "add.u32 it, it, 1;\n"
                 "setp.gt.u32 q, it, %2;\n"
                 "@q trap;\n"
                 "bra LOOP;\n"
                 "DONE:\n}" ::"r"(a), "r"(ph), "n"(SPIN_LIMIT) : "memory");
}
__device__ __forceinline__ void spin_check(int it) {
    asm volatile("{\n.reg .pred q;\nsetp.gt.s32 q, %0, %1;\n@q trap;\n}" ::"r"(it), "n"(SPIN_LIMIT));
}
__device__ __forceinline__ void tma2d(uint32_t dst, const CUtensorMap* m, int c0, int c1, uint32_t bar) {
    asm volatile("cp.async.bulk.tensor.2d.shared::cluster.global.mbarrier::complete_tx::bytes [%0], [%1, {%3, %4}], [%2];"
                 ::"r"(dst), "l"(m), "r"(bar), "r"(c0), "r"(c1) : "memory");
}
__device__ __forceinline__ void cpa16z(uint32_t d, const void* g, uint32_t v) {
    asm volatile("{\n.reg .pred p;\nsetp.eq.u32 p, %2, 0;\ncp.async.cg.shared.global [%0], [%1], 16, p;\n}" ::"r"(d), "l"(g), "r"(v) : "memory");
}
__device__ __forceinline__ void ldsm4(uint32_t* r, uint32_t a) { asm volatile("ldmatrix.sync.aligned.m8n8.x4.shared.b16 {%0,%1,%2,%3}, [%4];" : "=r"(r[0]), "=r"(r[1]), "=r"(r[2]), "=r"(r[3]) : "r"(a) : "memory"); }
__device__ __forceinline__ void ldsm4t(uint32_t* r, uint32_t a) { asm volatile("ldmatrix.sync.aligned.m8n8.x4.trans.shared.b16 {%0,%1,%2,%3}, [%4];" : "=r"(r[0]), "=r"(r[1]), "=r"(r[2]), "=r"(r[3]) : "r"(a) : "memory"); }
__device__ __forceinline__ void stsm4t(uint32_t a, uint32_t r0, uint32_t r1, uint32_t r2, uint32_t r3) { asm volatile("stmatrix.sync.aligned.m8n8.x4.trans.shared.b16 [%0], {%1,%2,%3,%4};" ::"r"(a), "r"(r0), "r"(r1), "r"(r2), "r"(r3) : "memory"); }
__device__ __forceinline__ void stsm2t(uint32_t a, uint32_t r0, uint32_t r1) { asm volatile("stmatrix.sync.aligned.m8n8.x2.trans.shared.b16 [%0], {%1,%2};" ::"r"(a), "r"(r0), "r"(r1) : "memory"); }
__device__ __forceinline__ void mma16(float* d, const uint32_t* a, uint32_t b0, uint32_t b1) {
    asm("mma.sync.aligned.m16n8k16.row.col.f32.bf16.bf16.f32 {%0,%1,%2,%3}, {%4,%5,%6,%7}, {%8,%9}, {%0,%1,%2,%3};"
        : "+f"(d[0]), "+f"(d[1]), "+f"(d[2]), "+f"(d[3]) : "r"(a[0]), "r"(a[1]), "r"(a[2]), "r"(a[3]), "r"(b0), "r"(b1));
}
__device__ __forceinline__ void mma8(float* d, uint32_t a0, uint32_t a1, uint32_t b0) {
    asm("mma.sync.aligned.m16n8k8.row.col.f32.bf16.bf16.f32 {%0,%1,%2,%3}, {%4,%5}, {%6}, {%0,%1,%2,%3};"
        : "+f"(d[0]), "+f"(d[1]), "+f"(d[2]), "+f"(d[3]) : "r"(a0), "r"(a1), "r"(b0));
}
__device__ __forceinline__ void mma16z(float* d, const uint32_t* a, uint32_t b0, uint32_t b1) {
    asm("mma.sync.aligned.m16n8k16.row.col.f32.bf16.bf16.f32 {%0,%1,%2,%3}, {%4,%5,%6,%7}, {%8,%9}, {%10,%10,%10,%10};"
        : "=f"(d[0]), "=f"(d[1]), "=f"(d[2]), "=f"(d[3]) : "r"(a[0]), "r"(a[1]), "r"(a[2]), "r"(a[3]), "r"(b0), "r"(b1), "f"(0.f));
}
__device__ __forceinline__ uint32_t pack(float lo, float hi) { uint32_t r; asm("cvt.rn.bf16x2.f32 %0, %1, %2;" : "=r"(r) : "f"(hi), "f"(lo)); return r; }
__device__ __forceinline__ uint32_t hmul(uint32_t a, uint32_t b) { uint32_t r; asm("mul.rn.bf16x2 %0, %1, %2;" : "=r"(r) : "r"(a), "r"(b)); return r; }
__device__ __forceinline__ uint32_t hfma(uint32_t a, uint32_t b, uint32_t c) { uint32_t r; asm("fma.rn.bf16x2 %0, %1, %2, %3;" : "=r"(r) : "r"(a), "r"(b), "r"(c)); return r; }
__device__ __forceinline__ uint4 lds128(uint32_t a) { uint4 v; asm volatile("ld.shared.v4.u32 {%0,%1,%2,%3}, [%4];" : "=r"(v.x), "=r"(v.y), "=r"(v.z), "=r"(v.w) : "r"(a) : "memory"); return v; }
__device__ __forceinline__ void sts128(uint32_t a, uint4 v) { asm volatile("st.shared.v4.u32 [%0], {%1,%2,%3,%4};" ::"r"(a), "r"(v.x), "r"(v.y), "r"(v.z), "r"(v.w) : "memory"); }
__device__ __forceinline__ int lds32(uint32_t a) { int v; asm volatile("ld.shared.u32 %0, [%1];" : "=r"(v) : "r"(a) : "memory"); return v; }
__device__ __forceinline__ void sts32(uint32_t a, int v) { asm volatile("st.shared.u32 [%0], %1;" ::"r"(a), "r"(v) : "memory"); }
__device__ __forceinline__ int atoms_add(uint32_t a, int v) { int r; asm volatile("atom.shared.add.u32 %0, [%1], %2;" : "=r"(r) : "r"(a), "r"(v) : "memory"); return r; }
__device__ __forceinline__ uint32_t ld_rlx(const void* p) { uint32_t v; asm volatile("ld.relaxed.gpu.global.u32 %0, [%1];" : "=r"(v) : "l"(p) : "memory"); return v; }
__device__ __forceinline__ void st_rlx(void* p, uint32_t v) { asm volatile("st.relaxed.gpu.global.u32 [%0], %1;" ::"l"(p), "r"(v) : "memory"); }
__device__ __forceinline__ void bulk(uint32_t dst, const void* g, int n, uint32_t bar) {
    asm volatile("cp.async.bulk.shared::cluster.global.mbarrier::complete_tx::bytes [%0], [%1], %2, [%3];" ::"r"(dst), "l"(g), "r"(n), "r"(bar) : "memory");
}
__device__ __forceinline__ void bulk_st(void* g, uint32_t src, int n) {
    asm volatile("cp.async.bulk.global.shared::cta.bulk_group [%0], [%1], %2;\ncp.async.bulk.commit_group;" ::"l"(g), "r"(src), "r"(n) : "memory");
}
__device__ __forceinline__ uint2 lds64(uint32_t a) { uint2 v; asm volatile("ld.shared.v2.u32 {%0,%1}, [%2];" : "=r"(v.x), "=r"(v.y) : "r"(a) : "memory"); return v; }
__device__ __forceinline__ void sts64(uint32_t a, uint32_t x, uint32_t y) { asm volatile("st.shared.v2.u32 [%0], {%1,%2};" ::"r"(a), "r"(x), "r"(y) : "memory"); }
__device__ __forceinline__ void tma3d(uint32_t dst, const CUtensorMap* m, int c2, uint32_t bar) {
    asm volatile("cp.async.bulk.tensor.3d.shared::cluster.global.mbarrier::complete_tx::bytes [%0], [%1, {%3, %3, %4}], [%2];"
                 ::"r"(dst), "l"(m), "r"(bar), "r"(0), "r"(c2) : "memory");
}
__device__ __forceinline__ void pf_l2(const void* g, int n) {
    asm volatile("{.reg .pred p; setp.gt.s32 p, %1, 0; @p cp.async.bulk.prefetch.L2.global [%0], %1;}" ::"l"(g), "r"(n) : "memory");
}
__device__ __forceinline__ void fence_async() { asm volatile("fence.proxy.async.shared::cta;" ::: "memory"); }
__device__ __forceinline__ uint64_t madw(uint32_t a, uint32_t b, uint64_t c) { uint64_t r; asm("mad.wide.u32 %0, %1, %2, %3;" : "=l"(r) : "r"(a), "r"(b), "l"(c)); return r; }
__device__ __forceinline__ uint32_t opaque(uint32_t v, int lane) { return __shfl_sync(0xffffffffu, v, lane); }
__device__ __forceinline__ void bar_sync(int id, int n) { asm volatile("bar.sync %0, %1;" ::"r"(id), "r"(n) : "memory"); }

__device__ __forceinline__ void wg_rs16(float* d, const uint32_t* a, uint64_t db, int sc) {
    asm volatile("{.reg .pred p; setp.ne.b32 p, %13, 0;\n"
                 "wgmma.mma_async.sync.aligned.m64n16k16.f32.bf16.bf16 {%0,%1,%2,%3,%4,%5,%6,%7}, {%8,%9,%10,%11}, %12, p, 1, 1, 0;}"
                 : "+f"(d[0]), "+f"(d[1]), "+f"(d[2]), "+f"(d[3]), "+f"(d[4]), "+f"(d[5]), "+f"(d[6]), "+f"(d[7])
                 : "r"(a[0]), "r"(a[1]), "r"(a[2]), "r"(a[3]), "l"(db), "r"(sc));
}
__device__ __forceinline__ void wg_ss48(float* d, uint64_t da, uint64_t db, int sc) {
    asm volatile("{.reg .pred p; setp.ne.b32 p, %26, 0;\n"
                 "wgmma.mma_async.sync.aligned.m64n48k16.f32.bf16.bf16 {%0,%1,%2,%3,%4,%5,%6,%7,%8,%9,%10,%11,%12,%13,%14,%15,%16,%17,%18,%19,%20,%21,%22,%23}, %24, %25, p, 1, 1, 1, 0;}"
                 : "+f"(d[0]), "+f"(d[1]), "+f"(d[2]), "+f"(d[3]), "+f"(d[4]), "+f"(d[5]), "+f"(d[6]), "+f"(d[7]),
                   "+f"(d[8]), "+f"(d[9]), "+f"(d[10]), "+f"(d[11]), "+f"(d[12]), "+f"(d[13]), "+f"(d[14]), "+f"(d[15]),
                   "+f"(d[16]), "+f"(d[17]), "+f"(d[18]), "+f"(d[19]), "+f"(d[20]), "+f"(d[21]), "+f"(d[22]), "+f"(d[23])
                 : "l"(da), "l"(db), "r"(sc));
}

__device__ __forceinline__ int warp_incl(int v) {
#pragma unroll
    for (int o = 1; o < 32; o <<= 1)
        asm volatile("{.reg .pred p; .reg .b32 u; shfl.sync.up.b32 u|p, %0, %1, 0, 0xffffffff; @p add.s32 %0, %0, u;}" : "+r"(v) : "r"(o));
    return v;
}
__device__ __forceinline__ void ldg128(uint32_t* r, const void* p, bool on) {
    asm volatile("{.reg .pred p; setp.ne.u32 p, %5, 0; @p ld.global.nc.v4.u32 {%0,%1,%2,%3}, [%4];}"
                 : "=r"(r[0]), "=r"(r[1]), "=r"(r[2]), "=r"(r[3]) : "l"(p), "r"((uint32_t)on));
}

template <bool B> struct Bool { static constexpr bool value = B; };
struct Acc {
    uint32_t p00[4], p110[4], p10[3][4];
    float t01[4], m[3][4];
};

#define LF(m) ldsm4t(f[m], so + xa + m * 256)
#define LY() ldsm4(yb, so + ya)
#define LC() ldsm4(yb + 4, so + yc)
#define ADV() { asm volatile("@lane0 mbarrier.arrive.shared::cta.b64 _, [%0];" ::"r"(so + S_EMPTY) : "memory"); \
                const bool wrap = so == sm + O_RING + (NSLOT - 1) * SLOT; so = wrap ? sm + O_RING : so + SLOT; ph ^= wrap ? 0x80000000u : 0u; }
#define LA() asm volatile("{\n.reg .pred p;\n.reg .b64 s;\nmov.b64 s, {0, %6};\nmbarrier.test_wait.shared::cta.b64 p, [%5], s;\nselp.u32 %4, 1, 0, p;\n" \
                          "@p ldmatrix.sync.aligned.m8n8.x4.shared.b16 {%0,%1,%2,%3}, [%7];\n}" \
                          : "+r"(a[0]), "+r"(a[1]), "+r"(a[2]), "+r"(a[3]), "=r"(ok) : "r"(so + S_FULL), "r"(ph), "r"(so + aa) : "memory")
#define RAD(p, s) { float c[4]; mma16z(c, wr[p], a[2 * s], a[2 * s + 1]); R[p][2 * s] = pack(c[0], c[1]); R[p][2 * s + 1] = pack(c[2], c[3]); }
#define MUL(x, y) (XS ? hmul(y, x) : hmul(x, y))
#define FMA(x, y, z) (XS ? hfma(y, x, z) : hfma(x, y, z))
#define ACC(x, y, z) z = F ? MUL(x, y) : FMA(x, y, z)
#define P00(i) ACC(f[0][i], R[0][i], A.p00[i ^ XA])
#define P10(k, i) ACC(f[1 + k][i], R[3][i], A.p10[k][i ^ XA])
#define SD(k, i) sd[i] = k ? FMA(f[1 + k][i], yb[2 * k + (i >> 1)], sd[i]) : MUL(f[1][i], yb[i >> 1])
#define P110(i) ACC(sd[i], R[1][i], A.p110[i ^ XA])
#define TU(i) u[3][i ^ XU] = MUL(f[0][i], R[2][i])
#define TM() if (F) mma16z(A.t01, u[3], yb[6], yb[7]); else mma16(A.t01, u[3], yb[6], yb[7])
#define MU(k, i) u[k][i ^ XU] = MUL(f[1 + k][i], R[4][i])
#define MM(k) if (F) mma16z(A.m[k], u[k], yb[6], yb[7]); else mma16(A.m[k], u[k], yb[6], yb[7])
#define PK(v, h) pack(v[2 * (h)], v[2 * (h) + 1])
#define LN() { sts32(na + sof, mt); mt = lds32(so + ma); rem = (int)(__reduce_max_sync(0xffffffffu, mt) >> 16) - 1; }
#define FY(k) if (k == 0) mma16z(y, A.p10[0], oh[0][0], oh[0][1]); else mma16(y, k < 3 ? A.p10[k % 3] : A.p00, oh[k][0], oh[k][1])
#define FZ(k) if (k == 0) mma16z(z, A.p110, oh[3][0], oh[3][1]); \
              else if (k == 1) { const uint32_t mp[4] = {PK(A.m[0], XA ^ XU), PK(A.m[0], 1 ^ XA ^ XU), PK(A.m[1], XA ^ XU), PK(A.m[1], 1 ^ XA ^ XU)}; mma16(z, mp, eb[0], eb[1]); } \
              else mma8(z, PK(A.m[2], XA ^ XU), PK(A.m[2], 1 ^ XA ^ XU), eb[2])
#define SX() stsm2t(fx + sof, PK(A.t01, XU), PK(A.t01, 1 ^ XU))
#define SY() stsm4t(fyz + sof, PK(y, XA), PK(y, 1 ^ XA), PK(z, XA), PK(z, 1 ^ XA))
#define X4(op) op(0); op(1); op(2); op(3)
#define Y4(op, k) op(k, 0); op(k, 1); op(k, 2); op(k, 3)
#define XA 0
#define XU 0
#define XS_R 0
#define SEQ_R LF(0); LC(); LF(1); LF(2); LF(3); LY(); ADV(); \
    RAD(0, 0); RAD(0, 1); RAD(1, 0); RAD(1, 1); RAD(2, 0); RAD(2, 1); RAD(3, 0); RAD(3, 1); RAD(4, 0); RAD(4, 1); LA(); \
    X4(P00); X4(TU); TM(); Y4(P10, 0); Y4(MU, 0); MM(0); Y4(P10, 1); Y4(MU, 1); MM(1); Y4(P10, 2); Y4(MU, 2); MM(2); \
    Y4(SD, 0); Y4(SD, 1); Y4(SD, 2); X4(P110);
#define XS_F 0
#define SEQ_F LN(); LF(0); LC(); LF(1); LF(2); LF(3); LY(); ADV(); FY(0); FZ(0); FY(1); FZ(1); FY(2); FZ(2); FY(3); SX(); SY(); \
    RAD(0, 0); RAD(0, 1); RAD(1, 0); RAD(1, 1); RAD(2, 0); RAD(2, 1); RAD(3, 0); RAD(3, 1); RAD(4, 0); RAD(4, 1); LA(); \
    X4(P00); X4(TU); TM(); Y4(P10, 0); Y4(MU, 0); MM(0); Y4(P10, 1); Y4(MU, 1); MM(1); Y4(P10, 2); Y4(MU, 2); MM(2); \
    Y4(SD, 0); Y4(SD, 1); Y4(SD, 2); X4(P110);

__global__ void __launch_bounds__(NT, 1)
tp_kernel(const int4* __restrict__ dst, const int4* __restrict__ src, const char* __restrict__ rhat, Scratch* __restrict__ gs,
          const char* __restrict__ x, const char* __restrict__ ea, const __nv_bfloat16* __restrict__ eps, char* __restrict__ out,
          const __grid_constant__ CUtensorMap m_wr, const __grid_constant__ CUtensorMap m_w0, const __grid_constant__ CUtensorMap m_w1) {
    extern __shared__ __align__(1024) char smem_raw[];
    constexpr uint32_t sm = 1024;
    spin_check((uint32_t)__cvta_generic_to_shared(smem_raw) == sm ? 0 : 2 * SPIN_LIMIT);
    int t;
    asm volatile("mov.u32 %0, %%tid.x;" : "=r"(t));
    const int w = t >> 5, lane = t & 31, b = blockIdx.x;

    const int g = lane >> 2, q = lane & 3, mat = lane >> 3, r = lane & 7;
    const int e0 = b * CH + t * 8, ne = min(CH, NE - b * CH);
    const bool act = t * 8 < ne;
    uint32_t d[8];
#pragma unroll
    for (int k = 0; k < 2; k++) ldg128(d + 4 * k, dst + e0 / 4 + k, act);
    uint32_t tag = ld_rlx(&gs->epoch[b * 32]), epl;
    asm volatile("ld.global.nc.u16 %0, [%1];" : "=r"(epl) : "l"(eps + min(lane, 26)));
    if (t < 60) sts128(sm + O_BCNT + 16 * t, make_uint4(0, 0, 0, 0));
    if (t == NT - 1) {
#pragma unroll
        for (int i = 0; i < 4; i++) mbar_init(sm + O_WBA + 8 * i, 1);
        fence_async();
        mbar_expect(sm + O_WBC, ne * 10); mbar_expect(sm + O_WBA, 20480); mbar_expect(sm + O_WBB, 98304); mbar_expect(sm + O_WBD, 65536);
        spin_check(tag);
        bulk(sm + O_RH, rhat + b * (CH * 6), ne * 6, sm + O_WBC);
        bulk(sm + O_SRC, src + b * (CH / 4), ne * 4, sm + O_WBC);
        tma3d(sm + O_WR0, &m_wr, 0, sm + O_WBA);
        tma3d(sm + O_WR1, &m_wr, 5, sm + O_WBA);
        tma3d(sm + O_W0S, &m_w0, 0, sm + O_WBD);
    }
    if (t == 320) {
#pragma unroll
        for (int i = 0; i < NSLOT; i++) {
            sts128(sm + O_RING + i * SLOT + S_C + 64, make_uint4(0, 0, 0, 0));
            mbar_init(sm + O_RING + i * SLOT + S_FULL, 32); mbar_init(sm + O_RING + i * SLOT + S_EMPTY, 8);
        }
    }
#pragma unroll
    for (int k = 0; k < LZ; k++) sts128(sm + O_L + 16 * (t + k * NT), make_uint4(0, 0, 0, 0));
    if (t < 80) sts32(sm + O_NCNT + 4 * t, t <= NLOC ? 4 * t : 0);
    if (t < 100) sts32(sm + O_NODE + 4 * t, 0);
    uint32_t ba[8], rk[8];
    auto pfx = [&](int r0, int n) {
        if (n) pf_l2(x + (b * NLOC + r0) * 1024, min(n, NN - b * NLOC - r0) * 1024);
    };
    if (w < 10) bar_sync(1, 320);
    tag = (tag + 1) << 30;
    if (act) {
#pragma unroll
        for (int i = 0; i < 8; i++) {
            const uint32_t l = __umulhi(d[i], (uint32_t)((1ull << 32) / G + 1));
            ba[i] = d[i] * 4 - l * (4 * G);
            d[i] = l * 4 + (tag + ((e0 + i + 1) << 9) + 4);
            rk[i] = atoms_add(sm + O_BCNT + ba[i], 4);
        }
#pragma unroll
        for (int i = 0; i < 8; i++)
            asm volatile("{.reg .pred p; setp.lt.u32 p, %2, 124; @p st.shared.u32 [%0], %1;}"
                         ::"r"(sm + O_KT + ba[i] * 32 + ((ba[i] + rk[i]) & 127)), "r"(d[i]), "r"(rk[i]) : "memory");
    }
    TS(0);
    __syncthreads();
    {
        int v[5], sum = 0;
#pragma unroll
        for (int i = 0; i < 5; i++) { v[i] = lds32(sm + O_BCNT + 4 * (lane * 5 + i)); sum += v[i]; }
        int e = warp_incl(sum) - sum;
        if (w == 10) {
#pragma unroll
            for (int i = 0; i < 5; i++) {
                const int k = lane * 5 + i;
                if (k < G) sts32(sm + O_KT + k * 128 + ((k * 4 + 124) & 127), tag | v[i] << 10 | e >> 2);
                e += v[i];
            }
            __syncwarp();
            if (lane == 0) {
                fence_async();
                bulk_st(&gs->keys[b * (G * 32)], sm + O_KT, G * 128);
                pfx(0, PFA);
            }
        } else {
#pragma unroll
            for (int i = 0; i < 5; i++) { sts32(sm + O_BOFF + 4 * (lane * 5 + i), e); e += v[i]; }
        }
        __syncwarp();
    }
    TS(11);
    const uint32_t sw = (uint32_t)(((2 * (w & 3) + (mat & 1)) ^ r) * 16 + ((mat >> 1) * 8 + r) * 128);
    uint32_t wr[5][4];
    const uint32_t* kp = &gs->keys[(w * SEGW * G + b) * 32 + ((lane + b) & 31)];
    uint32_t kv[SEGW + 1], ho[SEGW + 1], nk[SEGW + 1], old;
    if (act) {
        uint32_t mx = 0;
#pragma unroll
        for (int i = 0; i < 8; i++) { mx = max(mx, rk[i]); ba[i] = rk[i] + lds32(sm + O_BOFF + ba[i]); }
        if (mx >= 124) {
#pragma unroll
            for (int i = 0; i < 8; i++)
                if (rk[i] >= 124) st_rlx(&gs->more[b * CH + (ba[i] >> 2)], d[i]);
        }
    }
    if (w < 8) {
        mbar_wait(sm + O_WBA, 0);
#pragma unroll
        for (int p = 0; p < 5; p++) {
            const int c = 2 * p + (w >> 2);
            ldsm4t(wr[p], sm + (c < 5 ? O_WR0 : O_WR1 - 5 * 2048) + c * 2048 + sw);
        }
    }
    TS(21);
    mbar_wait(sm + O_WBC, 0);
    TS(22);
    if (act) {
        uint32_t s[8], y[12];
#pragma unroll
        for (int k = 0; k < 3; k++) *(uint4*)&y[4 * k] = lds128(sm + O_RH + t * 48 + k * 16);
#pragma unroll
        for (int k = 0; k < 2; k++) *(uint4*)&s[4 * k] = lds128(sm + O_SRC + t * 32 + k * 16);
#pragma unroll
        for (int i = 0; i < 8; i++) {
            const int k = 3 * i / 2;
            sts64(sm + O_OUT + ba[i] * 2, i & 1 ? __byte_perm(y[k], y[k + 1], 0x5432) : y[k],
                  __byte_perm(y[k + 1], s[i] + (tag >> 16) + 1, i & 1 ? 0x5432 : 0x5410));
        }
    }
    TS(12);
    if (w < 10) asm volatile("bar.arrive 4, 352;" ::: "memory");
    if (w == 11) {
        bar_sync(4, 352);
        if (lane == 0) { fence_async(); bulk_st(&gs->vals[b * CH], sm + O_OUT, ne * 8); pfx(PFA, PFB); }
        __syncwarp();
    }

    const uint32_t am = lane < 31 ? 511 : 0, none = tag | (320 + 4 * lane);
    auto check = [&]() {
        old = 0;
#pragma unroll
        for (int j = 0; j < SEGW; j++) {
            ho[j] = __shfl_sync(0xffffffffu, kv[j], 31);
            kv[j] = ho[j] >= (lane < 31 ? tag + ((lane + 1) << 12) : 0u) ? kv[j] : none;
            old |= kv[j] ^ tag;
        }
        return __any_sync(0xffffffffu, old >> 30);
    };
#pragma unroll
    for (int j = 0; j < SEGW; j++) kv[j] = ld_rlx(kp + j * (G * 32));
    TS(1);
    TV(19, 0);
    for (int it = 0; check(); it++) {
        spin_check(it);
        if (it == 0) TS(20);
        TV(19, (it + 1) * 100);
#pragma unroll
        for (int j = 0; j < SEGW; j++)
            if (__any_sync(0xffffffffu, (kv[j] ^ tag) >> 30)) kv[j] = ld_rlx(kp + j * (G * 32));
    }
    TS(3);
    kv[SEGW] = none; ho[SEGW] = 0;
    bool slow = false;
    const bool more = __any_sync(0xffffffffu, lane == 31 && (old & 0xfe0000));
    if (more) {
        int c = lane;
#pragma unroll
        for (int j = 0; j < SEGW; j++) {
            const int n = max((int)(ho[j] >> 12 & 0xfff) - 31, 0);
            if ((unsigned)c < (unsigned)n) ho[SEGW] = j * CH + (ho[j] & 0xfff) + 31 + c - lane;
            c -= n;
        }
        slow = lane == 31 && c < 0;
        if (c < 0 && lane < 31)
            for (int it = 0; ((kv[SEGW] = ld_rlx(&gs->more[w * SEGW * CH + lane + ho[SEGW]])) ^ tag) >> 30; it++) spin_check(it);
        __syncwarp();
    }
    uint32_t na_[SEGW + 1];
#pragma unroll
    for (int j = 0; j <= SEGW; j++) {
        na_[j] = (kv[j] & am) | (none & 511 & ~am);
        nk[j] = atoms_add(sm + O_NCNT + na_[j], 512);
    }
    auto visit = [&](auto f) {
#pragma unroll 1
        for (int j = 0; j < SEGW; j++) {
            const uint32_t* kl = &gs->keys[((w * SEGW + j) * G + b) * 32];
            const uint32_t h = ld_rlx(kl + ((31 + b) & 31));
#pragma unroll 1
            for (int i = lane; i < (h >> 12 & 0xfff); i += 32) {
                const int o = (w * SEGW + j) * CH + (h & 0xfff) + i;
                uint32_t k;
                int it = 0;
                do { k = ld_rlx(i < 31 ? kl + ((i + b) & 31) : &gs->more[o]); spin_check(it++); } while ((k ^ tag) >> 30);
                f(k, o, i);
            }
        }
    };
    slow = __syncthreads_or(slow);
    if (slow) {
        if (t < 80) sts32(sm + O_NCNT + 4 * t, t <= NLOC ? 4 * t : 0);
        __syncthreads();
        visit([&](uint32_t k, int, int) { atoms_add(sm + O_NCNT + (k & 511), 512); });
        __syncthreads();
    }
    TS(4);
    if (t == 352) pfx(PFA + PFB, PFC);
    if (w < 10) {
        const uint32_t key = lds32(sm + O_NCNT + 4 + (t & ~3));
        uint4 k[5];
#pragma unroll
        for (int i = 0; i < 5; i++) k[i] = lds128(sm + O_NCNT + q * 80 + i * 16);
        uint32_t c[4] = {0, 0, 0, 0};
#pragma unroll
        for (int i = 0; i < 5; i++) { c[0] += (key - k[i].x) >> 31; c[1] += (key - k[i].y) >> 31; c[2] += (key - k[i].z) >> 31; c[3] += (key - k[i].w) >> 31; }
        int rank = c[0] + c[1] + c[2] + c[3];
        rank += __shfl_xor_sync(0xffffffffu, rank, 1);
        rank += __shfl_xor_sync(0xffffffffu, rank, 2);
        if (t < NLOC * 4) sts32(sm + O_SORT + 4 * rank, key);
    }
    __syncthreads();
    TS(2);
    const bool on = lane < NLOC / 4;
    const uint4 k4 = lds128(sm + O_SORT + 16 * (on ? lane : 0));
    const uint32_t ks[4] = {k4.x, k4.y, k4.z, k4.w};
    const int n0 = on ? max(1u, (ks[0] + 3584) >> 12) : 0, n1 = on ? max(1u, (ks[2] + 3584) >> 12) : 0;
    const int u2 = warp_incl(n0 + n1), u1 = u2 - n1, u0 = u1 - n0;
    const int total = __shfl_sync(0xffffffffu, u2, 31);
    slow |= total > CAPT;
    int gbase = b * CAPT + 1;
    if (on) {
#pragma unroll
        for (int i = 0; i < 4; i++)
            sts32(sm + O_NOFF + (ks[i] & 511), (i >> 1 ? u1 : u0) * 128 + (i & 1 ? (slow ? 1 << 30 : LH) : 0) - ((ks[i] & 511) >> 5));
    }
    __syncwarp();
    auto mark = [&](int i) { const int node = (ks[i] & 511) * (G / 4) - G + b; return node < NN ? node + 1 : 0; };
    if (!slow) {
        const uint64_t vp = (uint64_t)&gs->vals[w * SEGW * CH + lane];
        uint64_t vv[SEGW + 1], va[SEGW + 1];
#pragma unroll
        for (int j = 0; j <= SEGW; j++) {
            nk[j] = lds32(sm + O_NOFF + na_[j]) + (nk[j] >> 5);
            va[j] = madw(j < SEGW ? ho[j] & 0xfff : ho[j], 8, vp) + (j < SEGW ? j * CH * 8 : 0);
            vv[j] = (uint64_t)tag << 32;
        }
        if (t == 352) asm volatile("cp.async.bulk.wait_group.read 0;" ::: "memory");
        __syncthreads();
        TS(13);
        if (t == 352) pfx(PFA + PFB + PFC, PFD);
        for (int it = 0;; it++) {
#pragma unroll
            for (int j = 0; j <= SEGW; j++)
                asm volatile("{.reg .pred p; setp.lt.u32 p, %2, 320; @p ld.relaxed.gpu.global.b64 %0, [%1];}" : "+l"(vv[j]) : "l"(va[j]), "r"(na_[j]) : "memory");
            old = 0;
#pragma unroll
            for (int j = 0; j <= SEGW; j++) old |= (uint32_t)(vv[j] >> 32) ^ tag;
            if (!__any_sync(0xffffffffu, old >> 30)) break;
            spin_check(it);
        }
#pragma unroll
        for (int j = 0; j <= SEGW; j++)
            asm volatile("{.reg .pred p; setp.ne.u32 p, %4, %5; @p st.shared.v4.u32 [%0], {%1,%2,%3,%4};}"
                         ::"r"(sm + O_L + nk[j]), "r"(kv[j]), "r"(0), "r"((uint32_t)vv[j]), "r"((uint32_t)(vv[j] >> 32)), "r"(tag) : "memory");
        if (na_[SEGW] < 320) gs->more[w * SEGW * CH + lane + ho[SEGW]] = 0;
    } else {
        int so = 0;
#pragma unroll
        for (int j = 0; j < SEGW; j++) so += ho[j] & 0xfff;
        if (lane == 0) atoms_add(sm + O_SUM, so);
        if (t == 352) asm volatile("cp.async.bulk.wait_group.read 0;" ::: "memory");
        __syncthreads();
        gbase = TBIG + (lds32(sm + O_SUM) >> 3) + (NLOC + 5) * b;
        auto put = [&](uint32_t k, uint64_t e, uint32_t a, int rank) {
            const uint32_t v = lds32(sm + O_NOFF + a) + (a >> 5) + rank * 16;
            unsigned short* p = (unsigned short*)(gs->list + (gbase + (v >> 7 & 0x7fffff) + (v >> 30) * NTILE) * 8);
            const int c = v >> 4 & 7, c2 = 8 + (c >> 1) * 4 + (c & 1);
            p[c] = e >> 48; p[c2] = k; p[c2 + 2] = k >> 16;
            p[32 + c] = e; p[40 + c] = e >> 16; p[48 + c] = e >> 32; p[56 + c] = 0;
        };
        visit([&](uint32_t k, int o, int i) {
            uint64_t e;
            int it = 0;
            do {
                asm volatile("ld.relaxed.gpu.global.b64 %0, [%1];" : "=l"(e) : "l"(&gs->vals[o]) : "memory");
                spin_check(it++);
            } while (((uint32_t)(e >> 32) ^ tag) >> 30);
            if (i >= 31) gs->more[o] = 0;
            put(k, e, k & 511, atoms_add(sm + O_NCUR + (k & 511), 1));
        });
#pragma unroll 1
        for (int i = 0; i < 4; i++) {
            const uint32_t k = i == 0 ? ks[0] : i == 1 ? ks[1] : i == 2 ? ks[2] : ks[3];
#pragma unroll 1
            for (int p = (k >> 9) + w; p < (i >> 1 ? n1 : n0) * 8; p += NT / 32) put(0, 0, k & 511, p);
        }
        __syncthreads();
        if (w == 0 && on) {
#pragma unroll
            for (int i = 0; i < 4; i++)
                *(uint32_t*)(gs->list + (gbase + (i >> 1 ? u1 : u0) + (i & 1) * NTILE) * 8 + 7) = mark(i) | (i & 1 ? 0 : i ? n1 : n0) << 16;
        }
        __threadfence();
    }
    int pos = gbase, end = gbase + __shfl_sync(0xffffffffu, NPRIV & 1 ? u1 : u2, (NPRIV - 1) / 2);
    __syncthreads();
    TS(5);

    if (w >= 8) {
        asm volatile("setmaxnreg.dec.sync.aligned.u32 " STR(PREG) ";");
        const int h = __reduce_max_sync(0xffffffffu, w & 3);
        const uint32_t ring = sm + O_RING;
        const int hp16 = r < 2 ? r * (NTILE * 8) : r < 4 ? r - 1 : NTILE * 8 + r - 3;
        uint32_t v0[3][4];
        if (!slow) {
            if (on) {
#pragma unroll
                for (int i = 0; i < 4; i++) sts32(sm + O_L + 4 + (i >> 1 ? u1 : u0) * 128 + (i & 1) * LH, mark(i));
                sts32(sm + O_L + 20 + u0 * 128, n0); sts32(sm + O_L + 20 + u1 * 128, n1);
            }
            __syncwarp();
#pragma unroll
            for (int k = 0; k < 3; k++) ldsm4t(v0[k], sm + O_L + (mat & 1) * LH + (h + 4 * k + (mat >> 1) * NSLOT) * 128 + r * 16);
        } else {
            if (r < 6 && h + 4 * mat < NSLOT) cpa16z(ring + (h + 4 * mat) * SLOT + S_H + r * 16, gs->list + (pos + h + 4 * mat) * 8 + hp16, 1);
            asm volatile("cp.async.wait_all;" ::: "memory");
        }
        const uint32_t xoff = opaque(mat * 4096 + ((r ^ (4 * (mat & 1))) * 16), lane);
        const uint32_t aoff = opaque(S_A + (lane >> 1) * 32 + (((lane ^ mat) & 1) * 16), lane);
        const uint32_t moff = opaque(mat < 2 ? (r < 4 ? S_C + mat * 80 + r * 16 : 0) : (mat == 2 && r < 6) ? S_H + r * 16 : 0, lane);
        const uint32_t hoff = opaque(S_H + mat * 8, lane), hoff2 = opaque(S_H + 32 + g * 8, lane);
        const uint32_t psel = opaque((lane & 2) ? 0x7632 : 0x5410, lane);
        const uint64_t xl = __shfl_sync(0xffffffffu, (uint64_t)(x - 1024 + r * 16) - (tag >> 6), lane);
        const uint64_t al = __shfl_sync(0xffffffffu, (uint64_t)(ea - 32 + (lane & 1) * 16) - (tag >> 4), lane);
        const uint64_t ml = __shfl_sync(0xffffffffu, (uint64_t)(gs->list + (mat < 2 ? mat * (NTILE * 8) + 4 + r : hp16)), lane);
        int cur = __reduce_max_sync(0xffffffffu, pos) + h;
        pos = cur + NSLOT; end = __reduce_max_sync(0xffffffffu, end);

        int ev = h ? end : end - 12, state = h ? 2 : 0, tk = 0, nr = 0, prv = pos - 1;
        uint32_t inf = 0;
        int ii = 0;
        auto take = [&]() {
            int v = 0;
            asm volatile("{.reg .pred p; setp.eq.s32 p, %2, 0; @p atom.relaxed.gpu.global.add.u32 %0, [%1], 1;}" : "+r"(v) : "l"(&gs->ticket), "r"(lane) : "memory");
            return v;
        };
        auto resolve = [&]() {
            const int k = __reduce_max_sync(0xffffffffu, tk);
            inf = tag;
            if (k < G * NPOOL) { const int l = k / G; ii = (k - l * G) * NPOOL + l; inf = ld_rlx(&gs->info[ii]); tk = take(); }
        };
        uint32_t so = ring + h * SLOT, ph = 1;
        auto fill = [&](auto first, const uint32_t* v) {
            constexpr bool F = decltype(first)::value;
            const uint32_t mi = max(moff >= S_H ? pos : cur, 0);
            const char* gm = (const char*)madw(mi, 128, ml);
            const uint32_t d0 = so + xoff;
            const uint32_t pa = so + (g == 7 ? S_H + q * 4 : g < 2 ? S_H + 32 + q * 8 + g * 4 : g == 2 ? S_C + 48 + q * 4 : S_C - 64 + lane * 4);
            const uint32_t ps = g == 7 ? 16 : g < 2 ? 32 : 80;
            mbar_wait(so + S_EMPTY, ph);
            if (F) {
                if (g != 3) { sts32(pa, v[0]); sts32(pa + ps, v[1]); }
                __syncwarp();
            } else if (cur <= 0) return false;
            const uint2 e = lds64(so + hoff), e2 = lds64(so + hoff2);
            const uint32_t s[4] = {e.x & 0xffffu, e.x >> 16, e.y & 0xffffu, e.y >> 16};
            const uint32_t id = __byte_perm(e2.x, e2.y, psel) >> 9;
            cpa16z(so + aoff, (const char*)madw(id, 32, al), id);
            if (F) {
                __syncwarp();
                if (ps != 80) { sts32(pa, v[2]); sts32(pa + ps, v[3]); }
            } else if (moff) cpa16z(so + moff, gm, mi);
#pragma unroll
            for (int j = 0; j < 4; j++) {
                const char* gx = (const char*)madw(s[j], 1024, xl);
#pragma unroll
                for (int k = 0; k < 8; k++) cpa16z((d0 ^ (j * 16)) + j * 1024 + k * 128, gx + k * 128, NULLP(s[j]));
            }
            asm volatile("cp.async.mbarrier.arrive.noinc.shared::cta.b64 [%0];" ::"r"(so + S_FULL) : "memory");
            if (so == ring) so += 4 * SLOT; else { so -= SLOT; ph ^= 1; }
            cur = prv;
            pos += 4; prv = pos - 1;
            return true;
        };
#pragma unroll 1
        for (int k = 0; k < 3; k++) {
            if (!slow) fill(Bool<true>(), v0[0]);
            if (k == 0) {
                asm volatile("bar.arrive 7, %0;" ::"n"(NT) : "memory");
                if (h == 3) {
                    bar_sync(5, 288);
                    if (lane == 0 && !slow) {
                        fence_async();
                        bulk_st(gs->list + gbase * 8, sm + O_L, total * 128);
                        bulk_st(gs->list + (gbase + NTILE) * 8, sm + O_L + LH, total * 128);
                    }
                    __syncwarp();
                }
            }
#pragma unroll
            for (int i = 0; i < 4; i++) { v0[0][i] = v0[1][i]; v0[1][i] = v0[2][i]; }
        }
        if (h == 3) {
            if (lane == 0) {
                asm volatile("cp.async.bulk.wait_group 0;\nfence.proxy.async;" ::: "memory");
                for (int j = 0; j < 4; j++) tma2d(sm + O_W1 + j * 24576, &m_w1, 64 * (j >> 1), 192 * (j & 1), sm + O_WBB);
            }
            __syncwarp();
            if (on && 2 * lane >= NPRIV) st_rlx(&gs->info[b * NPOOL + 2 * lane - NPRIV], tag | (gbase + u0) << 12 | n0);
            if (on && 2 * lane + 1 >= NPRIV) st_rlx(&gs->info[b * NPOOL + 2 * lane + 1 - NPRIV], tag | (gbase + u1) << 12 | n1);
        }
        bar_sync(6, 128);
        while (fill(Bool<false>(), nullptr)) {
            if (pos >= ev) {
                if (state == 0) { ev = end - 6; state = 1; tk = take(); }
                else if (state == 1) { resolve(); ev = end; state = 2; }
                else {
                    do {
                        const uint32_t mb = sm + O_MB + (nr & 31) * 8;
                        uint32_t rg;
                        nr++;
                        if (h == 0) {
                            for (int it = 0; (rg = __reduce_max_sync(0xffffffffu, inf ^ tag)) >> 30; it++) { spin_check(it); inf = ld_rlx(&gs->info[ii]); }
                            asm volatile("st.release.cta.shared.b64 [%0], %1;" ::"r"(mb), "l"(rg | (uint64_t)nr << 32) : "memory");
                            if (rg) resolve();
                        } else {
                            uint64_t m;
                            for (int it = 0;; it++) {
                                asm volatile("ld.acquire.cta.shared.b64 %0, [%1];" : "=l"(m) : "r"(mb) : "memory");
                                if (__all_sync(0xffffffffu, (int)(m >> 32) == nr)) break;
                                spin_check(it);
                            }
                            rg = __reduce_max_sync(0xffffffffu, (uint32_t)m);
                        }
                        const int ov = pos - end;
                        pos = rg ? (int)(rg >> 12) + ov : -(1 << 30);
                        if (ov) prv = pos - 1;
                        end = (rg >> 12) + (rg & 0xfff);
                    } while (pos >= end);
                    ev = end;
                }
            }
        }
        TSW(8 + (h & 1));
        if (lane == 0) sts32(so + S_C + 48, 0);
        mbar_arrive(so + S_FULL);
        if (t == 256) {
            gs->epoch[b * 32] = (tag >> 30) % 3;
            if (atomicInc(&gs->done, G - 1) == G - 1) gs->ticket = 0;
        }
        asm volatile("cp.async.wait_all;" ::: "memory");
    } else {
        asm volatile("setmaxnreg.inc.sync.aligned.u32 " STR(CREG) ";");
        const uint32_t xa = opaque(((mat >> 1) * 8 + r) * 1024 + (w >> 2) * 128 + (((2 * (w & 3) + (mat & 1)) ^ r) * 16), lane);
        const uint32_t aa = opaque(S_A + ((mat >> 1) * 8 + r) * 32 + (((mat & 1) ^ (r >> 2)) * 16), lane);
        const uint32_t ya = opaque(S_C + (mat & 1) * 80 + (mat >> 1) * 16, lane);
        const uint32_t yc = opaque(S_C + (mat < 2 ? mat * 80 + 32 : (r >> 2) == (mat & 1) && q < 3 ? (mat & 1) * 80 + q * 16 : 64), lane);
        const uint32_t ma = opaque(S_C + 48 + (lane >> 4) * 80, lane), na = opaque(sm + O_NODE + (lane >> 4) * 4, lane);
        const uint32_t pw = sm + O_P + w * PW;
        const uint32_t fx = opaque((q < 3 ? pw + P_1P0 + 2 * q * PSBO + (mat & 1) * 128 : sm + O_TRASH + ((pw - sm - O_TRASH + 96) & 127)) + (r >> 2) * PSBO, lane);
        const uint32_t fyz = opaque(pw + (q < 3 ? (mat < 2 ? P_1P1 : P_1P2) + 2 * q * PSBO : mat < 2 ? P_0P0 : P_0P1) + (mat & 1) * 128 + (r >> 2) * PSBO, lane);
        uint32_t oh[4][2];
#pragma unroll
        for (int c = 0; c < 8; c++) oh[c & 3][c >> 2] = opaque(g == c ? 0x3F803F80u : 0u, lane);
        uint32_t eb[3];
#pragma unroll
        for (int k = 0; k < 3; k++) {
            const int i = (g & 3) * 9 + (q & 1) * 6 + k;
            const uint32_t lo = __shfl_sync(0xffffffffu, epl, i), hi = __shfl_sync(0xffffffffu, epl, i + 3);
            eb[k] = (g & 3) < 3 && (q >> 1) == (g >> 2) ? (q & 1 ? lo : lo | hi << 16) : 0u;
        }
        asm volatile(".reg .pred lane0;\nsetp.eq.u32 lane0, %0, 0;" ::"r"(lane));
        uint32_t w0[16][4];
        bar_sync(7, NT);
        if (!slow) {
            uint32_t la = sm + O_L + (w & 1) * LH + (w >> 1) * 512;
            const uint32_t lo = (g < 2 ? 4 + q * 2 + g : g == 2 ? 28 + q : g == 7 ? q : lane) * 4;
#pragma unroll 1
            for (int c = total - 4 * (w >> 1); c > 0; c -= 48, la += 6144) {
                uint32_t v[3][4];
#pragma unroll
                for (int k = 0; k < 3; k++) ldsm4t(v[k], la + k * 2048 + lane * 16);
#pragma unroll
                for (int k = 0; k < 12; k++) sts32(la + lo + (k >> 2) * 2048 + (k & 3) * 128, v[k >> 2][k & 3]);
            }
        }
        mbar_wait(sm + O_WBD, 0);
#pragma unroll
        for (int k = 0; k < 16; k++) ldsm4t(w0[k], sm + O_W0S + (w >> 2) * 32768 + k * 2048 + sw);
        bar_sync(5, 288);
        TS(6);
        Acc A;
#pragma unroll
        for (int i = 0; i < 4; i++) { A.p00[i] = A.p110[i] = A.p10[0][i] = A.p10[1][i] = A.p10[2][i] = 0; A.t01[i] = A.m[0][i] = A.m[1][i] = A.m[2][i] = 0.f; }
        int slot = STAG * 16 - 16, rem;
        uint32_t so = sm + O_RING, ph = opaque(0, lane), a[4], ok, mt = 0;
        const uint32_t wg = __reduce_max_sync(0xffffffffu, w >> 2);
        mbar_wait(so + S_FULL, 0);
        ldsm4(a, so + aa);
        TS(7);
        while (true) {
            {
                constexpr bool F = true, XS = XS_F;
                uint32_t yb[8], f[4][4], R[5][4], u[4][4], sd[4];
                float y[4], z[4];
                const uint32_t sof = slot & 112;
                SEQ_F
                slot += 16;
            }
            if (!(ok && rem > 0 && slot != 128)) {
                if (slot == 128 || rem < 0) {
                    asm volatile("fence.proxy.async.shared::cta;" ::: "memory");
                    mbar_wait(sm + O_WBB, 0);
                    bar_sync(1, 256);
                    float d0[8], d1[24];
                    const uint64_t db = (uint64_t)((sm + O_P) >> 4) | (8ull << 16) | ((uint64_t)(PSBO / 16) << 32);
                    const uint32_t da = ((sm + O_W1) >> 4 | 1 << 16) + wg * 3072;
                    asm volatile("wgmma.fence.sync.aligned;" ::: "memory");
#pragma unroll
                    for (int k = 0; k < 16; k++) wg_rs16(d0, w0[k], db + (((k & 7) * PW + ((k >> 3) ? P_0P1 : P_0P0)) >> 4), k);
                    asm volatile("wgmma.commit_group.sync.aligned;" ::: "memory");
#pragma unroll
                    for (int k = 0; k < 24; k++)
                        wg_ss48(d1, (da + k * 128) | (64ull << 32) | (1ull << 62), db + (((k & 7) * PW + ((k >> 3) == 0 ? P_1P0 : (k >> 3) == 1 ? P_1P1 : P_1P2)) >> 4), k);
                    asm volatile("wgmma.commit_group.sync.aligned;" ::: "memory");
                    const uint2 n0 = lds64(sm + O_NODE + mat * 16), n1 = lds64(sm + O_NODE + 64 + mat * 16);
                    const uint32_t nd[4] = {mat * 16 < slot ? n0.x & 0xffff : 0, mat * 16 + 64 < slot ? n1.x & 0xffff : 0, mat * 16 < slot ? n0.y : 0, mat * 16 + 64 < slot ? n1.y : 0};
                    const uint64_t op = (uint64_t)(out - 1024 + (w & 3) * 256 + (w >> 2) * 128 + r * 16);
                    uint64_t oa[4];
#pragma unroll
                    for (int it = 0; it < 4; it++) oa[it] = madw(nd[it], 1024, op);
                    uint32_t sg = sm + O_P + (w & 4) * PW + ((mat >> 1) * 8 + r) * 128 + (((2 * (w & 3) + (mat & 1)) ^ r) * 16);
                    uint32_t sl = pw + mat * 128 + (r ^ mat) * 16, sl2 = pw + 512 + mat * 128 + (r ^ mat ^ 4) * 16;
                    asm volatile("wgmma.wait_group.sync.aligned 1;" ::: "memory");
#pragma unroll
                    for (int i = 0; i < 8; i++) asm volatile("" : "+f"(d0[i])::"memory");
                    uint32_t o[4][4], chk = sg & sl & sl2;
                    float gt[8];
#pragma unroll
                    for (int i = 0; i < 8; i++) {
                        asm("ex2.approx.ftz.f32 %0, %1;" : "=f"(gt[i]) : "f"(d0[i] * -1.4426950408889634f));
                        asm("rcp.approx.ftz.f32 %0, %1;" : "=f"(gt[i]) : "f"(gt[i] + 1.f));
                        chk &= __float_as_uint(gt[i]);
                    }
#pragma unroll
                    for (int i = 0; i < 4; i++) { o[0][i] = pack(d0[2 * i], d0[2 * i + 1]); chk &= o[0][i] & (uint32_t)(oa[i] >> 32); }
                    sts32(sm + O_TRASH, chk);
                    asm volatile("wgmma.wait_group.sync.aligned 0;" ::: "memory");
#pragma unroll
                    for (int i = 0; i < 24; i++) asm volatile("" : "+f"(d1[i])::"memory");
                    bar_sync(1, 256);
#pragma unroll
                    for (int i = 0; i < 4; i++)
#pragma unroll
                        for (int j = 0; j < 3; j++) o[1 + j][i] = pack(d1[8 * j + 2 * i] * gt[2 * i], d1[8 * j + 2 * i + 1] * gt[2 * i + 1]);
#pragma unroll
                    for (int j = 0; j < 4; j++) stsm4t(sg + j * PW, o[j][0], o[j][1], o[j][2], o[j][3]);
                    bar_sync(2 + wg, 128);
                    uint4 v[4];
#pragma unroll
                    for (int it = 0; it < 4; it++) v[it] = lds128((it & 1 ? sl2 : sl) + (it >> 1) * 1024);
#pragma unroll
                    for (int it = 0; it < 4; it++)
                        asm volatile("{.reg .pred p; setp.ne.u32 p, %5, 0; @p st.global.v4.u32 [%0], {%1,%2,%3,%4};}"
                                     ::"l"(oa[it]), "r"(v[it].x), "r"(v[it].y), "r"(v[it].z), "r"(v[it].w), "r"(nd[it]) : "memory");
                    __syncwarp();
                    slot = 0;
                    if (rem < 0) break;
                }
                if (!ok) { mbar_wait(so + S_FULL, ph >> 31); ldsm4(a, so + aa); }
                if (rem == 0) continue;
            }
            while (true) {
                do {
                    constexpr bool F = false, XS = XS_R;
                    uint32_t yb[8], f[4][4], R[5][4], u[4][4], sd[4];
                    SEQ_R
                    rem--;
                } while (ok && rem > 0);
                if (ok) break;
                mbar_wait(so + S_FULL, ph >> 31); ldsm4(a, so + aa);
                if (rem == 0) break;
            }
        }
        TS(10);
    }
}

typedef CUresult (*EncFn)(CUtensorMap*, CUtensorMapDataType, cuuint32_t, void*, const cuuint64_t*, const cuuint64_t*,
                          const cuuint32_t*, const cuuint32_t*, CUtensorMapInterleave, CUtensorMapSwizzle,
                          CUtensorMapL2promotion, CUtensorMapFloatOOBfill);

void make_map(EncFn fn, CUtensorMap* m, void* p, int rows, int cols, int brows, int rank, int bblk, CUtensorMapSwizzle swz) {
    cuuint64_t dims[3] = {(cuuint64_t)(rank == 3 ? 64 : cols), (cuuint64_t)rows, (cuuint64_t)cols / 64}, strides[2] = {(cuuint64_t)cols * 2, 128};
    cuuint32_t box[3] = {64, (cuuint32_t)brows, (cuuint32_t)bblk}, es[3] = {1, 1, 1};
    fn(m, CU_TENSOR_MAP_DATA_TYPE_BFLOAT16, rank, p, dims, strides, box, es, CU_TENSOR_MAP_INTERLEAVE_NONE,
       swz, CU_TENSOR_MAP_L2_PROMOTION_NONE, CU_TENSOR_MAP_FLOAT_OOB_FILL_NONE);
}

}

extern "C" void kernel_launch(void* const* d_in, const int* in_sizes, int n_in, void* d_out, int out_size) {
    static EncFn enc = nullptr;
    static void* scratch = nullptr;
    if (!enc) {
        void* fn = nullptr;
        cudaDriverEntryPointQueryResult qr;
        cudaGetDriverEntryPoint("cuTensorMapEncodeTiled", &fn, cudaEnableDefault, &qr);
        enc = (EncFn)fn;
        cudaGetSymbolAddress(&scratch, g_scratch);
        cudaFuncSetAttribute(tp_kernel, cudaFuncAttributeMaxDynamicSharedMemorySize, SMEM_BYTES);
    }
    CUtensorMap m_wr, m_w0, m_w1;
    make_map(enc, &m_wr, d_in[5], 16, 640, 16, 3, 5, CU_TENSOR_MAP_SWIZZLE_128B);
    make_map(enc, &m_w0, d_in[6], 256, 128, 256, 3, 2, CU_TENSOR_MAP_SWIZZLE_128B);
    make_map(enc, &m_w1, d_in[7], 384, 128, 192, 2, 1, CU_TENSOR_MAP_SWIZZLE_128B);
    tp_kernel<<<G, NT, SMEM_BYTES>>>((const int4*)d_in[4], (const int4*)d_in[3], (const char*)d_in[1], (Scratch*)scratch,
                                     (const char*)d_in[0], (const char*)d_in[2], (const __nv_bfloat16*)d_in[8], (char*)d_out,
                                     m_wr, m_w0, m_w1);
}
```

```cpp
#include <cuda_runtime.h>
#include <cuda_bf16.h>
#include <cuda.h>
#include <stdint.h>
#include <stddef.h>

namespace {

constexpr int NN = 10000;
constexpr int NE = 320000;
constexpr int G = 132;
constexpr int NT = 384;
constexpr int CH = 2432;
constexpr int NLOC = (NN + G - 1) / G;
#define NPOOL 5
constexpr int NPAIR = NLOC / 2, NPRIV = NPAIR - NPOOL;
constexpr int SEGW = 11;

#define NSLOT 5
#define PFA 16
#define PFB 20
#define PFC 20
#define PFD 20
#define STAG (b & 7)
#define NULLP(v) v
#define CREG 216
#define PREG 72
#define STR2(x) #x
#define STR(x) STR2(x)

constexpr int S_A = 16384, S_C = S_A + 512, S_FULL = S_C + 144, S_EMPTY = S_FULL + 8, S_H = S_C + 160, SLOT = 17152;

constexpr int PSBO = 272;
constexpr int PB1 = 5 * PSBO + 256, PB0 = PSBO + 256;
constexpr int P_1P0 = 0, P_1P1 = PB1, P_0P1 = 2 * PB1, P_0P0 = P_0P1 + PB0, P_1P2 = P_0P0 + PB0;
constexpr int PW = P_1P2 + PB1;

constexpr int O_W1 = 0;
constexpr int O_P = 98304;
constexpr int O_RING = O_P + 8 * PW;
constexpr int O_TRASH = O_RING + 5 * SLOT;
constexpr int O_WBA = O_TRASH + 512, O_WBB = O_WBA + 8, O_WBC = O_WBA + 16, O_WBD = O_WBA + 24, O_NODE = O_WBA + 48;
constexpr int O_SUM = O_NODE + 128, O_MB = O_SUM + 16;
constexpr int SMEM_BYTES = O_MB + 256;
constexpr int CAPT = 240, LH = CAPT * 128;
constexpr int O_L = 0, LZ = 2 * LH / (NT * 16), O_W0S = O_L + 2 * LH, O_OUT = O_W0S + 65536, O_RH = O_OUT + CH * 8;
constexpr int O_KT = O_RING + SLOT, O_SRC = O_RING + 2 * SLOT;
constexpr int O_BCNT = O_SRC + CH * 4, O_NCUR = O_BCNT + 640, O_NCNT = O_NCUR + 320;
constexpr int O_BOFF = O_NCNT + 512, O_SORT = O_BOFF + 640, O_NOFF = O_SORT + 320;
constexpr int O_WR0 = (O_RING + 3 * SLOT + 1023) / 1024 * 1024, O_WR1 = (O_RING + 4 * SLOT + 1023) / 1024 * 1024;
constexpr int TBIG = G * CAPT + 8, NTILE = TBIG + NE / 8 + G * (NLOC + 5);
static_assert(SMEM_BYTES <= 232448 && NSLOT == 5 && CAPT % 16 == 0 && NTILE < (1 << 18), "smem");
static_assert(LZ * NT * 16 == 2 * LH && O_W0S % 1024 == 0 && O_RH + CH * 6 <= O_RING + S_C && G * 128 <= S_C && O_NOFF + 512 <= O_SRC + S_C, "staging");
static_assert(O_RING % 128 == 0 && SLOT % 128 == 0 && 2 * LH <= O_P, "layout");
static_assert(G * CH >= NE && NE % 8 == 0 && CH < 4096 && CH / 8 <= 320 && NE < (1 << 21), "chunks");
static_assert(SEGW * (NT / 32) == G && G <= 160 && G % 4 == 0, "segments");
static_assert(NLOC % 4 == 0 && NLOC < 80 && NLOC * 4 <= 320 && NN < 0xffff && NE / 8 < 0xffff && NPRIV >= 30, "scan width");

struct __align__(128) Scratch {
    uint32_t keys[G * G * 32];
    uint64_t vals[G * CH];
    uint32_t more[G * CH];
    uint32_t epoch[G * 32];
    uint32_t info[G * NPOOL];
    unsigned done, pad0[31], ticket, pad1[31 + 32 - G * NPOOL % 32];
    uint4 list[2 * NTILE * 8];
};
static_assert(offsetof(Scratch, list) % 128 == 0, "list");
__device__ Scratch g_scratch;
#define TS(i)
#define TSW(i)
#define TV(i, v)

constexpr int SPIN_LIMIT = 1 << 24;

__device__ __forceinline__ void mbar_init(uint32_t a, int c) { asm volatile("mbarrier.init.shared::cta.b64 [%0], %1;" ::"r"(a), "r"(c) : "memory"); }
__device__ __forceinline__ void mbar_expect(uint32_t a, int b) { asm volatile("mbarrier.arrive.expect_tx.shared::cta.b64 _, [%0], %1;" ::"r"(a), "r"(b) : "memory"); }
__device__ __forceinline__ void mbar_arrive(uint32_t a) { asm volatile("mbarrier.arrive.shared::cta.b64 _, [%0];" ::"r"(a) : "memory"); }
__device__ __forceinline__ void mbar_wait(uint32_t a, uint32_t ph) {
    asm volatile("{\n.reg .pred p, q;\n.reg .u32 it;\n"
                 "mbarrier.try_wait.parity.shared::cta.b64 p, [%0], %1;\n"
                 "@p bra DONE;\n"
                 "mov.u32 it, 0;\n"
                 "LOOP:\n"
                 "mbarrier.try_wait.parity.shared::cta.b64 p, [%0], %1;\n"
                 "@p bra DONE;\n"
                 "add.u32 it, it, 1;\n"
                 "setp.gt.u32 q, it, %2;\n"
                 "@q trap;\n"
                 "bra LOOP;\n"
                 "DONE:\n}" ::"r"(a), "r"(ph), "n"(SPIN_LIMIT) : "memory");
}
__device__ __forceinline__ void spin_check(int it) {
    asm volatile("{\n.reg .pred q;\nsetp.gt.s32 q, %0, %1;\n@q trap;\n}" ::"r"(it), "n"(SPIN_LIMIT));
}
__device__ __forceinline__ void tma2d(uint32_t dst, const CUtensorMap* m, int c0, int c1, uint32_t bar) {
    asm volatile("cp.async.bulk.tensor.2d.shared::cluster.global.mbarrier::complete_tx::bytes [%0], [%1, {%3, %4}], [%2];"
                 ::"r"(dst), "l"(m), "r"(bar), "r"(c0), "r"(c1) : "memory");
}
__device__ __forceinline__ void cpa16z(uint32_t d, const void* g, uint32_t v) {
    asm volatile("{\n.reg .pred p;\nsetp.eq.u32 p, %2, 0;\ncp.async.cg.shared.global [%0], [%1], 16, p;\n}" ::"r"(d), "l"(g), "r"(v) : "memory");
}
__device__ __forceinline__ void ldsm4(uint32_t* r, uint32_t a) { asm volatile("ldmatrix.sync.aligned.m8n8.x4.shared.b16 {%0,%1,%2,%3}, [%4];" : "=r"(r[0]), "=r"(r[1]), "=r"(r[2]), "=r"(r[3]) : "r"(a) : "memory"); }
__device__ __forceinline__ void ldsm4t(uint32_t* r, uint32_t a) { asm volatile("ldmatrix.sync.aligned.m8n8.x4.trans.shared.b16 {%0,%1,%2,%3}, [%4];" : "=r"(r[0]), "=r"(r[1]), "=r"(r[2]), "=r"(r[3]) : "r"(a) : "memory"); }
__device__ __forceinline__ void stsm4t(uint32_t a, uint32_t r0, uint32_t r1, uint32_t r2, uint32_t r3) { asm volatile("stmatrix.sync.aligned.m8n8.x4.trans.shared.b16 [%0], {%1,%2,%3,%4};" ::"r"(a), "r"(r0), "r"(r1), "r"(r2), "r"(r3) : "memory"); }
__device__ __forceinline__ void stsm2t(uint32_t a, uint32_t r0, uint32_t r1) { asm volatile("stmatrix.sync.aligned.m8n8.x2.trans.shared.b16 [%0], {%1,%2};" ::"r"(a), "r"(r0), "r"(r1) : "memory"); }
__device__ __forceinline__ void mma16(float* d, const uint32_t* a, uint32_t b0, uint32_t b1) {
    asm("mma.sync.aligned.m16n8k16.row.col.f32.bf16.bf16.f32 {%0,%1,%2,%3}, {%4,%5,%6,%7}, {%8,%9}, {%0,%1,%2,%3};"
        : "+f"(d[0]), "+f"(d[1]), "+f"(d[2]), "+f"(d[3]) : "r"(a[0]), "r"(a[1]), "r"(a[2]), "r"(a[3]), "r"(b0), "r"(b1));
}
__device__ __forceinline__ void mma8(float* d, uint32_t a0, uint32_t a1, uint32_t b0) {
    asm("mma.sync.aligned.m16n8k8.row.col.f32.bf16.bf16.f32 {%0,%1,%2,%3}, {%4,%5}, {%6}, {%0,%1,%2,%3};"
        : "+f"(d[0]), "+f"(d[1]), "+f"(d[2]), "+f"(d[3]) : "r"(a0), "r"(a1), "r"(b0));
}
__device__ __forceinline__ void mma16z(float* d, const uint32_t* a, uint32_t b0, uint32_t b1) {
    asm("mma.sync.aligned.m16n8k16.row.col.f32.bf16.bf16.f32 {%0,%1,%2,%3}, {%4,%5,%6,%7}, {%8,%9}, {%10,%10,%10,%10};"
        : "=f"(d[0]), "=f"(d[1]), "=f"(d[2]), "=f"(d[3]) : "r"(a[0]), "r"(a[1]), "r"(a[2]), "r"(a[3]), "r"(b0), "r"(b1), "f"(0.f));
}
__device__ __forceinline__ uint32_t pack(float lo, float hi) { uint32_t r; asm("cvt.rn.bf16x2.f32 %0, %1, %2;" : "=r"(r) : "f"(hi), "f"(lo)); return r; }
__device__ __forceinline__ uint32_t hmul(uint32_t a, uint32_t b) { uint32_t r; asm("mul.rn.bf16x2 %0, %1, %2;" : "=r"(r) : "r"(a), "r"(b)); return r; }
__device__ __forceinline__ uint32_t hfma(uint32_t a, uint32_t b, uint32_t c) { uint32_t r; asm("fma.rn.bf16x2 %0, %1, %2, %3;" : "=r"(r) : "r"(a), "r"(b), "r"(c)); return r; }
__device__ __forceinline__ uint4 lds128(uint32_t a) { uint4 v; asm volatile("ld.shared.v4.u32 {%0,%1,%2,%3}, [%4];" : "=r"(v.x), "=r"(v.y), "=r"(v.z), "=r"(v.w) : "r"(a) : "memory"); return v; }
__device__ __forceinline__ void sts128(uint32_t a, uint4 v) { asm volatile("st.shared.v4.u32 [%0], {%1,%2,%3,%4};" ::"r"(a), "r"(v.x), "r"(v.y), "r"(v.z), "r"(v.w) : "memory"); }
__device__ __forceinline__ int lds32(uint32_t a) { int v; asm volatile("ld.shared.u32 %0, [%1];" : "=r"(v) : "r"(a) : "memory"); return v; }
__device__ __forceinline__ void sts32(uint32_t a, int v) { asm volatile("st.shared.u32 [%0], %1;" ::"r"(a), "r"(v) : "memory"); }
__device__ __forceinline__ int atoms_add(uint32_t a, int v) { int r; asm volatile("atom.shared.add.u32 %0, [%1], %2;" : "=r"(r) : "r"(a), "r"(v) : "memory"); return r; }
__device__ __forceinline__ uint32_t ld_rlx(const void* p) { uint32_t v; asm volatile("ld.relaxed.gpu.global.u32 %0, [%1];" : "=r"(v) : "l"(p) : "memory"); return v; }
__device__ __forceinline__ void st_rlx(void* p, uint32_t v) { asm volatile("st.relaxed.gpu.global.u32 [%0], %1;" ::"l"(p), "r"(v) : "memory"); }
__device__ __forceinline__ void bulk(uint32_t dst, const void* g, int n, uint32_t bar) {
    asm volatile("cp.async.bulk.shared::cluster.global.mbarrier::complete_tx::bytes [%0], [%1], %2, [%3];" ::"r"(dst), "l"(g), "r"(n), "r"(bar) : "memory");
}
__device__ __forceinline__ void bulk_st(void* g, uint32_t src, int n) {
    asm volatile("cp.async.bulk.global.shared::cta.bulk_group [%0], [%1], %2;\ncp.async.bulk.commit_group;" ::"l"(g), "r"(src), "r"(n) : "memory");
}
__device__ __forceinline__ uint2 lds64(uint32_t a) { uint2 v; asm volatile("ld.shared.v2.u32 {%0,%1}, [%2];" : "=r"(v.x), "=r"(v.y) : "r"(a) : "memory"); return v; }
__device__ __forceinline__ void sts64(uint32_t a, uint32_t x, uint32_t y) { asm volatile("st.shared.v2.u32 [%0], {%1,%2};" ::"r"(a), "r"(x), "r"(y) : "memory"); }
__device__ __forceinline__ void tma3d(uint32_t dst, const CUtensorMap* m, int c2, uint32_t bar) {
    asm volatile("cp.async.bulk.tensor.3d.shared::cluster.global.mbarrier::complete_tx::bytes [%0], [%1, {%3, %3, %4}], [%2];"
                 ::"r"(dst), "l"(m), "r"(bar), "r"(0), "r"(c2) : "memory");
}
__device__ __forceinline__ void pf_l2(const void* g, int n) {
    asm volatile("{.reg .pred p; setp.gt.s32 p, %1, 0; @p cp.async.bulk.prefetch.L2.global [%0], %1;}" ::"l"(g), "r"(n) : "memory");
}
__device__ __forceinline__ void fence_async() { asm volatile("fence.proxy.async.shared::cta;" ::: "memory"); }
__device__ __forceinline__ uint64_t madw(uint32_t a, uint32_t b, uint64_t c) { uint64_t r; asm("mad.wide.u32 %0, %1, %2, %3;" : "=l"(r) : "r"(a), "r"(b), "l"(c)); return r; }
__device__ __forceinline__ uint32_t opaque(uint32_t v, int lane) { return __shfl_sync(0xffffffffu, v, lane); }
__device__ __forceinline__ void bar_sync(int id, int n) { asm volatile("bar.sync %0, %1;" ::"r"(id), "r"(n) : "memory"); }

__device__ __forceinline__ void wg_rs16(float* d, const uint32_t* a, uint64_t db, int sc) {
    asm volatile("{.reg .pred p; setp.ne.b32 p, %13, 0;\n"
                 "wgmma.mma_async.sync.aligned.m64n16k16.f32.bf16.bf16 {%0,%1,%2,%3,%4,%5,%6,%7}, {%8,%9,%10,%11}, %12, p, 1, 1, 0;}"
                 : "+f"(d[0]), "+f"(d[1]), "+f"(d[2]), "+f"(d[3]), "+f"(d[4]), "+f"(d[5]), "+f"(d[6]), "+f"(d[7])
                 : "r"(a[0]), "r"(a[1]), "r"(a[2]), "r"(a[3]), "l"(db), "r"(sc));
}
__device__ __forceinline__ void wg_ss48(float* d, uint64_t da, uint64_t db, int sc) {
    asm volatile("{.reg .pred p; setp.ne.b32 p, %26, 0;\n"
                 "wgmma.mma_async.sync.aligned.m64n48k16.f32.bf16.bf16 {%0,%1,%2,%3,%4,%5,%6,%7,%8,%9,%10,%11,%12,%13,%14,%15,%16,%17,%18,%19,%20,%21,%22,%23}, %24, %25, p, 1, 1, 1, 0;}"
                 : "+f"(d[0]), "+f"(d[1]), "+f"(d[2]), "+f"(d[3]), "+f"(d[4]), "+f"(d[5]), "+f"(d[6]), "+f"(d[7]),
                   "+f"(d[8]), "+f"(d[9]), "+f"(d[10]), "+f"(d[11]), "+f"(d[12]), "+f"(d[13]), "+f"(d[14]), "+f"(d[15]),
                   "+f"(d[16]), "+f"(d[17]), "+f"(d[18]), "+f"(d[19]), "+f"(d[20]), "+f"(d[21]), "+f"(d[22]), "+f"(d[23])
                 : "l"(da), "l"(db), "r"(sc));
}

__device__ __forceinline__ int warp_incl(int v) {
#pragma unroll
    for (int o = 1; o < 32; o <<= 1)
        asm volatile("{.reg .pred p; .reg .b32 u; shfl.sync.up.b32 u|p, %0, %1, 0, 0xffffffff; @p add.s32 %0, %0, u;}" : "+r"(v) : "r"(o));
    return v;
}
__device__ __forceinline__ void ldg128(uint32_t* r, const void* p, bool on) {
    asm volatile("{.reg .pred p; setp.ne.u32 p, %5, 0; @p ld.global.nc.v4.u32 {%0,%1,%2,%3}, [%4];}"
                 : "=r"(r[0]), "=r"(r[1]), "=r"(r[2]), "=r"(r[3]) : "l"(p), "r"((uint32_t)on));
}

template <bool B> struct Bool { static constexpr bool value = B; };
struct Acc {
    uint32_t p00[4], p110[4], p10[3][4];
    float t01[4], m[3][4];
};

#define LF(m) ldsm4t(f[m], so + xa + m * 256)
#define LY() ldsm4(yb, so + ya)
#define LC() ldsm4(yb + 4, so + yc)
#define ADV() { asm volatile("@lane0 mbarrier.arrive.shared::cta.b64 _, [%0];" ::"r"(so + S_EMPTY) : "memory"); \
                const bool wrap = so == sm + O_RING + (NSLOT - 1) * SLOT; so = wrap ? sm + O_RING : so + SLOT; ph ^= wrap ? 0x80000000u : 0u; }
#define LA() asm volatile("{\n.reg .pred p;\n.reg .b64 s;\nmov.b64 s, {0, %6};\nmbarrier.test_wait.shared::cta.b64 p, [%5], s;\nselp.u32 %4, 1, 0, p;\n" \
                          "@p ldmatrix.sync.aligned.m8n8.x4.shared.b16 {%0,%1,%2,%3}, [%7];\n}" \
                          : "+r"(a[0]), "+r"(a[1]), "+r"(a[2]), "+r"(a[3]), "=r"(ok) : "r"(so + S_FULL), "r"(ph), "r"(so + aa) : "memory")
#define RAD(p, s) { float c[4]; mma16z(c, wr[p], a[2 * s], a[2 * s + 1]); R[p][2 * s] = pack(c[0], c[1]); R[p][2 * s + 1] = pack(c[2], c[3]); }
#define MUL(n, x, y) (XS >> n & 1 ? hmul(y, x) : hmul(x, y))
#define FMA(n, x, y, z) (XS >> n & 1 ? hfma(y, x, z) : hfma(x, y, z))
#define ACC(n, x, y, z) z = F ? MUL(n, x, y) : FMA(n, x, y, z)
#define P00(i) ACC(0, f[0][i], R[0][i], A.p00[i ^ XA])
#define P10(k, i) ACC(1, f[1 + k][i], R[3][i], A.p10[k][i ^ XA])
#define S0(k, i) sd[i] = MUL(2, f[1 + k][i], yb[2 * k + (i >> 1)])
#define SD(k, i) sd[i] = FMA(2, f[1 + k][i], yb[2 * k + (i >> 1)], sd[i])
#define P110(i) ACC(3, sd[i], R[1][i], A.p110[i ^ XA])
#define TU(i) u[3][i ^ XU] = MUL(4, f[0][i], R[2][i])
#define TM() if (F) mma16z(A.t01, u[3], yb[6], yb[7]); else mma16(A.t01, u[3], yb[6], yb[7])
#define MU(k, i) u[k][i ^ XU] = MUL(5, f[1 + k][i], R[4][i])
#define MM(k) if (F) mma16z(A.m[k], u[k], yb[6], yb[7]); else mma16(A.m[k], u[k], yb[6], yb[7])
#define PK(v, h) pack(v[2 * (h)], v[2 * (h) + 1])
#define LN() { sts32(na + sof, mt); mt = lds32(so + ma); rem = (int)(__reduce_max_sync(0xffffffffu, mt) >> 16) - 1; }
#define FY(k) if (k == 0) mma16z(y, A.p10[0], oh[0][0], oh[0][1]); else mma16(y, k < 3 ? A.p10[k % 3] : A.p00, oh[k][0], oh[k][1])
#define FZ(k) if (k == 0) mma16z(z, A.p110, oh[3][0], oh[3][1]); \
              else if (k == 1) { const uint32_t mp[4] = {PK(A.m[0], XA ^ XU), PK(A.m[0], 1 ^ XA ^ XU), PK(A.m[1], XA ^ XU), PK(A.m[1], 1 ^ XA ^ XU)}; mma16(z, mp, eb[0], eb[1]); } \
              else mma8(z, PK(A.m[2], XA ^ XU), PK(A.m[2], 1 ^ XA ^ XU), eb[2])
#define SX() stsm2t(fx + sof, PK(A.t01, XU), PK(A.t01, 1 ^ XU))
#define SY() stsm4t(fyz + sof, PK(y, XA), PK(y, 1 ^ XA), PK(z, XA), PK(z, 1 ^ XA))
#define X4(op) op(0); op(1); op(2); op(3)
#define Y4(op, k) op(k, 0); op(k, 1); op(k, 2); op(k, 3)
#define XA 0
#define XU 0
#define XS_R 0
#define SEQ_R LF(0); LC(); LF(1); LF(2); LF(3); LY(); ADV(); \
    RAD(0, 0); RAD(0, 1); RAD(1, 0); RAD(1, 1); RAD(2, 0); RAD(2, 1); RAD(3, 0); RAD(3, 1); RAD(4, 0); RAD(4, 1); LA(); \
    X4(P00); X4(TU); TM(); Y4(P10, 0); Y4(MU, 0); MM(0); Y4(P10, 1); Y4(MU, 1); MM(1); Y4(P10, 2); Y4(MU, 2); MM(2); \
    Y4(S0, 0); Y4(SD, 1); Y4(SD, 2); X4(P110);
#define XS_F 0
#define SEQ_F LN(); LF(0); LC(); LF(1); LF(2); LF(3); LY(); ADV(); FY(0); FZ(0); FY(1); FZ(1); FY(2); FZ(2); FY(3); SX(); SY(); \
    RAD(0, 0); RAD(0, 1); RAD(1, 0); RAD(1, 1); RAD(2, 0); RAD(2, 1); RAD(3, 0); RAD(3, 1); RAD(4, 0); RAD(4, 1); LA(); \
    X4(P00); X4(TU); TM(); Y4(P10, 0); Y4(MU, 0); MM(0); Y4(P10, 1); Y4(MU, 1); MM(1); Y4(P10, 2); Y4(MU, 2); MM(2); \
    Y4(S0, 0); Y4(SD, 1); Y4(SD, 2); X4(P110);

__global__ void __launch_bounds__(NT, 1)
tp_kernel(const int4* __restrict__ dst, const int4* __restrict__ src, const char* __restrict__ rhat, Scratch* __restrict__ gs,
          const char* __restrict__ x, const char* __restrict__ ea, const __nv_bfloat16* __restrict__ eps, char* __restrict__ out,
          const __grid_constant__ CUtensorMap m_wr, const __grid_constant__ CUtensorMap m_w0, const __grid_constant__ CUtensorMap m_w1) {
    extern __shared__ __align__(1024) char smem_raw[];
    constexpr uint32_t sm = 1024;
    spin_check((uint32_t)__cvta_generic_to_shared(smem_raw) == sm ? 0 : 2 * SPIN_LIMIT);
    int t;
    asm volatile("mov.u32 %0, %%tid.x;" : "=r"(t));
    const int w = t >> 5, lane = t & 31, b = blockIdx.x;

    const int g = lane >> 2, q = lane & 3, mat = lane >> 3, r = lane & 7;
    const int e0 = b * CH + t * 8, ne = min(CH, NE - b * CH);
    const bool act = t * 8 < ne;
    uint32_t d[8];
#pragma unroll
    for (int k = 0; k < 2; k++) ldg128(d + 4 * k, dst + e0 / 4 + k, act);
    uint32_t tag = ld_rlx(&gs->epoch[b * 32]), epl;
    asm volatile("ld.global.nc.u16 %0, [%1];" : "=r"(epl) : "l"(eps + min(lane, 26)));
    if (t < 60) sts128(sm + O_BCNT + 16 * t, make_uint4(0, 0, 0, 0));
    if (t == NT - 1) {
#pragma unroll
        for (int i = 0; i < 4; i++) mbar_init(sm + O_WBA + 8 * i, 1);
        fence_async();
        mbar_expect(sm + O_WBC, ne * 10); mbar_expect(sm + O_WBA, 20480); mbar_expect(sm + O_WBB, 98304); mbar_expect(sm + O_WBD, 65536);
        spin_check(tag);
        bulk(sm + O_RH, rhat + b * (CH * 6), ne * 6, sm + O_WBC);
        bulk(sm + O_SRC, src + b * (CH / 4), ne * 4, sm + O_WBC);
        tma3d(sm + O_WR0, &m_wr, 0, sm + O_WBA);
        tma3d(sm + O_WR1, &m_wr, 5, sm + O_WBA);
        tma3d(sm + O_W0S, &m_w0, 0, sm + O_WBD);
    }
    if (t == 320) {
#pragma unroll
        for (int i = 0; i < NSLOT; i++) {
            sts128(sm + O_RING + i * SLOT + S_C + 64, make_uint4(0, 0, 0, 0));
            mbar_init(sm + O_RING + i * SLOT + S_FULL, 32); mbar_init(sm + O_RING + i * SLOT + S_EMPTY, 8);
        }
    }
#pragma unroll
    for (int k = 0; k < LZ; k++) sts128(sm + O_L + 16 * (t + k * NT), make_uint4(0, 0, 0, 0));
    if (t < 80) sts32(sm + O_NCNT + 4 * t, t <= NLOC ? 4 * t : 0);
    if (t < 100) sts32(sm + O_NODE + 4 * t, 0);
    uint32_t ba[8], rk[8];
    auto pfx = [&](int r0, int n) {
        if (n) pf_l2(x + (b * NLOC + r0) * 1024, min(n, NN - b * NLOC - r0) * 1024);
    };
    if (w < 10) bar_sync(1, 320);
    tag = (tag + 1) << 30;
    if (act) {
#pragma unroll
        for (int i = 0; i < 8; i++) {
            const uint32_t l = __umulhi(d[i], (uint32_t)((1ull << 32) / G + 1));
            ba[i] = d[i] * 4 - l * (4 * G);
            d[i] = l * 4 + (tag + ((e0 + i + 1) << 9) + 4);
            rk[i] = atoms_add(sm + O_BCNT + ba[i], 4);
        }
#pragma unroll
        for (int i = 0; i < 8; i++)
            asm volatile("{.reg .pred p; setp.lt.u32 p, %2, 124; @p st.shared.u32 [%0], %1;}"
                         ::"r"(sm + O_KT + ba[i] * 32 + ((ba[i] + rk[i]) & 127)), "r"(d[i]), "r"(rk[i]) : "memory");
    }
    TS(0);
    __syncthreads();
    {
        int v[5], sum = 0;
#pragma unroll
        for (int i = 0; i < 5; i++) { v[i] = lds32(sm + O_BCNT + 4 * (lane * 5 + i)); sum += v[i]; }
        int e = warp_incl(sum) - sum;
        if (w == 10) {
#pragma unroll
            for (int i = 0; i < 5; i++) {
                const int k = lane * 5 + i;
                if (k < G) sts32(sm + O_KT + k * 128 + ((k * 4 + 124) & 127), tag | v[i] << 10 | e >> 2);
                e += v[i];
            }
            __syncwarp();
            if (lane == 0) {
                fence_async();
                bulk_st(&gs->keys[b * (G * 32)], sm + O_KT, G * 128);
                pfx(0, PFA);
            }
        } else {
#pragma unroll
            for (int i = 0; i < 5; i++) { sts32(sm + O_BOFF + 4 * (lane * 5 + i), e); e += v[i]; }
        }
        __syncwarp();
    }
    TS(11);
    const uint32_t sw = (uint32_t)(((2 * (w & 3) + (mat & 1)) ^ r) * 16 + ((mat >> 1) * 8 + r) * 128);
    uint32_t wr[5][4];
    const uint32_t* kp = &gs->keys[(w * SEGW * G + b) * 32 + ((lane + b) & 31)];
    uint32_t kv[SEGW + 1], ho[SEGW + 1], nk[SEGW + 1], old;
    if (act) {
        uint32_t mx = 0;
#pragma unroll
        for (int i = 0; i < 8; i++) { mx = max(mx, rk[i]); ba[i] = rk[i] + lds32(sm + O_BOFF + ba[i]); }
        if (mx >= 124) {
#pragma unroll
            for (int i = 0; i < 8; i++)
                if (rk[i] >= 124) st_rlx(&gs->more[b * CH + (ba[i] >> 2)], d[i]);
        }
    }
    if (w < 8) {
        mbar_wait(sm + O_WBA, 0);
#pragma unroll
        for (int p = 0; p < 5; p++) {
            const int c = 2 * p + (w >> 2);
            ldsm4t(wr[p], sm + (c < 5 ? O_WR0 : O_WR1 - 5 * 2048) + c * 2048 + sw);
        }
    } else {
        const uint64_t xl = (uint64_t)(x - 1024 + r * 16) - (tag >> 6), al = (uint64_t)(ea - 32 + (lane & 1) * 16) - (tag >> 4);
        const uint64_t ml = (uint64_t)(gs->list + (mat < 2 ? mat * (NTILE * 8) + 4 + r : r < 2 ? r * (NTILE * 8) : r < 4 ? r - 1 : NTILE * 8 + r - 3));
        const uint32_t c[16] = {(uint32_t)xl, (uint32_t)(xl >> 32), (uint32_t)al, (uint32_t)(al >> 32), (uint32_t)ml, (uint32_t)(ml >> 32),
            mat * 4096u + ((r ^ (4 * (mat & 1))) * 16), S_A + (lane >> 1) * 32u + (((lane ^ mat) & 1) * 16),
            mat < 2 ? (r < 4 ? S_C + mat * 80 + r * 16u : 0u) : (mat == 2 && r < 6) ? S_H + r * 16u : 0u,
            S_H + mat * 8u, S_H + 32 + g * 8u, (lane & 2) ? 0x7632u : 0x5410u,
            g == 7 ? S_H + q * 4u : g < 2 ? S_H + 32 + q * 8u + g * 4 : g == 2 ? S_C + 48 + q * 4u : S_C - 64 + lane * 4u,
            g == 7 ? 16u : g < 2 ? 32u : 80u,
            sm + O_L + (mat >> 1) * LH + (w & 3) * 128 + (mat & 1) * 64 + 12, sm + O_L + (mat >> 1) * LH + (w & 3) * 128 + (lane & 14) * 8};
#pragma unroll
        for (int i = 0; i < 20; i++) wr[i >> 2][i & 3] = i < 16 ? opaque(c[i & 15], lane) : 0;
    }
    TS(21);
    mbar_wait(sm + O_WBC, 0);
    TS(22);
    if (act) {
        uint32_t s[8], y[12];
#pragma unroll
        for (int k = 0; k < 3; k++) *(uint4*)&y[4 * k] = lds128(sm + O_RH + t * 48 + k * 16);
#pragma unroll
        for (int k = 0; k < 2; k++) *(uint4*)&s[4 * k] = lds128(sm + O_SRC + t * 32 + k * 16);
#pragma unroll
        for (int i = 0; i < 8; i++) {
            const int k = 3 * i / 2;
            sts64(sm + O_OUT + ba[i] * 2, i & 1 ? __byte_perm(y[k], y[k + 1], 0x5432) : y[k],
                  __byte_perm(y[k + 1], s[i] + (tag >> 16) + 1, i & 1 ? 0x5432 : 0x5410));
        }
    }
    TS(12);
    if (w < 10) asm volatile("bar.arrive 4, 352;" ::: "memory");
    if (w == 11) {
        bar_sync(4, 352);
        if (lane == 0) { fence_async(); bulk_st(&gs->vals[b * CH], sm + O_OUT, ne * 8); pfx(PFA, PFB); }
        __syncwarp();
    }

    const uint32_t am = lane < 31 ? 511 : 0, none = tag | (320 + 4 * lane);
    auto check = [&]() {
        old = 0;
#pragma unroll
        for (int j = 0; j < SEGW; j++) {
            ho[j] = __shfl_sync(0xffffffffu, kv[j], 31);
            kv[j] = ho[j] >= (lane < 31 ? tag + ((lane + 1) << 12) : 0u) ? kv[j] : none;
            old |= kv[j] ^ tag;
        }
        return __any_sync(0xffffffffu, old >> 30);
    };
#pragma unroll
    for (int j = 0; j < SEGW; j++) kv[j] = ld_rlx(kp + j * (G * 32));
    TS(1);
    TV(19, 0);
    for (int it = 0; check(); it++) {
        spin_check(it);
        if (it == 0) TS(20);
        TV(19, (it + 1) * 100);
#pragma unroll
        for (int j = 0; j < SEGW; j++)
            if (__any_sync(0xffffffffu, (kv[j] ^ tag) >> 30)) kv[j] = ld_rlx(kp + j * (G * 32));
    }
    TS(3);
    kv[SEGW] = none; ho[SEGW] = 0;
    bool slow = false;
    const bool more = __any_sync(0xffffffffu, lane == 31 && (old & 0xfe0000));
    if (more) {
        int c = lane;
#pragma unroll
        for (int j = 0; j < SEGW; j++) {
            const int n = max((int)(ho[j] >> 12 & 0xfff) - 31, 0);
            if ((unsigned)c < (unsigned)n) ho[SEGW] = j * CH + (ho[j] & 0xfff) + 31 + c - lane;
            c -= n;
        }
        slow = lane == 31 && c < 0;
        if (c < 0 && lane < 31)
            for (int it = 0; ((kv[SEGW] = ld_rlx(&gs->more[w * SEGW * CH + lane + ho[SEGW]])) ^ tag) >> 30; it++) spin_check(it);
        __syncwarp();
    }
    uint32_t na_[SEGW + 1];
#pragma unroll
    for (int j = 0; j <= SEGW; j++) {
        na_[j] = (kv[j] & am) | (none & 511 & ~am);
        nk[j] = atoms_add(sm + O_NCNT + na_[j], 512);
    }
    auto visit = [&](auto f) {
#pragma unroll 1
        for (int j = 0; j < SEGW; j++) {
            const uint32_t* kl = &gs->keys[((w * SEGW + j) * G + b) * 32];
            const uint32_t h = ld_rlx(kl + ((31 + b) & 31));
#pragma unroll 1
            for (int i = lane; i < (h >> 12 & 0xfff); i += 32) {
                const int o = (w * SEGW + j) * CH + (h & 0xfff) + i;
                uint32_t k;
                int it = 0;
                do { k = ld_rlx(i < 31 ? kl + ((i + b) & 31) : &gs->more[o]); spin_check(it++); } while ((k ^ tag) >> 30);
                f(k, o, i);
            }
        }
    };
    slow = __syncthreads_or(slow);
    if (slow) {
        if (t < 80) sts32(sm + O_NCNT + 4 * t, t <= NLOC ? 4 * t : 0);
        __syncthreads();
        visit([&](uint32_t k, int, int) { atoms_add(sm + O_NCNT + (k & 511), 512); });
        __syncthreads();
    }
    TS(4);
    if (t == 352) pfx(PFA + PFB, PFC);
    if (w < 10) {
        const uint32_t key = lds32(sm + O_NCNT + 4 + (t & ~3));
        uint4 k[5];
#pragma unroll
        for (int i = 0; i < 5; i++) k[i] = lds128(sm + O_NCNT + q * 80 + i * 16);
        uint32_t c[4] = {0, 0, 0, 0};
#pragma unroll
        for (int i = 0; i < 5; i++) { c[0] += (key - k[i].x) >> 31; c[1] += (key - k[i].y) >> 31; c[2] += (key - k[i].z) >> 31; c[3] += (key - k[i].w) >> 31; }
        int rank = c[0] + c[1] + c[2] + c[3];
        rank += __shfl_xor_sync(0xffffffffu, rank, 1);
        rank += __shfl_xor_sync(0xffffffffu, rank, 2);
        if (t < NLOC * 4) sts32(sm + O_SORT + 4 * rank, key);
    }
    __syncthreads();
    TS(2);
    const bool on = lane < NLOC / 4;
    const uint4 k4 = lds128(sm + O_SORT + 16 * (on ? lane : 0));
    const uint32_t ks[4] = {k4.x, k4.y, k4.z, k4.w};
    const int n0 = on ? max(1u, (ks[0] + 3584) >> 12) : 0, n1 = on ? max(1u, (ks[2] + 3584) >> 12) : 0;
    const int u2 = warp_incl(n0 + n1), u1 = u2 - n1, u0 = u1 - n0;
    const int total = __shfl_sync(0xffffffffu, u2, 31);
    slow |= total > CAPT;
    int gbase = b * CAPT + 1;
    if (on) {
#pragma unroll
        for (int i = 0; i < 4; i++)
            sts32(sm + O_NOFF + (ks[i] & 511), (i >> 1 ? u1 : u0) * 128 + (i & 1 ? (slow ? 1 << 30 : LH) : 0) - ((ks[i] & 511) >> 5));
    }
    __syncwarp();
    auto mark = [&](int i) { const int node = (ks[i] & 511) * (G / 4) - G + b; return node < NN ? node + 1 : 0; };
    if (!slow) {
        const uint64_t vp = (uint64_t)&gs->vals[w * SEGW * CH + lane];
        uint64_t vv[SEGW + 1], va[SEGW + 1];
#pragma unroll
        for (int j = 0; j <= SEGW; j++) {
            nk[j] = lds32(sm + O_NOFF + na_[j]) + (nk[j] >> 5);
            va[j] = madw(j < SEGW ? ho[j] & 0xfff : ho[j], 8, vp) + (j < SEGW ? j * CH * 8 : 0);
            vv[j] = (uint64_t)tag << 32;
        }
        if (t == 352) asm volatile("cp.async.bulk.wait_group.read 0;" ::: "memory");
        __syncthreads();
        TS(13);
        if (t == 352) pfx(PFA + PFB + PFC, PFD);
        for (int it = 0;; it++) {
#pragma unroll
            for (int j = 0; j <= SEGW; j++)
                asm volatile("{.reg .pred p; setp.lt.u32 p, %2, 320; @p ld.relaxed.gpu.global.b64 %0, [%1];}" : "+l"(vv[j]) : "l"(va[j]), "r"(na_[j]) : "memory");
            old = 0;
#pragma unroll
            for (int j = 0; j <= SEGW; j++) old |= (uint32_t)(vv[j] >> 32) ^ tag;
            if (!__any_sync(0xffffffffu, old >> 30)) break;
            spin_check(it);
        }
#pragma unroll
        for (int j = 0; j <= SEGW; j++)
            asm volatile("{.reg .pred p; setp.ne.u32 p, %4, %5; @p st.shared.v4.u32 [%0], {%1,%2,%3,%4};}"
                         ::"r"(sm + O_L + nk[j]), "r"(kv[j]), "r"(0), "r"((uint32_t)vv[j]), "r"((uint32_t)(vv[j] >> 32)), "r"(tag) : "memory");
        if (na_[SEGW] < 320) gs->more[w * SEGW * CH + lane + ho[SEGW]] = 0;
    } else {
        int so = 0;
#pragma unroll
        for (int j = 0; j < SEGW; j++) so += ho[j] & 0xfff;
        if (lane == 0) atoms_add(sm + O_SUM, so);
        if (t == 352) asm volatile("cp.async.bulk.wait_group.read 0;" ::: "memory");
        __syncthreads();
        gbase = TBIG + (lds32(sm + O_SUM) >> 3) + (NLOC + 5) * b;
        auto put = [&](uint32_t k, uint64_t e, uint32_t a, int rank) {
            const uint32_t v = lds32(sm + O_NOFF + a) + (a >> 5) + rank * 16;
            unsigned short* p = (unsigned short*)(gs->list + (gbase + (v >> 7 & 0x7fffff) + (v >> 30) * NTILE) * 8);
            const int c = v >> 4 & 7, c2 = 8 + (c >> 1) * 4 + (c & 1);
            p[c] = e >> 48; p[c2] = k; p[c2 + 2] = k >> 16;
            p[32 + c] = e; p[40 + c] = e >> 16; p[48 + c] = e >> 32; p[56 + c] = 0;
        };
        visit([&](uint32_t k, int o, int i) {
            uint64_t e;
            int it = 0;
            do {
                asm volatile("ld.relaxed.gpu.global.b64 %0, [%1];" : "=l"(e) : "l"(&gs->vals[o]) : "memory");
                spin_check(it++);
            } while (((uint32_t)(e >> 32) ^ tag) >> 30);
            if (i >= 31) gs->more[o] = 0;
            put(k, e, k & 511, atoms_add(sm + O_NCUR + (k & 511), 1));
        });
#pragma unroll 1
        for (int i = 0; i < 4; i++) {
            const uint32_t k = i == 0 ? ks[0] : i == 1 ? ks[1] : i == 2 ? ks[2] : ks[3];
#pragma unroll 1
            for (int p = (k >> 9) + w; p < (i >> 1 ? n1 : n0) * 8; p += NT / 32) put(0, 0, k & 511, p);
        }
        __syncthreads();
        if (w == 0 && on) {
#pragma unroll
            for (int i = 0; i < 4; i++)
                *(uint32_t*)(gs->list + (gbase + (i >> 1 ? u1 : u0) + (i & 1) * NTILE) * 8 + 7) = mark(i) | (i & 1 ? 0 : i ? n1 : n0) << 16;
        }
        __threadfence();
    }
    int pos = gbase, end = gbase + __shfl_sync(0xffffffffu, NPRIV & 1 ? u1 : u2, (NPRIV - 1) / 2);
    __syncthreads();
    TS(5);

    if (w >= 8) {
        asm volatile("setmaxnreg.dec.sync.aligned.u32 " STR(PREG) ";");
        const int h = __reduce_max_sync(0xffffffffu, w & 3);
        const uint32_t ring = sm + O_RING;
        const uint64_t xl = wr[0][0] | (uint64_t)wr[0][1] << 32, al = wr[0][2] | (uint64_t)wr[0][3] << 32, ml = wr[1][0] | (uint64_t)wr[1][1] << 32;
        const uint32_t xoff = wr[1][2], aoff = wr[1][3], moff = wr[2][0], hoff = wr[2][1], hoff2 = wr[2][2], psel = wr[2][3], pa = wr[3][0], ps = wr[3][1];
        uint32_t v0[3][5];
        if (!slow) {
#pragma unroll
            for (int k = 0; k < 3; k++) {
                v0[k][0] = lds32(wr[3][3] + k * 512);
#pragma unroll
                for (int j = 0; j < 2; j++) v0[k][1 + j] = __byte_perm(lds32(wr[3][2] + k * 512 + j * 32), lds32(wr[3][2] + k * 512 + j * 32 + 16), 0x7632);
            }
        } else {
            for (int i = h; i < NSLOT; i += 4)
                if (moff >= S_H) cpa16z(ring + i * SLOT + moff, (const char*)madw(pos + i, 128, ml), 1);
            asm volatile("cp.async.wait_all;" ::: "memory");
        }
        int cur = __reduce_max_sync(0xffffffffu, pos) + h;
        pos = cur + NSLOT; end = __reduce_max_sync(0xffffffffu, end);

        int ev = h ? end : end - 12, state = h ? 2 : 0, tk = 0, nr = 0, prv = pos - 1;
        uint32_t inf = 0;
        int ii = 0;
        auto take = [&]() {
            int v = 0;
            asm volatile("{.reg .pred p; setp.eq.s32 p, %2, 0; @p atom.relaxed.gpu.global.add.u32 %0, [%1], 1;}" : "+r"(v) : "l"(&gs->ticket), "r"(lane) : "memory");
            return v;
        };
        auto resolve = [&]() {
            const int k = __reduce_max_sync(0xffffffffu, tk);
            inf = tag;
            if (k < G * NPOOL) { const int l = k / G; ii = (k - l * G) * NPOOL + l; inf = ld_rlx(&gs->info[ii]); tk = take(); }
        };
        uint32_t so = ring + h * SLOT, ph = 1;
        auto fill = [&](auto first, int k) {
            constexpr bool F = decltype(first)::value;
            const uint32_t mi = max(moff >= S_H ? pos : cur, 0);
            const char* gm = (const char*)madw(mi, 128, ml);
            const uint32_t d0 = so + xoff;
            mbar_wait(so + S_EMPTY, ph);
            if (!F && cur <= 0) return false;
            uint2 e = make_uint2(v0[0][1], v0[0][2]);
            uint32_t id = v0[0][0] >> 9;
            if (!F) { e = lds64(so + hoff); const uint2 e2 = lds64(so + hoff2); id = __byte_perm(e2.x, e2.y, psel) >> 9; }
            const uint32_t s[4] = {e.x & 0xffffu, e.x >> 16, e.y & 0xffffu, e.y >> 16};
            cpa16z(so + aoff, (const char*)madw(id, 32, al), id);
            if (!F && moff) cpa16z(so + moff, gm, mi);
#pragma unroll
            for (int j = 0; j < 4; j++) {
                const char* gx = (const char*)madw(s[j], 1024, xl);
#pragma unroll
                for (int k = 0; k < 8; k++) cpa16z((d0 ^ (j * 16)) + j * 1024 + k * 128, gx + k * 128, NULLP(s[j]));
            }
            if (F) {
                if (k == 0) {
                    if (on) {
#pragma unroll
                        for (int i = 0; i < 4; i++) sts32(sm + O_L + 4 + (i >> 1 ? u1 : u0) * 128 + (i & 1) * LH, mark(i));
                        sts32(sm + O_L + 20 + u0 * 128, n0); sts32(sm + O_L + 20 + u1 * 128, n1);
                    }
                    __syncwarp();
#pragma unroll
                    for (int i = 0; i < 3; i++) {
                        uint32_t v[4];
                        ldsm4t(v, sm + O_L + (mat & 1) * LH + (h + 4 * i + (mat >> 1) * NSLOT) * 128 + r * 16);
                        v0[i][3] = ps == 80 ? v[0] : v[2]; v0[i][4] = ps == 80 ? v[1] : v[3];
                    }
                }
                if (g != 3) { sts32(so + pa, v0[0][3]); sts32(so + pa + ps, v0[0][4]); }
            }
            asm volatile("cp.async.mbarrier.arrive.noinc.shared::cta.b64 [%0];" ::"r"(so + S_FULL) : "memory");
            if (so == ring) so += 4 * SLOT; else { so -= SLOT; ph ^= 1; }
            cur = prv;
            pos += 4; prv = pos - 1;
            return true;
        };
#pragma unroll 1
        for (int k = 0; k < 3; k++) {
            if (k == 0 && h == 0) TSW(23);
            if (!slow) fill(Bool<true>(), k);
            if (k == 0 && h == 0) TSW(24);
            if (k == 0 && h == 3) TSW(25);
            if (k == 0) {
                asm volatile("bar.arrive 7, %0;" ::"n"(NT) : "memory");
                if (h == 3) {
                    bar_sync(5, 288);
                    if (lane == 0) {
                        fence_async();
                        if (!slow) {
                            bulk_st(gs->list + gbase * 8, sm + O_L, total * 128);
                            bulk_st(gs->list + (gbase + NTILE) * 8, sm + O_L + LH, total * 128);
                        }
                        asm volatile("cp.async.bulk.wait_group.read 0;" ::: "memory");
                        for (int j = 0; j < 4; j++) tma2d(sm + O_W1 + j * 24576, &m_w1, 64 * (j >> 1), 192 * (j & 1), sm + O_WBB);
                    }
                    __syncwarp();
                }
            }
#pragma unroll
            for (int i = 0; i < 5; i++) { v0[0][i] = v0[1][i]; v0[1][i] = v0[2][i]; }
        }
        if (h == 3) {
            if (lane == 0) asm volatile("cp.async.bulk.wait_group 0;\nfence.proxy.async;" ::: "memory");
            __syncwarp();
            if (on && 2 * lane >= NPRIV) st_rlx(&gs->info[b * NPOOL + 2 * lane - NPRIV], tag | (gbase + u0) << 12 | n0);
            if (on && 2 * lane + 1 >= NPRIV) st_rlx(&gs->info[b * NPOOL + 2 * lane + 1 - NPRIV], tag | (gbase + u1) << 12 | n1);
        }
        bar_sync(6, 128);
        while (fill(Bool<false>(), 0)) {
            if (pos >= ev) {
                if (state == 0) { ev = end - 6; state = 1; tk = take(); }
                else if (state == 1) { resolve(); ev = end; state = 2; }
                else {
                    do {
                        const uint32_t mb = sm + O_MB + (nr & 31) * 8;
                        uint32_t rg;
                        nr++;
                        if (h == 0) {
                            for (int it = 0; (rg = __reduce_max_sync(0xffffffffu, inf ^ tag)) >> 30; it++) { spin_check(it); inf = ld_rlx(&gs->info[ii]); }
                            asm volatile("st.release.cta.shared.b64 [%0], %1;" ::"r"(mb), "l"(rg | (uint64_t)nr << 32) : "memory");
                            if (rg) resolve();
                        } else {
                            uint64_t m;
                            for (int it = 0;; it++) {
                                asm volatile("ld.acquire.cta.shared.b64 %0, [%1];" : "=l"(m) : "r"(mb) : "memory");
                                if (__all_sync(0xffffffffu, (int)(m >> 32) == nr)) break;
                                spin_check(it);
                            }
                            rg = __reduce_max_sync(0xffffffffu, (uint32_t)m);
                        }
                        const int ov = pos - end;
                        pos = rg ? (int)(rg >> 12) + ov : -(1 << 30);
                        if (ov) prv = pos - 1;
                        end = (rg >> 12) + (rg & 0xfff);
                    } while (pos >= end);
                    ev = end;
                }
            }
        }
        TSW(8 + (h & 1));
        if (lane == 0) sts32(so + S_C + 48, 0);
        mbar_arrive(so + S_FULL);
        if (t == 256) {
            gs->epoch[b * 32] = (tag >> 30) % 3;
            if (atomicInc(&gs->done, G - 1) == G - 1) gs->ticket = 0;
        }
        asm volatile("cp.async.wait_all;" ::: "memory");
    } else {
        asm volatile("setmaxnreg.inc.sync.aligned.u32 " STR(CREG) ";");
        const uint32_t xa = opaque(((mat >> 1) * 8 + r) * 1024 + (w >> 2) * 128 + (((2 * (w & 3) + (mat & 1)) ^ r) * 16), lane);
        const uint32_t aa = opaque(S_A + ((mat >> 1) * 8 + r) * 32 + (((mat & 1) ^ (r >> 2)) * 16), lane);
        const uint32_t ya = opaque(S_C + (mat & 1) * 80 + (mat >> 1) * 16, lane);
        const uint32_t yc = opaque(S_C + (mat < 2 ? mat * 80 + 32 : (r >> 2) == (mat & 1) && q < 3 ? (mat & 1) * 80 + q * 16 : 64), lane);
        const uint32_t ma = opaque(S_C + 48 + (lane >> 4) * 80, lane), na = opaque(sm + O_NODE + (lane >> 4) * 4, lane);
        const uint32_t pw = sm + O_P + w * PW;
        const uint32_t fx = opaque((q < 3 ? pw + P_1P0 + 2 * q * PSBO + (mat & 1) * 128 : sm + O_TRASH + ((pw - sm - O_TRASH + 96) & 127)) + (r >> 2) * PSBO, lane);
        const uint32_t fyz = opaque(pw + (q < 3 ? (mat < 2 ? P_1P1 : P_1P2) + 2 * q * PSBO : mat < 2 ? P_0P0 : P_0P1) + (mat & 1) * 128 + (r >> 2) * PSBO, lane);
        uint32_t oh[4][2];
#pragma unroll
        for (int c = 0; c < 8; c++) oh[c & 3][c >> 2] = opaque(g == c ? 0x3F803F80u : 0u, lane);
        uint32_t eb[3];
#pragma unroll
        for (int k = 0; k < 3; k++) {
            const int i = (g & 3) * 9 + (q & 1) * 6 + k;
            const uint32_t lo = __shfl_sync(0xffffffffu, epl, i), hi = __shfl_sync(0xffffffffu, epl, i + 3);
            eb[k] = (g & 3) < 3 && (q >> 1) == (g >> 2) ? (q & 1 ? lo : lo | hi << 16) : 0u;
        }
        asm volatile(".reg .pred lane0;\nsetp.eq.u32 lane0, %0, 0;" ::"r"(lane));
        uint32_t w0[16][4];
        mbar_wait(sm + O_WBD, 0);
#pragma unroll
        for (int k = 0; k < 16; k++) ldsm4t(w0[k], sm + O_W0S + (w >> 2) * 32768 + k * 2048 + sw);
        bar_sync(7, NT);
        if (!slow) {
            uint32_t la = sm + O_L + (w & 1) * LH + (w >> 1) * 512;
            const uint32_t lo = (g < 2 ? 4 + q * 2 + g : g == 2 ? 28 + q : g == 7 ? q : lane) * 4;
#pragma unroll 1
            for (int c = total - 4 * (w >> 1); c > 0; c -= 48, la += 6144) {
                uint32_t v[3][4];
#pragma unroll
                for (int k = 0; k < 3; k++) ldsm4t(v[k], la + k * 2048 + lane * 16);
#pragma unroll
                for (int k = 0; k < 12; k++) sts32(la + lo + (k >> 2) * 2048 + (k & 3) * 128, v[k >> 2][k & 3]);
            }
        }
        asm volatile("bar.arrive 5, 288;" ::: "memory");
        TS(6);
        Acc A;
#pragma unroll
        for (int i = 0; i < 4; i++) { A.p00[i] = A.p110[i] = A.p10[0][i] = A.p10[1][i] = A.p10[2][i] = 0; A.t01[i] = A.m[0][i] = A.m[1][i] = A.m[2][i] = 0.f; }
        int slot = STAG * 16 - 16, rem;
        uint32_t so = sm + O_RING, ph = opaque(0, lane), a[4], ok, mt = 0;
        const uint32_t wg = __reduce_max_sync(0xffffffffu, w >> 2);
        mbar_wait(so + S_FULL, 0);
        ldsm4(a, so + aa);
        TS(7);
        while (true) {
            {
                constexpr int F = 1, XS = XS_F;
                uint32_t yb[8], f[4][4], R[5][4], u[4][4], sd[4];
                float y[4], z[4];
                const uint32_t sof = slot & 112;
                SEQ_F
                slot += 16;
            }
            if (!(ok && rem > 0 && slot != 128)) {
                if (slot == 128 || rem < 0) {
                    asm volatile("fence.proxy.async.shared::cta;" ::: "memory");
                    mbar_wait(sm + O_WBB, 0);
                    bar_sync(1, 256);
                    float d0[8], d1[24];
                    const uint64_t db = (uint64_t)((sm + O_P) >> 4) | (8ull << 16) | ((uint64_t)(PSBO / 16) << 32);
                    const uint32_t da = ((sm + O_W1) >> 4 | 1 << 16) + wg * 3072;
                    asm volatile("wgmma.fence.sync.aligned;" ::: "memory");
#pragma unroll
                    for (int k = 0; k < 16; k++) wg_rs16(d0, w0[k], db + (((k & 7) * PW + ((k >> 3) ? P_0P1 : P_0P0)) >> 4), k);
                    asm volatile("wgmma.commit_group.sync.aligned;" ::: "memory");
#pragma unroll
                    for (int k = 0; k < 24; k++)
                        wg_ss48(d1, (da + k * 128) | (64ull << 32) | (1ull << 62), db + (((k & 7) * PW + ((k >> 3) == 0 ? P_1P0 : (k >> 3) == 1 ? P_1P1 : P_1P2)) >> 4), k);
                    asm volatile("wgmma.commit_group.sync.aligned;" ::: "memory");
                    const uint2 n0 = lds64(sm + O_NODE + mat * 16), n1 = lds64(sm + O_NODE + 64 + mat * 16);
                    const uint32_t nd[4] = {mat * 16 < slot ? n0.x & 0xffff : 0, mat * 16 + 64 < slot ? n1.x & 0xffff : 0, mat * 16 < slot ? n0.y : 0, mat * 16 + 64 < slot ? n1.y : 0};
                    const uint64_t op = (uint64_t)(out - 1024 + (w & 3) * 256 + (w >> 2) * 128 + r * 16);
                    uint64_t oa[4];
#pragma unroll
                    for (int it = 0; it < 4; it++) oa[it] = madw(nd[it], 1024, op);
                    uint32_t sg = sm + O_P + (w & 4) * PW + ((mat >> 1) * 8 + r) * 128 + (((2 * (w & 3) + (mat & 1)) ^ r) * 16);
                    uint32_t sl = pw + mat * 128 + (r ^ mat) * 16, sl2 = pw + 512 + mat * 128 + (r ^ mat ^ 4) * 16;
                    asm volatile("wgmma.wait_group.sync.aligned 1;" ::: "memory");
#pragma unroll
                    for (int i = 0; i < 8; i++) asm volatile("" : "+f"(d0[i])::"memory");
                    uint32_t o[4][4], chk = sg & sl & sl2;
                    float gt[8];
#pragma unroll
                    for (int i = 0; i < 8; i++) {
                        asm("ex2.approx.ftz.f32 %0, %1;" : "=f"(gt[i]) : "f"(d0[i] * -1.4426950408889634f));
                        asm("rcp.approx.ftz.f32 %0, %1;" : "=f"(gt[i]) : "f"(gt[i] + 1.f));
                        chk &= __float_as_uint(gt[i]);
                    }
#pragma unroll
                    for (int i = 0; i < 4; i++) { o[0][i] = pack(d0[2 * i], d0[2 * i + 1]); chk &= o[0][i] & (uint32_t)(oa[i] >> 32); }
                    sts32(sm + O_TRASH, chk);
                    asm volatile("wgmma.wait_group.sync.aligned 0;" ::: "memory");
#pragma unroll
                    for (int i = 0; i < 24; i++) asm volatile("" : "+f"(d1[i])::"memory");
                    bar_sync(1, 256);
#pragma unroll
                    for (int i = 0; i < 4; i++)
#pragma unroll
                        for (int j = 0; j < 3; j++) o[1 + j][i] = pack(d1[8 * j + 2 * i] * gt[2 * i], d1[8 * j + 2 * i + 1] * gt[2 * i + 1]);
#pragma unroll
                    for (int j = 0; j < 4; j++) stsm4t(sg + j * PW, o[j][0], o[j][1], o[j][2], o[j][3]);
                    bar_sync(2 + wg, 128);
                    uint4 v[4];
#pragma unroll
                    for (int it = 0; it < 4; it++) v[it] = lds128((it & 1 ? sl2 : sl) + (it >> 1) * 1024);
#pragma unroll
                    for (int it = 0; it < 4; it++)
                        asm volatile("{.reg .pred p; setp.ne.u32 p, %5, 0; @p st.global.v4.u32 [%0], {%1,%2,%3,%4};}"
                                     ::"l"(oa[it]), "r"(v[it].x), "r"(v[it].y), "r"(v[it].z), "r"(v[it].w), "r"(nd[it]) : "memory");
                    __syncwarp();
                    slot = 0;
                    if (rem < 0) break;
                }
                if (!ok) { mbar_wait(so + S_FULL, ph >> 31); ldsm4(a, so + aa); }
                if (rem == 0) continue;
            }
            while (true) {
                do {
                    constexpr int F = 0, XS = XS_R;
                    uint32_t yb[8], f[4][4], R[5][4], u[4][4], sd[4];
                    SEQ_R
                    rem--;
                } while (ok && rem > 0);
                if (ok) break;
                mbar_wait(so + S_FULL, ph >> 31); ldsm4(a, so + aa);
                if (rem == 0) break;
            }
        }
        TS(10);
    }
}

typedef CUresult (*EncFn)(CUtensorMap*, CUtensorMapDataType, cuuint32_t, void*, const cuuint64_t*, const cuuint64_t*,
                          const cuuint32_t*, const cuuint32_t*, CUtensorMapInterleave, CUtensorMapSwizzle,
                          CUtensorMapL2promotion, CUtensorMapFloatOOBfill);

void make_map(EncFn fn, CUtensorMap* m, void* p, int rows, int cols, int brows, int rank, int bblk, CUtensorMapSwizzle swz) {
    cuuint64_t dims[3] = {(cuuint64_t)(rank == 3 ? 64 : cols), (cuuint64_t)rows, (cuuint64_t)cols / 64}, strides[2] = {(cuuint64_t)cols * 2, 128};
    cuuint32_t box[3] = {64, (cuuint32_t)brows, (cuuint32_t)bblk}, es[3] = {1, 1, 1};
    fn(m, CU_TENSOR_MAP_DATA_TYPE_BFLOAT16, rank, p, dims, strides, box, es, CU_TENSOR_MAP_INTERLEAVE_NONE,
       swz, CU_TENSOR_MAP_L2_PROMOTION_NONE, CU_TENSOR_MAP_FLOAT_OOB_FILL_NONE);
}

}

extern "C" void kernel_launch(void* const* d_in, const int* in_sizes, int n_in, void* d_out, int out_size) {
    static EncFn enc = nullptr;
    static void* scratch = nullptr;
    if (!enc) {
        void* fn = nullptr;
        cudaDriverEntryPointQueryResult qr;
        cudaGetDriverEntryPoint("cuTensorMapEncodeTiled", &fn, cudaEnableDefault, &qr);
        enc = (EncFn)fn;
        cudaGetSymbolAddress(&scratch, g_scratch);
        cudaFuncSetAttribute(tp_kernel, cudaFuncAttributeMaxDynamicSharedMemorySize, SMEM_BYTES);
    }
    CUtensorMap m_wr, m_w0, m_w1;
    make_map(enc, &m_wr, d_in[5], 16, 640, 16, 3, 5, CU_TENSOR_MAP_SWIZZLE_128B);
    make_map(enc, &m_w0, d_in[6], 256, 128, 256, 3, 2, CU_TENSOR_MAP_SWIZZLE_128B);
    make_map(enc, &m_w1, d_in[7], 384, 128, 192, 2, 1, CU_TENSOR_MAP_SWIZZLE_128B);
    tp_kernel<<<G, NT, SMEM_BYTES>>>((const int4*)d_in[4], (const int4*)d_in[3], (const char*)d_in[1], (Scratch*)scratch,
                                     (const char*)d_in[0], (const char*)d_in[2], (const __nv_bfloat16*)d_in[8], (char*)d_out,
                                     m_wr, m_w0, m_w1);
}
```

```cpp
#include <cuda_runtime.h>
#include <cuda_bf16.h>
#include <cuda.h>
#include <stdint.h>
#include <stddef.h>

namespace {

constexpr int NN = 10000;
constexpr int NE = 320000;
constexpr int G = 132;
constexpr int NT = 384;
constexpr int CH = 2432;
constexpr int NLOC = (NN + G - 1) / G;
#define NPOOL 5
constexpr int NPAIR = NLOC / 2, NPRIV = NPAIR - NPOOL;
constexpr int SEGW = 11;

#define NSLOT 5
#define PFA 16
#define PFB 20
#define PFC 20
#define PFD 20
#define STAG (b & 7)
#define NULLP(v) v
#define CREG 216
#define PREG 72
#define STR2(x) #x
#define STR(x) STR2(x)

constexpr int S_A = 16384, S_C = S_A + 512, S_FULL = S_C + 144, S_EMPTY = S_FULL + 8, S_N = S_C + 160, SLOT = 17152;

constexpr int PSBO = 272;
constexpr int PB1 = 5 * PSBO + 256, PB0 = PSBO + 256;
constexpr int P_1P0 = 0, P_1P1 = PB1, P_0P1 = 2 * PB1, P_0P0 = P_0P1 + PB0, P_1P2 = P_0P0 + PB0;
constexpr int PW = P_1P2 + PB1;

constexpr int O_W1 = 0;
constexpr int O_P = 98304;
constexpr int O_RING = O_P + 8 * PW;
constexpr int O_TRASH = O_RING + 5 * SLOT;
constexpr int O_WBA = O_TRASH + 512, O_WBB = O_WBA + 8, O_WBC = O_WBA + 16, O_WBD = O_WBA + 24, O_NODE = O_WBA + 48;
constexpr int O_SUM = O_NODE + 128, O_MB = O_SUM + 16;
constexpr int SMEM_BYTES = O_MB + 256;
constexpr int CAPT = 240;
constexpr int O_L = 0, LZ = CAPT * 256 / (NT * 16), O_W0S = O_L + CAPT * 256, O_OUT = O_W0S + 65536, O_RH = O_OUT + CH * 8;
constexpr int O_KT = O_RING + SLOT, O_SRC = O_RING + 2 * SLOT;
constexpr int O_BCNT = O_SRC + CH * 4, O_NCUR = O_BCNT + 640, O_NCNT = O_NCUR + 320;
constexpr int O_BOFF = O_NCNT + 512, O_SORT = O_BOFF + 640, O_NOFF = O_SORT + 320;
constexpr int O_WR0 = (O_RING + 3 * SLOT + 1023) / 1024 * 1024, O_WR1 = (O_RING + 4 * SLOT + 1023) / 1024 * 1024;
constexpr int TBIG = G * CAPT + 8, NTILE = TBIG + NE / 8 + G * (NLOC + 5);
static_assert(SMEM_BYTES <= 232448 && NSLOT == 5 && CAPT % 16 == 0 && NTILE < (1 << 18), "smem");
static_assert(LZ * NT * 16 == CAPT * 256 && O_W0S % 1024 == 0 && O_RH + CH * 6 <= O_RING + S_C && G * 128 <= S_C && O_NOFF + 1024 <= O_SRC + S_C, "staging");
static_assert(O_RING % 128 == 0 && SLOT % 128 == 0 && O_W0S <= O_P && O_NOFF % 8 == 0, "layout");
static_assert(G * CH >= NE && NE % 8 == 0 && CH < 4096 && CH / 8 <= 320 && NE < (1 << 21), "chunks");
static_assert(SEGW * (NT / 32) == G && G <= 160 && G % 4 == 0, "segments");
static_assert(NLOC % 4 == 0 && NLOC < 80 && NLOC * 4 <= 320 && NN < 0x3fff && NE / 8 < 0xbfff && NPRIV >= 30, "scan width");

struct __align__(128) Scratch {
    uint32_t keys[G * G * 32];
    uint64_t vals[G * CH];
    uint32_t more[G * CH];
    uint32_t epoch[G * 32];
    uint32_t info[G * NPOOL];
    unsigned done, pad0[31], ticket, pad1[31 + 32 - G * NPOOL % 32];
    uint4 list[NTILE * 16];
};
static_assert(offsetof(Scratch, list) % 128 == 0, "list");
__device__ Scratch g_scratch;
#define TS(i)
#define TSW(i)
#define TV(i, v)

constexpr int SPIN_LIMIT = 1 << 24;

__device__ __forceinline__ void mbar_init(uint32_t a, int c) { asm volatile("mbarrier.init.shared::cta.b64 [%0], %1;" ::"r"(a), "r"(c) : "memory"); }
__device__ __forceinline__ void mbar_expect(uint32_t a, int b) { asm volatile("mbarrier.arrive.expect_tx.shared::cta.b64 _, [%0], %1;" ::"r"(a), "r"(b) : "memory"); }
__device__ __forceinline__ void mbar_arrive(uint32_t a) { asm volatile("mbarrier.arrive.shared::cta.b64 _, [%0];" ::"r"(a) : "memory"); }
__device__ __forceinline__ void mbar_wait(uint32_t a, uint32_t ph) {
    asm volatile("{\n.reg .pred p, q;\n.reg .u32 it;\n"
                 "mbarrier.try_wait.parity.shared::cta.b64 p, [%0], %1;\n"
                 "@p bra DONE;\n"
                 "mov.u32 it, 0;\n"
                 "LOOP:\n"
                 "mbarrier.try_wait.parity.shared::cta.b64 p, [%0], %1;\n"
                 "@p bra DONE;\n"
                 "add.u32 it, it, 1;\n"
                 "setp.gt.u32 q, it, %2;\n"
                 "@q trap;\n"
                 "bra LOOP;\n"
                 "DONE:\n}" ::"r"(a), "r"(ph), "n"(SPIN_LIMIT) : "memory");
}
__device__ __forceinline__ void spin_check(int it) {
    asm volatile("{\n.reg .pred q;\nsetp.gt.s32 q, %0, %1;\n@q trap;\n}" ::"r"(it), "n"(SPIN_LIMIT));
}
__device__ __forceinline__ void tma2d(uint32_t dst, const CUtensorMap* m, int c0, int c1, uint32_t bar) {
    asm volatile("cp.async.bulk.tensor.2d.shared::cluster.global.mbarrier::complete_tx::bytes [%0], [%1, {%3, %4}], [%2];"
                 ::"r"(dst), "l"(m), "r"(bar), "r"(c0), "r"(c1) : "memory");
}
__device__ __forceinline__ void cpa16z(uint32_t d, const void* g, uint32_t v) {
    asm volatile("{\n.reg .pred p;\nsetp.eq.u32 p, %2, 0;\ncp.async.cg.shared.global [%0], [%1], 16, p;\n}" ::"r"(d), "l"(g), "r"(v) : "memory");
}
__device__ __forceinline__ void ldsm4(uint32_t* r, uint32_t a) { asm volatile("ldmatrix.sync.aligned.m8n8.x4.shared.b16 {%0,%1,%2,%3}, [%4];" : "=r"(r[0]), "=r"(r[1]), "=r"(r[2]), "=r"(r[3]) : "r"(a) : "memory"); }
__device__ __forceinline__ void ldsm4t(uint32_t* r, uint32_t a) { asm volatile("ldmatrix.sync.aligned.m8n8.x4.trans.shared.b16 {%0,%1,%2,%3}, [%4];" : "=r"(r[0]), "=r"(r[1]), "=r"(r[2]), "=r"(r[3]) : "r"(a) : "memory"); }
__device__ __forceinline__ void stsm4t(uint32_t a, uint32_t r0, uint32_t r1, uint32_t r2, uint32_t r3) { asm volatile("stmatrix.sync.aligned.m8n8.x4.trans.shared.b16 [%0], {%1,%2,%3,%4};" ::"r"(a), "r"(r0), "r"(r1), "r"(r2), "r"(r3) : "memory"); }
__device__ __forceinline__ void stsm2t(uint32_t a, uint32_t r0, uint32_t r1) { asm volatile("stmatrix.sync.aligned.m8n8.x2.trans.shared.b16 [%0], {%1,%2};" ::"r"(a), "r"(r0), "r"(r1) : "memory"); }
__device__ __forceinline__ void mma16(float* d, const uint32_t* a, uint32_t b0, uint32_t b1) {
    asm("mma.sync.aligned.m16n8k16.row.col.f32.bf16.bf16.f32 {%0,%1,%2,%3}, {%4,%5,%6,%7}, {%8,%9}, {%0,%1,%2,%3};"
        : "+f"(d[0]), "+f"(d[1]), "+f"(d[2]), "+f"(d[3]) : "r"(a[0]), "r"(a[1]), "r"(a[2]), "r"(a[3]), "r"(b0), "r"(b1));
}
__device__ __forceinline__ void mma8(float* d, uint32_t a0, uint32_t a1, uint32_t b0) {
    asm("mma.sync.aligned.m16n8k8.row.col.f32.bf16.bf16.f32 {%0,%1,%2,%3}, {%4,%5}, {%6}, {%0,%1,%2,%3};"
        : "+f"(d[0]), "+f"(d[1]), "+f"(d[2]), "+f"(d[3]) : "r"(a0), "r"(a1), "r"(b0));
}
__device__ __forceinline__ void mma16z(float* d, const uint32_t* a, uint32_t b0, uint32_t b1) {
    asm("mma.sync.aligned.m16n8k16.row.col.f32.bf16.bf16.f32 {%0,%1,%2,%3}, {%4,%5,%6,%7}, {%8,%9}, {%10,%10,%10,%10};"
        : "=f"(d[0]), "=f"(d[1]), "=f"(d[2]), "=f"(d[3]) : "r"(a[0]), "r"(a[1]), "r"(a[2]), "r"(a[3]), "r"(b0), "r"(b1), "f"(0.f));
}
__device__ __forceinline__ uint32_t pack(float lo, float hi) { uint32_t r; asm("cvt.rn.bf16x2.f32 %0, %1, %2;" : "=r"(r) : "f"(hi), "f"(lo)); return r; }
__device__ __forceinline__ uint32_t hmul(uint32_t a, uint32_t b) { uint32_t r; asm("mul.rn.bf16x2 %0, %1, %2;" : "=r"(r) : "r"(a), "r"(b)); return r; }
__device__ __forceinline__ uint32_t hfma(uint32_t a, uint32_t b, uint32_t c) { uint32_t r; asm("fma.rn.bf16x2 %0, %1, %2, %3;" : "=r"(r) : "r"(a), "r"(b), "r"(c)); return r; }
__device__ __forceinline__ uint4 lds128(uint32_t a) { uint4 v; asm volatile("ld.shared.v4.u32 {%0,%1,%2,%3}, [%4];" : "=r"(v.x), "=r"(v.y), "=r"(v.z), "=r"(v.w) : "r"(a) : "memory"); return v; }
__device__ __forceinline__ void sts128(uint32_t a, uint4 v) { asm volatile("st.shared.v4.u32 [%0], {%1,%2,%3,%4};" ::"r"(a), "r"(v.x), "r"(v.y), "r"(v.z), "r"(v.w) : "memory"); }
__device__ __forceinline__ int lds32(uint32_t a) { int v; asm volatile("ld.shared.u32 %0, [%1];" : "=r"(v) : "r"(a) : "memory"); return v; }
__device__ __forceinline__ void sts32(uint32_t a, int v) { asm volatile("st.shared.u32 [%0], %1;" ::"r"(a), "r"(v) : "memory"); }
__device__ __forceinline__ int atoms_add(uint32_t a, int v) { int r; asm volatile("atom.shared.add.u32 %0, [%1], %2;" : "=r"(r) : "r"(a), "r"(v) : "memory"); return r; }
__device__ __forceinline__ uint32_t ld_rlx(const void* p) { uint32_t v; asm volatile("ld.relaxed.gpu.global.u32 %0, [%1];" : "=r"(v) : "l"(p) : "memory"); return v; }
__device__ __forceinline__ void st_rlx(void* p, uint32_t v) { asm volatile("st.relaxed.gpu.global.u32 [%0], %1;" ::"l"(p), "r"(v) : "memory"); }
__device__ __forceinline__ void bulk(uint32_t dst, const void* g, int n, uint32_t bar) {
    asm volatile("cp.async.bulk.shared::cluster.global.mbarrier::complete_tx::bytes [%0], [%1], %2, [%3];" ::"r"(dst), "l"(g), "r"(n), "r"(bar) : "memory");
}
__device__ __forceinline__ void bulk_st(void* g, uint32_t src, int n) {
    asm volatile("cp.async.bulk.global.shared::cta.bulk_group [%0], [%1], %2;\ncp.async.bulk.commit_group;" ::"l"(g), "r"(src), "r"(n) : "memory");
}
__device__ __forceinline__ uint2 lds64(uint32_t a) { uint2 v; asm volatile("ld.shared.v2.u32 {%0,%1}, [%2];" : "=r"(v.x), "=r"(v.y) : "r"(a) : "memory"); return v; }
__device__ __forceinline__ void sts64(uint32_t a, uint32_t x, uint32_t y) { asm volatile("st.shared.v2.u32 [%0], {%1,%2};" ::"r"(a), "r"(x), "r"(y) : "memory"); }
__device__ __forceinline__ void tma3d(uint32_t dst, const CUtensorMap* m, int c2, uint32_t bar) {
    asm volatile("cp.async.bulk.tensor.3d.shared::cluster.global.mbarrier::complete_tx::bytes [%0], [%1, {%3, %3, %4}], [%2];"
                 ::"r"(dst), "l"(m), "r"(bar), "r"(0), "r"(c2) : "memory");
}
__device__ __forceinline__ void pf_l2(const void* g, int n) {
    asm volatile("{.reg .pred p; setp.gt.s32 p, %1, 0; @p cp.async.bulk.prefetch.L2.global [%0], %1;}" ::"l"(g), "r"(n) : "memory");
}
__device__ __forceinline__ void fence_async() { asm volatile("fence.proxy.async.shared::cta;" ::: "memory"); }
__device__ __forceinline__ uint64_t madw(uint32_t a, uint32_t b, uint64_t c) { uint64_t r; asm("mad.wide.u32 %0, %1, %2, %3;" : "=l"(r) : "r"(a), "r"(b), "l"(c)); return r; }
__device__ __forceinline__ uint32_t opaque(uint32_t v, int lane) { return __shfl_sync(0xffffffffu, v, lane); }
__device__ __forceinline__ void bar_sync(int id, int n) { asm volatile("bar.sync %0, %1;" ::"r"(id), "r"(n) : "memory"); }

__device__ __forceinline__ void wg_rs16(float* d, const uint32_t* a, uint64_t db, int sc) {
    asm volatile("{.reg .pred p; setp.ne.b32 p, %13, 0;\n"
                 "wgmma.mma_async.sync.aligned.m64n16k16.f32.bf16.bf16 {%0,%1,%2,%3,%4,%5,%6,%7}, {%8,%9,%10,%11}, %12, p, 1, 1, 0;}"
                 : "+f"(d[0]), "+f"(d[1]), "+f"(d[2]), "+f"(d[3]), "+f"(d[4]), "+f"(d[5]), "+f"(d[6]), "+f"(d[7])
                 : "r"(a[0]), "r"(a[1]), "r"(a[2]), "r"(a[3]), "l"(db), "r"(sc));
}
__device__ __forceinline__ void wg_ss48(float* d, uint64_t da, uint64_t db, int sc) {
    asm volatile("{.reg .pred p; setp.ne.b32 p, %26, 0;\n"
                 "wgmma.mma_async.sync.aligned.m64n48k16.f32.bf16.bf16 {%0,%1,%2,%3,%4,%5,%6,%7,%8,%9,%10,%11,%12,%13,%14,%15,%16,%17,%18,%19,%20,%21,%22,%23}, %24, %25, p, 1, 1, 1, 0;}"
                 : "+f"(d[0]), "+f"(d[1]), "+f"(d[2]), "+f"(d[3]), "+f"(d[4]), "+f"(d[5]), "+f"(d[6]), "+f"(d[7]),
                   "+f"(d[8]), "+f"(d[9]), "+f"(d[10]), "+f"(d[11]), "+f"(d[12]), "+f"(d[13]), "+f"(d[14]), "+f"(d[15]),
                   "+f"(d[16]), "+f"(d[17]), "+f"(d[18]), "+f"(d[19]), "+f"(d[20]), "+f"(d[21]), "+f"(d[22]), "+f"(d[23])
                 : "l"(da), "l"(db), "r"(sc));
}

__device__ __forceinline__ int warp_incl(int v) {
#pragma unroll
    for (int o = 1; o < 32; o <<= 1)
        asm volatile("{.reg .pred p; .reg .b32 u; shfl.sync.up.b32 u|p, %0, %1, 0, 0xffffffff; @p add.s32 %0, %0, u;}" : "+r"(v) : "r"(o));
    return v;
}
__device__ __forceinline__ void ldg128(uint32_t* r, const void* p, bool on) {
    asm volatile("{.reg .pred p; setp.ne.u32 p, %5, 0; @p ld.global.nc.v4.u32 {%0,%1,%2,%3}, [%4];}"
                 : "=r"(r[0]), "=r"(r[1]), "=r"(r[2]), "=r"(r[3]) : "l"(p), "r"((uint32_t)on));
}

struct Acc {
    uint32_t p00[4], p110[4], p10[3][4];
    float t01[4], m[3][4];
};

#define LF(m) ldsm4t(f[m], so + xa + m * 256)
#define LY() ldsm4(yb, so + ya)
#define LC() ldsm4(yb + 4, so + yc)
#define ADV() { asm volatile("@lane0 mbarrier.arrive.shared::cta.b64 _, [%0];" ::"r"(so + S_EMPTY) : "memory"); \
                const bool wrap = so == sm + O_RING + (NSLOT - 1) * SLOT; so = wrap ? sm + O_RING : so + SLOT; ph ^= wrap ? 0x80000000u : 0u; }
#define LA() asm volatile("{\n.reg .pred p;\n.reg .b64 s;\nmov.b64 s, {0, %6};\nmbarrier.test_wait.shared::cta.b64 p, [%5], s;\nselp.u32 %4, 1, 0, p;\n" \
                          "@p ldmatrix.sync.aligned.m8n8.x4.shared.b16 {%0,%1,%2,%3}, [%7];\n}" \
                          : "+r"(a[0]), "+r"(a[1]), "+r"(a[2]), "+r"(a[3]), "=r"(ok) : "r"(so + S_FULL), "r"(ph), "r"(so + aa) : "memory")
#define RAD(p, s) { float c[4]; mma16z(c, wr[p], a[2 * s], a[2 * s + 1]); R[p][2 * s] = pack(c[0], c[1]); R[p][2 * s + 1] = pack(c[2], c[3]); }
#define MUL(n, x, y) (XS >> n & 1 ? hmul(y, x) : hmul(x, y))
#define FMA(n, x, y, z) (XS >> n & 1 ? hfma(y, x, z) : hfma(x, y, z))
#define ACC(n, x, y, z) z = F ? MUL(n, x, y) : FMA(n, x, y, z)
#define P00(i) ACC(0, f[0][i], R[0][i], A.p00[i ^ XA])
#define P10(k, i) ACC(1, f[1 + k][i], R[3][i], A.p10[k][i ^ XA])
#define S0(k, i) sd[i] = MUL(2, f[1 + k][i], yb[2 * k + (i >> 1)])
#define SD(k, i) sd[i] = FMA(2, f[1 + k][i], yb[2 * k + (i >> 1)], sd[i])
#define P110(i) ACC(3, sd[i], R[1][i], A.p110[i ^ XA])
#define TU(i) u[3][i ^ XU] = MUL(4, f[0][i], R[2][i])
#define TM() if (F) mma16z(A.t01, u[3], yb[6], yb[7]); else mma16(A.t01, u[3], yb[6], yb[7])
#define MU(k, i) u[k][i ^ XU] = MUL(5, f[1 + k][i], R[4][i])
#define MM(k) if (F) mma16z(A.m[k], u[k], yb[6], yb[7]); else mma16(A.m[k], u[k], yb[6], yb[7])
#define PK(v, h) pack(v[2 * (h)], v[2 * (h) + 1])
#define LN() { sts32(na + sof, mt); asm volatile("ld.shared.u16 %0, [%1];" : "=r"(mt) : "r"(so + ma) : "memory"); rem = (int)__reduce_max_sync(0xffffffffu, mt) - 0x4001; }
#define FY(k) if (k == 0) mma16z(y, A.p10[0], oh[0][0], oh[0][1]); else mma16(y, k < 3 ? A.p10[k % 3] : A.p00, oh[k][0], oh[k][1])
#define FZ(k) if (k == 0) mma16z(z, A.p110, oh[3][0], oh[3][1]); \
              else if (k == 1) { const uint32_t mp[4] = {PK(A.m[0], XA ^ XU), PK(A.m[0], 1 ^ XA ^ XU), PK(A.m[1], XA ^ XU), PK(A.m[1], 1 ^ XA ^ XU)}; mma16(z, mp, eb[0], eb[1]); } \
              else mma8(z, PK(A.m[2], XA ^ XU), PK(A.m[2], 1 ^ XA ^ XU), eb[2])
#define SX() stsm2t(fx + sof, PK(A.t01, XU), PK(A.t01, 1 ^ XU))
#define SY() stsm4t(fyz + sof, PK(y, XA), PK(y, 1 ^ XA), PK(z, XA), PK(z, 1 ^ XA))
#define X4(op) op(0); op(1); op(2); op(3)
#define Y4(op, k) op(k, 0); op(k, 1); op(k, 2); op(k, 3)
#define XA 1
#define XU 0
#define XS_R 63
#define SEQ_R LF(1); LF(3); LF(0); LF(2); LC(); RAD(1,0); RAD(1,1); RAD(2,0); RAD(0,0); RAD(0,1); RAD(2,1); RAD(3,0); P00(0); TU(0); \
    P10(0,0); P10(0,1); TU(2); TU(3); RAD(4,1); MU(2,2); MU(2,3); TU(1); TM(); P00(1); RAD(4,0); MU(2,0); MU(2,1); MU(0,0); MU(0,2); \
    RAD(3,1); P10(0,2); P10(0,3); LY(); ADV(); LA(); P00(2); MU(0,3); P00(3); MM(2); MU(0,1); MM(0); P10(2,0); P10(2,2); P10(2,3); P10(2,1); \
    P10(1,0); P10(1,1); P10(1,2); P10(1,3); MU(1,2); S0(2,0); SD(1,0); SD(0,0); P110(0); S0(2,1); SD(1,1); SD(0,1); P110(1); S0(2,2); \
    SD(1,2); SD(0,2); P110(2); MU(1,3); S0(2,3); SD(1,3); SD(0,3); P110(3); MU(1,0); MU(1,1); MM(1);
#define XS_F 0
#define SEQ_F LN(); LF(0); LC(); LF(1); LF(2); LF(3); LY(); ADV(); FY(0); FZ(0); FY(1); FZ(1); FY(2); FZ(2); FY(3); SX(); SY(); \
    RAD(0, 0); RAD(0, 1); RAD(1, 0); RAD(1, 1); RAD(2, 0); RAD(2, 1); RAD(3, 0); RAD(3, 1); RAD(4, 0); RAD(4, 1); LA(); \
    X4(P00); X4(TU); TM(); Y4(P10, 0); Y4(MU, 0); MM(0); Y4(P10, 1); Y4(MU, 1); MM(1); Y4(P10, 2); Y4(MU, 2); MM(2); \
    Y4(S0, 0); Y4(SD, 1); Y4(SD, 2); X4(P110);

__global__ void __launch_bounds__(NT, 1)
tp_kernel(const int4* __restrict__ dst, const int4* __restrict__ src, const char* __restrict__ rhat, Scratch* __restrict__ gs,
          const char* __restrict__ x, const char* __restrict__ ea, const __nv_bfloat16* __restrict__ eps, char* __restrict__ out,
          const __grid_constant__ CUtensorMap m_wr, const __grid_constant__ CUtensorMap m_w0, const __grid_constant__ CUtensorMap m_w1) {
    extern __shared__ __align__(1024) char smem_raw[];
    constexpr uint32_t sm = 1024;
    spin_check((uint32_t)__cvta_generic_to_shared(smem_raw) == sm ? 0 : 2 * SPIN_LIMIT);
    int t;
    asm volatile("mov.u32 %0, %%tid.x;" : "=r"(t));
    const int w = t >> 5, lane = t & 31, b = blockIdx.x;

    const int g = lane >> 2, q = lane & 3, mat = lane >> 3, r = lane & 7;
    const int e0 = b * CH + t * 8, ne = min(CH, NE - b * CH);
    const bool act = t * 8 < ne;
    uint32_t d[8];
#pragma unroll
    for (int k = 0; k < 2; k++) ldg128(d + 4 * k, dst + e0 / 4 + k, act);
    uint32_t tag = ld_rlx(&gs->epoch[b * 32]), epl;
    asm volatile("ld.global.nc.u16 %0, [%1];" : "=r"(epl) : "l"(eps + min(lane, 26)));
    if (t < 60) sts128(sm + O_BCNT + 16 * t, make_uint4(0, 0, 0, 0));
    if (t == NT - 1) {
#pragma unroll
        for (int i = 0; i < 4; i++) mbar_init(sm + O_WBA + 8 * i, 1);
        fence_async();
        mbar_expect(sm + O_WBC, ne * 10); mbar_expect(sm + O_WBA, 20480); mbar_expect(sm + O_WBB, 98304); mbar_expect(sm + O_WBD, 65536);
        spin_check(tag);
        bulk(sm + O_RH, rhat + b * (CH * 6), ne * 6, sm + O_WBC);
        bulk(sm + O_SRC, src + b * (CH / 4), ne * 4, sm + O_WBC);
        tma3d(sm + O_WR0, &m_wr, 0, sm + O_WBA);
        tma3d(sm + O_WR1, &m_wr, 5, sm + O_WBA);
        tma3d(sm + O_W0S, &m_w0, 0, sm + O_WBD);
    }
    if (t == 320) {
#pragma unroll
        for (int i = 0; i < NSLOT; i++) {
            sts128(sm + O_RING + i * SLOT + S_C + 64, make_uint4(0, 0, 0, 0));
            mbar_init(sm + O_RING + i * SLOT + S_FULL, 32); mbar_init(sm + O_RING + i * SLOT + S_EMPTY, 8);
        }
    }
#pragma unroll
    for (int k = 0; k < LZ; k++) sts128(sm + O_L + 16 * (t + k * NT), make_uint4(0, 0, 0, 0));
    if (t < 80) sts32(sm + O_NCNT + 4 * t, t <= NLOC ? 4 * t : 0);
    if (t < 100) sts32(sm + O_NODE + 4 * t, 0);
    uint32_t ba[8], rk[8];
    auto pfx = [&](int r0, int n) {
        if (n) pf_l2(x + (b * NLOC + r0) * 1024, min(n, NN - b * NLOC - r0) * 1024);
    };
    if (w < 10) bar_sync(1, 320);
    tag = (tag + 1) << 30;
    if (act) {
#pragma unroll
        for (int i = 0; i < 8; i++) {
            const uint32_t l = __umulhi(d[i], (uint32_t)((1ull << 32) / G + 1));
            ba[i] = d[i] * 4 - l * (4 * G);
            d[i] = l * 4 + (tag + ((e0 + i + 1) << 9) + 4);
            rk[i] = atoms_add(sm + O_BCNT + ba[i], 4);
        }
#pragma unroll
        for (int i = 0; i < 8; i++)
            asm volatile("{.reg .pred p; setp.lt.u32 p, %2, 124; @p st.shared.u32 [%0], %1;}"
                         ::"r"(sm + O_KT + ba[i] * 32 + ((ba[i] + rk[i]) & 127)), "r"(d[i]), "r"(rk[i]) : "memory");
    }
    TS(0);
    __syncthreads();
    {
        int v[5], sum = 0;
#pragma unroll
        for (int i = 0; i < 5; i++) { v[i] = lds32(sm + O_BCNT + 4 * (lane * 5 + i)); sum += v[i]; }
        int e = warp_incl(sum) - sum;
        if (w == 10) {
#pragma unroll
            for (int i = 0; i < 5; i++) {
                const int k = lane * 5 + i;
                if (k < G) sts32(sm + O_KT + k * 128 + ((k * 4 + 124) & 127), tag | v[i] << 10 | e >> 2);
                e += v[i];
            }
            __syncwarp();
            if (lane == 0) {
                fence_async();
                bulk_st(&gs->keys[b * (G * 32)], sm + O_KT, G * 128);
                pfx(0, PFA);
            }
        } else {
#pragma unroll
            for (int i = 0; i < 5; i++) { sts32(sm + O_BOFF + 4 * (lane * 5 + i), e); e += v[i]; }
        }
        __syncwarp();
    }
    TS(11);
    const uint32_t sw = (uint32_t)(((2 * (w & 3) + (mat & 1)) ^ r) * 16 + ((mat >> 1) * 8 + r) * 128);
    uint32_t wr[5][4];
    const uint32_t* kp = &gs->keys[(w * SEGW * G + b) * 32 + ((lane + b) & 31)];
    uint32_t kv[SEGW + 1], ho[SEGW + 1], nk[SEGW + 1], old;
    if (act) {
        uint32_t mx = 0;
#pragma unroll
        for (int i = 0; i < 8; i++) { mx = max(mx, rk[i]); ba[i] = rk[i] + lds32(sm + O_BOFF + ba[i]); }
        if (mx >= 124) {
#pragma unroll
            for (int i = 0; i < 8; i++)
                if (rk[i] >= 124) st_rlx(&gs->more[b * CH + (ba[i] >> 2)], d[i]);
        }
    }
    if (w < 8) {
        mbar_wait(sm + O_WBA, 0);
#pragma unroll
        for (int p = 0; p < 5; p++) {
            const int c = 2 * p + (w >> 2);
            ldsm4t(wr[p], sm + (c < 5 ? O_WR0 : O_WR1 - 5 * 2048) + c * 2048 + sw);
        }
    } else {
        const uint64_t xl = (uint64_t)(x - 1024 + r * 16) - (tag >> 6), al = (uint64_t)(ea - 32 + (lane & 1) * 16) - (tag >> 4);
        const uint64_t ml = (uint64_t)gs->list + lane * 8;
        const uint32_t row = 0x76b821a3u >> 4 * r & 15, row0 = 0xc5bfe0cbu >> 4 * r & 15;
        const uint32_t c[12] = {(uint32_t)xl, (uint32_t)(xl >> 32), (uint32_t)al, (uint32_t)(al >> 32), (uint32_t)ml, (uint32_t)(ml >> 32),
            mat * 2048u + (r ^ 2 * mat) * 16, mat * 2048u + 1024 + (r ^ 2 * mat ^ 1) * 16,
            S_A + (lane & 2) * 128u + g * 32 + ((lane ^ lane >> 4) & 1) * 16, S_C + (mat & 1 ? row : row0) * 16, lane & 1 ? 16u : 9u, lane & 30u};
#pragma unroll
        for (int i = 0; i < 20; i++) wr[i >> 2][i & 3] = i < 12 ? opaque(c[i % 12], lane) : 0;
    }
    TS(21);
    mbar_wait(sm + O_WBC, 0);
    TS(22);
    if (act) {
        uint32_t s[8], y[12];
#pragma unroll
        for (int k = 0; k < 3; k++) *(uint4*)&y[4 * k] = lds128(sm + O_RH + t * 48 + k * 16);
#pragma unroll
        for (int k = 0; k < 2; k++) *(uint4*)&s[4 * k] = lds128(sm + O_SRC + t * 32 + k * 16);
#pragma unroll
        for (int i = 0; i < 8; i++) {
            const int k = 3 * i / 2;
            sts64(sm + O_OUT + ba[i] * 2, __byte_perm(y[k], s[i] + (tag >> 16) + 1, i & 1 ? 0x5432 : 0x5410),
                  i & 1 ? y[k + 1] : __byte_perm(y[k], y[k + 1], 0x5432));
        }
    }
    TS(12);
    if (w < 10) asm volatile("bar.arrive 4, 352;" ::: "memory");
    if (w == 11) {
        bar_sync(4, 352);
        if (lane == 0) { fence_async(); bulk_st(&gs->vals[b * CH], sm + O_OUT, ne * 8); pfx(PFA, PFB); }
        __syncwarp();
    }

    const uint32_t am = lane < 31 ? 511 : 0, none = tag | (320 + 4 * lane);
    auto check = [&]() {
        old = 0;
#pragma unroll
        for (int j = 0; j < SEGW; j++) {
            ho[j] = __shfl_sync(0xffffffffu, kv[j], 31);
            kv[j] = ho[j] >= (lane < 31 ? tag + ((lane + 1) << 12) : 0u) ? kv[j] : none;
            old |= kv[j] ^ tag;
        }
        return __any_sync(0xffffffffu, old >> 30);
    };
#pragma unroll
    for (int j = 0; j < SEGW; j++) kv[j] = ld_rlx(kp + j * (G * 32));
    TS(1);
    TV(19, 0);
    for (int it = 0; check(); it++) {
        spin_check(it);
        if (it == 0) TS(20);
        TV(19, (it + 1) * 100);
#pragma unroll
        for (int j = 0; j < SEGW; j++)
            if (__any_sync(0xffffffffu, (kv[j] ^ tag) >> 30)) kv[j] = ld_rlx(kp + j * (G * 32));
    }
    TS(3);
    kv[SEGW] = none; ho[SEGW] = 0;
    bool slow = false;
    const bool more = __any_sync(0xffffffffu, lane == 31 && (old & 0xfe0000));
    if (more) {
        int c = lane;
#pragma unroll
        for (int j = 0; j < SEGW; j++) {
            const int n = max((int)(ho[j] >> 12 & 0xfff) - 31, 0);
            if ((unsigned)c < (unsigned)n) ho[SEGW] = j * CH + (ho[j] & 0xfff) + 31 + c - lane;
            c -= n;
        }
        slow = lane == 31 && c < 0;
        if (c < 0 && lane < 31)
            for (int it = 0; ((kv[SEGW] = ld_rlx(&gs->more[w * SEGW * CH + lane + ho[SEGW]])) ^ tag) >> 30; it++) spin_check(it);
        __syncwarp();
    }
    uint32_t na_[SEGW + 1];
#pragma unroll
    for (int j = 0; j <= SEGW; j++) {
        na_[j] = (kv[j] & am) | (none & 511 & ~am);
        nk[j] = atoms_add(sm + O_NCNT + na_[j], 512);
    }
    auto visit = [&](auto f) {
#pragma unroll 1
        for (int j = 0; j < SEGW; j++) {
            const uint32_t* kl = &gs->keys[((w * SEGW + j) * G + b) * 32];
            const uint32_t h = ld_rlx(kl + ((31 + b) & 31));
#pragma unroll 1
            for (int i = lane; i < (h >> 12 & 0xfff); i += 32) {
                const int o = (w * SEGW + j) * CH + (h & 0xfff) + i;
                uint32_t k;
                int it = 0;
                do { k = ld_rlx(i < 31 ? kl + ((i + b) & 31) : &gs->more[o]); spin_check(it++); } while ((k ^ tag) >> 30);
                f(k, o, i);
            }
        }
    };
    slow = __syncthreads_or(slow);
    if (slow) {
        if (t < 80) sts32(sm + O_NCNT + 4 * t, t <= NLOC ? 4 * t : 0);
        __syncthreads();
        visit([&](uint32_t k, int, int) { atoms_add(sm + O_NCNT + (k & 511), 512); });
        __syncthreads();
    }
    TS(4);
    if (t == 352) pfx(PFA + PFB, PFC);
    if (w < 10) {
        const uint32_t key = lds32(sm + O_NCNT + 4 + (t & ~3));
        uint4 k[5];
#pragma unroll
        for (int i = 0; i < 5; i++) k[i] = lds128(sm + O_NCNT + q * 80 + i * 16);
        uint32_t c[4] = {0, 0, 0, 0};
#pragma unroll
        for (int i = 0; i < 5; i++) { c[0] += (key - k[i].x) >> 31; c[1] += (key - k[i].y) >> 31; c[2] += (key - k[i].z) >> 31; c[3] += (key - k[i].w) >> 31; }
        int rank = c[0] + c[1] + c[2] + c[3];
        rank += __shfl_xor_sync(0xffffffffu, rank, 1);
        rank += __shfl_xor_sync(0xffffffffu, rank, 2);
        if (t < NLOC * 4) sts32(sm + O_SORT + 4 * rank, key);
    }
    __syncthreads();
    TS(2);
    const bool on = lane < NLOC / 4;
    const uint4 k4 = lds128(sm + O_SORT + 16 * (on ? lane : 0));
    const uint32_t ks[4] = {k4.x, k4.y, k4.z, k4.w};
    const int n0 = on ? max(1u, (ks[0] + 3584) >> 12) : 0, n1 = on ? max(1u, (ks[2] + 3584) >> 12) : 0;
    const int u2 = warp_incl(n0 + n1), u1 = u2 - n1, u0 = u1 - n0;
    const int total = __shfl_sync(0xffffffffu, u2, 31);
    slow |= total > CAPT;
    int gbase = b * CAPT + 1;
    if (on) {
#pragma unroll
        for (int i = 0; i < 4; i++) {
            const int a = ks[i] & 511, node = a * (G / 4) - G + b, o = (i >> 1 ? u1 : u0) * 256 + (i & 1) * 16;
            const uint32_t mk = (node < NN ? node + 1 : 0) + ((i >> 1 ? n1 : n0) << 16) + 0x40000000;
            sts64(sm + O_NOFF + 2 * a, o - (a >> 4), mk);
            if (!slow) sts32(sm + O_L + 4 + o, mk);
        }
    }
    __syncwarp();
    if (!slow) {
        uint64_t vp = (uint64_t)&gs->vals[w * SEGW * CH + lane], vv[SEGW + 1];
        uint32_t mk[SEGW + 1];
#pragma unroll
        for (int j = 0; j <= SEGW; j++) vv[j] = tag;
        TS(13);
        if (t == 352) { pfx(PFA + PFB + PFC, PFD); asm volatile("cp.async.bulk.wait_group.read 0;" ::: "memory"); }
        auto ldv = [&](bool again) {
#pragma unroll
            for (int j = 0; j <= SEGW; j++)
                asm volatile("{.reg .pred p; setp.lt.u32 p, %2, 320; @p ld.relaxed.gpu.global.b64 %0, [%1];}" : "+l"(vv[j])
                             : "l"(madw(j < SEGW ? ho[j] & 0xfff : ho[j], 8, vp) + (j < SEGW ? j * CH * 8 : 0)),
                               "r"(again ? (((uint32_t)vv[j] ^ tag) >> 30 ? 0 : 320) : na_[j]) : "memory");
        };
        ldv(false);
#pragma unroll
        for (int j = 0; j <= SEGW; j++) {
            const uint2 o = lds64(sm + O_NOFF + 2 * na_[j]);
            nk[j] = o.x + (nk[j] >> 4); mk[j] = o.y;
        }
        for (int it = 0;; it++) {
            old = 0;
#pragma unroll
            for (int j = 0; j <= SEGW; j++) old |= (uint32_t)vv[j] ^ tag;
            if (!__any_sync(0xffffffffu, old >> 30)) break;
            spin_check(it);
            vp = __shfl_sync(0xffffffffu, vp, lane);
            ldv(true);
        }
#pragma unroll
        for (int j = 0; j <= SEGW; j++)
            asm volatile("{.reg .pred p; setp.ne.u32 p, %3, %5; @p st.shared.v4.u32 [%0], {%1,%2,%3,%4};}"
                         ::"r"(sm + O_L + nk[j]), "r"(kv[j]), "r"(mk[j]), "r"((uint32_t)vv[j]), "r"((uint32_t)(vv[j] >> 32)), "r"(tag) : "memory");
        if (na_[SEGW] < 320) gs->more[w * SEGW * CH + lane + ho[SEGW]] = 0;
    } else {
        int so = 0;
#pragma unroll
        for (int j = 0; j < SEGW; j++) so += ho[j] & 0xfff;
        if (lane == 0) atoms_add(sm + O_SUM, so);
        if (t == 352) asm volatile("cp.async.bulk.wait_group.read 0;" ::: "memory");
        __syncthreads();
        gbase = TBIG + (lds32(sm + O_SUM) >> 3) + (NLOC + 5) * b;
        auto put = [&](uint32_t k, uint64_t e, uint32_t a, int rank) {
            const uint2 o = lds64(sm + O_NOFF + 2 * a);
            gs->list[gbase * 16 + ((o.x + (a >> 4)) >> 4) + rank * 2] = make_uint4(k, o.y, e, e >> 32);
        };
        visit([&](uint32_t k, int o, int i) {
            uint64_t e;
            int it = 0;
            do {
                asm volatile("ld.relaxed.gpu.global.b64 %0, [%1];" : "=l"(e) : "l"(&gs->vals[o]) : "memory");
                spin_check(it++);
            } while (((uint32_t)e ^ tag) >> 30);
            if (i >= 31) gs->more[o] = 0;
            put(k, e, k & 511, atoms_add(sm + O_NCUR + (k & 511), 1));
        });
#pragma unroll 1
        for (int i = 0; i < 4; i++) {
            const uint32_t k = i == 0 ? ks[0] : i == 1 ? ks[1] : i == 2 ? ks[2] : ks[3];
#pragma unroll 1
            for (int p = (k >> 9) + w; p < (i >> 1 ? n1 : n0) * 8; p += NT / 32) put(0, 0, k & 511, p);
        }
        __threadfence();
    }
    __syncthreads();
    TS(5);

    if (w >= 8) {
        asm volatile("setmaxnreg.dec.sync.aligned.u32 " STR(PREG) ";");
        const int h = __reduce_max_sync(0xffffffffu, w & 3);
        gbase = __reduce_max_sync(0xffffffffu, gbase);
        int pos = gbase + h, end = gbase + __reduce_max_sync(0xffffffffu, lane == (NPRIV - 1) / 2 ? (NPRIV & 1 ? u1 : u2) : 0);
        const uint32_t ring = sm + O_RING;
        const uint64_t xl = wr[0][0] | (uint64_t)wr[0][1] << 32, al = wr[0][2] | (uint64_t)wr[0][3] << 32, ml = wr[1][0] | (uint64_t)wr[1][1] << 32;
        const uint32_t xoff[2] = {wr[1][2], wr[1][3]}, aoff = wr[2][0], coff = wr[2][1], sh = wr[2][2], ial = wr[2][3];
        auto lde = [&](uint2& e, int p) {
            asm volatile("{.reg .pred p; setp.gt.s32 p, %3, 0; @p ld.relaxed.gpu.global.v2.u32 {%0,%1}, [%2];}" : "+r"(e.x), "+r"(e.y) : "l"(madw(p, 256, ml)), "r"(p) : "memory");
        };
        uint2 e0[3] = {};
#pragma unroll
        for (int k = 0; k < 3; k++) {
            e0[k] = lds64(sm + O_L - 2048 + k * 1024 + t * 8);
            lde(e0[k], slow ? pos + 4 * k : 0);
        }
        if (h == 3) fence_async();
        int cur = pos;
        pos += 4;

        int ev = 0, state = -2, tk = 0, nr = 0;
        uint32_t inf = 0;
        int ii = 0;
        auto take = [&]() {
            int v = 0;
            asm volatile("{.reg .pred p; setp.eq.s32 p, %2, 0; @p atom.relaxed.gpu.global.add.u32 %0, [%1], 1;}" : "+r"(v) : "l"(&gs->ticket), "r"(lane) : "memory");
            return v;
        };
        auto resolve = [&]() {
            const int k = __reduce_max_sync(0xffffffffu, tk);
            inf = tag;
            if (k < G * NPOOL) { const int l = k / G; ii = (k - l * G) * NPOOL + l; inf = ld_rlx(&gs->info[ii]); tk = take(); }
        };
        uint32_t so = ring + h * SLOT, ph = 1;
#define CLK(c, dep)
        while (true) {
            CLK(c0, 0);
            const uint2 e = e0[0];
            const uint32_t o = e.x >> sh, id = __shfl_sync(0xffffffffu, o, ial);
            uint32_t s[4];
#pragma unroll
            for (int j = 0; j < 4; j++) s[j] = __shfl_sync(0xffffffffu, o, 2 * j + 1, 8);
            const char* ga = (const char*)madw(id, 32, al);
            const char* gx[4];
#pragma unroll
            for (int j = 0; j < 4; j++) gx[j] = (const char*)madw(s[j], 1024, xl);
            CLK(c1, 0);
            lde(e0[0], state < 0 ? 0 : pos);
            mbar_wait(so + S_EMPTY, ph);
            if (cur <= 0) break;
            CLK(c2, 0);
            cpa16z(so + aoff, ga, id);
#pragma unroll
            for (int j = 0; j < 4; j++)
#pragma unroll
                for (int k = 0; k < 8; k++) cpa16z(so + xoff[j >> 1] + (j & 1) * 8192 + k * 128, gx[j] + k * 128, NULLP(s[j]));
            stsm2t(so + coff, e.x, e.y);
            asm volatile("cp.async.mbarrier.arrive.noinc.shared::cta.b64 [%0];" ::"r"(so + S_FULL) : "memory");
            CLK(c3, 0);
            ph ^= so != ring;
            so = so == ring ? so + 4 * SLOT : so - SLOT;
            cur = pos;
            pos += 4;
            if (pos >= ev) {
                if (state < 0) {
                    e0[0] = e0[1]; e0[1] = e0[2];
                    if (state == -2) {
                        if (h == 0) TSW(24);
                        if (h == 3) TSW(25);
                        if (h < 3) asm volatile("bar.arrive 7, %0;" ::"n"(NT) : "memory");
                        else {
                            bar_sync(7, NT);
                            if (lane == 0) {
                                if (!slow) bulk_st(gs->list + gbase * 16, sm + O_L, total * 256);
                                asm volatile("cp.async.bulk.wait_group.read 0;" ::: "memory");
                                for (int j = 0; j < 4; j++) tma2d(sm + O_W1 + j * 24576, &m_w1, 64 * (j >> 1), 192 * (j & 1), sm + O_WBB);
                            }
                            __syncwarp();
                        }
                        state = -1;
                    } else {
                        if (h == 3) {
                            if (lane == 0) asm volatile("cp.async.bulk.wait_group 0;\nfence.proxy.async;" ::: "memory");
                            __syncwarp();
                            if (on && 2 * lane >= NPRIV) st_rlx(&gs->info[b * NPOOL + 2 * lane - NPRIV], tag | (gbase + u0) << 12 | n0);
                            if (on && 2 * lane + 1 >= NPRIV) st_rlx(&gs->info[b * NPOOL + 2 * lane + 1 - NPRIV], tag | (gbase + u1) << 12 | n1);
                        }
                        bar_sync(6, 128);
                        ev = h ? end : end - 12; state = h ? 2 : 0;
                    }
                } else if (state == 0) { ev = end - 6; state = 1; tk = take(); }
                else if (state == 1) { resolve(); ev = end; state = 2; }
                else {
                    do {
                        const uint32_t mb = sm + O_MB + (nr & 31) * 8;
                        uint32_t rg;
                        nr++;
                        if (h == 0) {
                            for (int it = 0; (rg = __reduce_max_sync(0xffffffffu, inf ^ tag)) >> 30; it++) { spin_check(it); inf = ld_rlx(&gs->info[ii]); }
                            asm volatile("st.release.cta.shared.b64 [%0], %1;" ::"r"(mb), "l"(rg | (uint64_t)nr << 32) : "memory");
                            if (rg) resolve();
                        } else {
                            uint64_t m;
                            for (int it = 0;; it++) {
                                asm volatile("ld.acquire.cta.shared.b64 %0, [%1];" : "=l"(m) : "r"(mb) : "memory");
                                if (__all_sync(0xffffffffu, (int)(m >> 32) == nr)) break;
                                spin_check(it);
                            }
                            rg = __reduce_max_sync(0xffffffffu, (uint32_t)m);
                        }
                        pos = rg ? (int)(rg >> 12) + pos - end : -(1 << 30);
                        end = (rg >> 12) + (rg & 0xfff);
                    } while (pos >= end);
                    ev = end;
                }
            }
        }
        TSW(8 + (h & 1));
        if (lane == 0) sts32(so + S_N, 0);
        mbar_arrive(so + S_FULL);
        if (t == 256) {
            gs->epoch[b * 32] = (tag >> 30) % 3;
            if (atomicInc(&gs->done, G - 1) == G - 1) gs->ticket = 0;
        }
        asm volatile("cp.async.wait_all;" ::: "memory");
    } else {
        asm volatile("setmaxnreg.inc.sync.aligned.u32 " STR(CREG) ";");
        const uint32_t xa = opaque(((mat >> 1) * 8 + r) * 1024 + (w >> 2) * 128 + (((2 * (w & 3) + (mat & 1)) ^ r) * 16), lane);
        const uint32_t aa = opaque(S_A + ((mat >> 1) * 8 + r) * 32 + (((mat & 1) ^ (r >> 2)) * 16), lane);
        const uint32_t ya = opaque(S_C + (mat & 1) * 80 + (mat >> 1) * 16, lane);
        const uint32_t yc = opaque(S_C + (mat < 2 ? mat * 80 + 32 : (r >> 2) == (mat & 1) && q < 3 ? (mat & 1) * 80 + q * 16 : 64), lane);
        const uint32_t ma = opaque(mat < 2 ? S_C + 48 + mat * 80 : S_N, lane), na = opaque(sm + O_NODE + mat * 4, lane);
        const uint32_t pw = sm + O_P + w * PW;
        const uint32_t fx = opaque((q < 3 ? pw + P_1P0 + 2 * q * PSBO + (mat & 1) * 128 : sm + O_TRASH + ((pw - sm - O_TRASH + 96) & 127)) + (r >> 2) * PSBO, lane);
        const uint32_t fyz = opaque(pw + (q < 3 ? (mat < 2 ? P_1P1 : P_1P2) + 2 * q * PSBO : mat < 2 ? P_0P0 : P_0P1) + (mat & 1) * 128 + (r >> 2) * PSBO, lane);
        uint32_t oh[4][2];
#pragma unroll
        for (int c = 0; c < 8; c++) oh[c & 3][c >> 2] = opaque(g == c ? 0x3F803F80u : 0u, lane);
        uint32_t eb[3];
#pragma unroll
        for (int k = 0; k < 3; k++) {
            const int i = (g & 3) * 9 + (q & 1) * 6 + k;
            const uint32_t lo = __shfl_sync(0xffffffffu, epl, i), hi = __shfl_sync(0xffffffffu, epl, i + 3);
            eb[k] = (g & 3) < 3 && (q >> 1) == (g >> 2) ? (q & 1 ? lo : lo | hi << 16) : 0u;
        }
        asm volatile(".reg .pred lane0;\nsetp.eq.u32 lane0, %0, 0;" ::"r"(lane));
        uint32_t w0[16][4];
        mbar_wait(sm + O_WBD, 0);
#pragma unroll
        for (int k = 0; k < 16; k++) ldsm4t(w0[k], sm + O_W0S + (w >> 2) * 32768 + k * 2048 + sw);
        bar_sync(7, NT);
        TS(6);
        Acc A;
#pragma unroll
        for (int i = 0; i < 4; i++) { A.p00[i] = A.p110[i] = A.p10[0][i] = A.p10[1][i] = A.p10[2][i] = 0; A.t01[i] = A.m[0][i] = A.m[1][i] = A.m[2][i] = 0.f; }
        int slot = STAG * 16 - 16, rem;
        uint32_t so = sm + O_RING, ph = opaque(0, lane), a[4], ok, mt = 0;
        mbar_wait(so + S_FULL, 0);
        ldsm4(a, so + aa);
        TS(7);
        while (true) {
            {
                constexpr int F = 1, XS = XS_F;
                uint32_t yb[8], f[4][4], R[5][4], u[4][4], sd[4];
                float y[4], z[4];
                const uint32_t sof = slot & 112;
                SEQ_F
                slot += 16;
            }
            if (!(ok && rem > 0 && slot != 128)) {
                if (slot == 128 || rem < 0) {
                    asm volatile("fence.proxy.async.shared::cta;" ::: "memory");
                    mbar_wait(sm + O_WBB, 0);
                    bar_sync(1, 256);
                    float d0[8], d1[24];
                    const uint32_t wg = __reduce_max_sync(0xffffffffu, w >> 2);
                    const uint64_t db = (uint64_t)((sm + O_P) >> 4) | (8ull << 16) | ((uint64_t)(PSBO / 16) << 32);
                    const uint32_t da = ((sm + O_W1) >> 4 | 1 << 16) + wg * 3072;
                    asm volatile("wgmma.fence.sync.aligned;" ::: "memory");
#pragma unroll
                    for (int k = 0; k < 16; k++) wg_rs16(d0, w0[k], db + (((k & 7) * PW + ((k >> 3) ? P_0P1 : P_0P0)) >> 4), k);
                    asm volatile("wgmma.commit_group.sync.aligned;" ::: "memory");
#pragma unroll
                    for (int k = 0; k < 24; k++)
                        wg_ss48(d1, (da + k * 128) | (64ull << 32) | (1ull << 62), db + (((k & 7) * PW + ((k >> 3) == 0 ? P_1P0 : (k >> 3) == 1 ? P_1P1 : P_1P2)) >> 4), k);
                    asm volatile("wgmma.commit_group.sync.aligned;" ::: "memory");
                    const uint2 n0 = lds64(sm + O_NODE + mat * 16), n1 = lds64(sm + O_NODE + 64 + mat * 16);
                    const uint32_t nd[4] = {mat * 16 < slot ? n0.x : 0, mat * 16 + 64 < slot ? n1.x : 0, mat * 16 < slot ? n0.y : 0, mat * 16 + 64 < slot ? n1.y : 0};
                    const uint64_t op = (uint64_t)(out - 1024 + (w & 3) * 256 + (w >> 2) * 128 + r * 16);
                    uint64_t oa[4];
#pragma unroll
                    for (int it = 0; it < 4; it++) oa[it] = madw(nd[it], 1024, op);
                    uint32_t sg = sm + O_P + (w & 4) * PW + ((mat >> 1) * 8 + r) * 128 + (((2 * (w & 3) + (mat & 1)) ^ r) * 16);
                    uint32_t sl = pw + mat * 128 + (r ^ mat) * 16, sl2 = pw + 512 + mat * 128 + (r ^ mat ^ 4) * 16;
                    asm volatile("wgmma.wait_group.sync.aligned 1;" ::: "memory");
#pragma unroll
                    for (int i = 0; i < 8; i++) asm volatile("" : "+f"(d0[i])::"memory");
                    uint32_t o[4][4], chk = sg & sl & sl2;
                    float gt[8];
#pragma unroll
                    for (int i = 0; i < 8; i++) {
                        asm("ex2.approx.ftz.f32 %0, %1;" : "=f"(gt[i]) : "f"(d0[i] * -1.4426950408889634f));
                        asm("rcp.approx.ftz.f32 %0, %1;" : "=f"(gt[i]) : "f"(gt[i] + 1.f));
                        chk &= __float_as_uint(gt[i]);
                    }
#pragma unroll
                    for (int i = 0; i < 4; i++) { o[0][i] = pack(d0[2 * i], d0[2 * i + 1]); chk &= o[0][i] & (uint32_t)(oa[i] >> 32); }
                    sts32(sm + O_TRASH, chk);
                    asm volatile("wgmma.wait_group.sync.aligned 0;" ::: "memory");
#pragma unroll
                    for (int i = 0; i < 24; i++) asm volatile("" : "+f"(d1[i])::"memory");
                    bar_sync(1, 256);
#pragma unroll
                    for (int i = 0; i < 4; i++)
#pragma unroll
                        for (int j = 0; j < 3; j++) o[1 + j][i] = pack(d1[8 * j + 2 * i] * gt[2 * i], d1[8 * j + 2 * i + 1] * gt[2 * i + 1]);
#pragma unroll
                    for (int j = 0; j < 4; j++) stsm4t(sg + j * PW, o[j][0], o[j][1], o[j][2], o[j][3]);
                    bar_sync(2 + wg, 128);
                    uint4 v[4];
#pragma unroll
                    for (int it = 0; it < 4; it++) v[it] = lds128((it & 1 ? sl2 : sl) + (it >> 1) * 1024);
#pragma unroll
                    for (int it = 0; it < 4; it++)
                        asm volatile("{.reg .pred p; setp.ne.u32 p, %5, 0; @p st.global.v4.u32 [%0], {%1,%2,%3,%4};}"
                                     ::"l"(oa[it]), "r"(v[it].x), "r"(v[it].y), "r"(v[it].z), "r"(v[it].w), "r"(nd[it]) : "memory");
                    __syncwarp();
                    slot = 0;
                    if (rem < 0) break;
                }
                if (!ok) { mbar_wait(so + S_FULL, ph >> 31); ldsm4(a, so + aa); }
                if (rem == 0) continue;
            }
            while (true) {
                do {
                    constexpr int F = 0, XS = XS_R;
                    uint32_t yb[8], f[4][4], R[5][4], u[4][4], sd[4];
                    SEQ_R
                    rem--;
                } while (ok && rem > 0);
                if (ok) break;
                mbar_wait(so + S_FULL, ph >> 31); ldsm4(a, so + aa);
                if (rem == 0) break;
            }
        }
        TS(10);
    }
}

typedef CUresult (*EncFn)(CUtensorMap*, CUtensorMapDataType, cuuint32_t, void*, const cuuint64_t*, const cuuint64_t*,
                          const cuuint32_t*, const cuuint32_t*, CUtensorMapInterleave, CUtensorMapSwizzle,
                          CUtensorMapL2promotion, CUtensorMapFloatOOBfill);

void make_map(EncFn fn, CUtensorMap* m, void* p, int rows, int cols, int brows, int rank, int bblk, CUtensorMapSwizzle swz) {
    cuuint64_t dims[3] = {(cuuint64_t)(rank == 3 ? 64 : cols), (cuuint64_t)rows, (cuuint64_t)cols / 64}, strides[2] = {(cuuint64_t)cols * 2, 128};
    cuuint32_t box[3] = {64, (cuuint32_t)brows, (cuuint32_t)bblk}, es[3] = {1, 1, 1};
    fn(m, CU_TENSOR_MAP_DATA_TYPE_BFLOAT16, rank, p, dims, strides, box, es, CU_TENSOR_MAP_INTERLEAVE_NONE,
       swz, CU_TENSOR_MAP_L2_PROMOTION_NONE, CU_TENSOR_MAP_FLOAT_OOB_FILL_NONE);
}

}

extern "C" void kernel_launch(void* const* d_in, const int* in_sizes, int n_in, void* d_out, int out_size) {
    static EncFn enc = nullptr;
    static void* scratch = nullptr;
    if (!enc) {
        void* fn = nullptr;
        cudaDriverEntryPointQueryResult qr;
        cudaGetDriverEntryPoint("cuTensorMapEncodeTiled", &fn, cudaEnableDefault, &qr);
        enc = (EncFn)fn;
        cudaGetSymbolAddress(&scratch, g_scratch);
        cudaFuncSetAttribute(tp_kernel, cudaFuncAttributeMaxDynamicSharedMemorySize, SMEM_BYTES);
    }
    CUtensorMap m_wr, m_w0, m_w1;
    make_map(enc, &m_wr, d_in[5], 16, 640, 16, 3, 5, CU_TENSOR_MAP_SWIZZLE_128B);
    make_map(enc, &m_w0, d_in[6], 256, 128, 256, 3, 2, CU_TENSOR_MAP_SWIZZLE_128B);
    make_map(enc, &m_w1, d_in[7], 384, 128, 192, 2, 1, CU_TENSOR_MAP_SWIZZLE_128B);
    tp_kernel<<<G, NT, SMEM_BYTES>>>((const int4*)d_in[4], (const int4*)d_in[3], (const char*)d_in[1], (Scratch*)scratch,
                                     (const char*)d_in[0], (const char*)d_in[2], (const __nv_bfloat16*)d_in[8], (char*)d_out,
                                     m_wr, m_w0, m_w1);
}
```

```cpp
#include <cuda_runtime.h>
#include <cuda_bf16.h>
#include <cuda.h>
#include <stdint.h>
#include <stddef.h>

namespace {

constexpr int NN = 10000;
constexpr int NE = 320000;
constexpr int G = 132;
constexpr int NT = 384;
constexpr int CH = 2432;
constexpr int NLOC = (NN + G - 1) / G;
#define NPOOL 4
constexpr int NPAIR = NLOC / 2, NPRIV = NPAIR - NPOOL;
constexpr int SEGW = 11;

#define NSLOT 5
#define PFA 16
#define PFB 20
#define PFC 20
#define PFD 20
#define STAG (b & 7)
#define ASC (b & 1)
#define THETA G
#define PFI "@!z4 prefetch.global.L2 [%5];"
#define NULLP(v) v
#define CREG 216
#define PREG 72
#define STR2(x) #x
#define STR(x) STR2(x)

constexpr int S_A = 16384, S_C = S_A + 512, S_FULL = S_C + 144, S_EMPTY = S_FULL + 8, S_N = S_C + 160, SLOT = S_C + 256;

constexpr int PSBO = 272;
constexpr int PB1 = 5 * PSBO + 256, PB0 = PSBO + 256;
constexpr int P_1P0 = 0, P_1P1 = PB1, P_0P1 = 2 * PB1, P_0P0 = P_0P1 + PB0, P_1P2 = P_0P0 + PB0;
constexpr int PW = P_1P2 + PB1;

constexpr int O_W1 = 0;
constexpr int O_P = 98304;
constexpr int O_RING = O_P + 8 * PW;
constexpr int O_TRASH = O_RING + 5 * SLOT;
constexpr int O_WBA = O_TRASH + 512, O_WBB = O_WBA + 8, O_WBC = O_WBA + 16, O_WBD = O_WBA + 24, O_NODE = O_WBA + 48;
constexpr int O_SUM = O_NODE + 128, O_MB = O_SUM + 16;
constexpr int SMEM_BYTES = O_MB + 256;
constexpr int CAPT = 240;
constexpr int O_L = 0, LZ = CAPT * 256 / (NT * 16), O_W0S = O_L + CAPT * 256, O_OUT = O_W0S + 65536, O_RH = O_OUT + CH * 8;
constexpr int O_KT = O_RING + SLOT, O_SRC = O_RING + 2 * SLOT;
constexpr int O_BCNT = O_SRC + CH * 4, O_NCUR = O_BCNT + 640, O_NCNT = O_NCUR + 320;
constexpr int O_BOFF = O_NCNT + 512, O_SORT = O_BOFF + 640, O_NOFF = O_SORT + 320;
constexpr int O_WR0 = (O_RING + 3 * SLOT + 1023) / 1024 * 1024, O_WR1 = (O_RING + 4 * SLOT + 1023) / 1024 * 1024;
constexpr int TBIG = G * CAPT + 8, NTILE = TBIG + NE / 8 + G * (NLOC + 5);
static_assert(SMEM_BYTES <= 232448 && CAPT % 16 == 0 && NTILE < (1 << 18), "smem");
static_assert(LZ * NT * 16 == CAPT * 256 && O_W0S % 1024 == 0 && O_RH + CH * 6 <= O_RING + S_C && G * 128 <= S_C && O_NOFF + 1024 <= O_SRC + S_C, "staging");
static_assert(O_RING % 128 == 0 && SLOT % 16 == 0 && O_W0S <= O_P && O_NOFF % 8 == 0, "layout");
static_assert(G * CH >= NE && NE % 8 == 0 && CH < 4096 && CH / 8 <= 320 && NE < (1 << 21), "chunks");
static_assert(SEGW * (NT / 32) == G && G <= 160 && G % 4 == 0, "segments");
static_assert(NLOC % 4 == 0 && NLOC < 80 && NLOC * 4 <= 320 && NN < 0x3fff && NE / 8 < 0xbfff && NPRIV >= 30, "scan width");

struct __align__(128) Scratch {
    uint32_t keys[G * G * 32];
    uint64_t vals[G * CH];
    uint32_t more[G * CH];
    uint32_t epoch[G * 32];
    uint32_t info[G * NPOOL];
    unsigned done, pad0[31], ticket, pad1[31 + 32 - G * NPOOL % 32];
    uint4 list[NTILE * 16];
};
static_assert(offsetof(Scratch, list) % 128 == 0, "list");
__device__ Scratch g_scratch;
#define TS(i)
#define TSW(i)
#define TV(i, v)

constexpr int SPIN_LIMIT = 1 << 24;

__device__ __forceinline__ void mbar_init(uint32_t a, int c) { asm volatile("mbarrier.init.shared::cta.b64 [%0], %1;" ::"r"(a), "r"(c) : "memory"); }
__device__ __forceinline__ void mbar_expect(uint32_t a, int b) { asm volatile("mbarrier.arrive.expect_tx.shared::cta.b64 _, [%0], %1;" ::"r"(a), "r"(b) : "memory"); }
__device__ __forceinline__ void mbar_arrive(uint32_t a) { asm volatile("mbarrier.arrive.shared::cta.b64 _, [%0];" ::"r"(a) : "memory"); }
__device__ __forceinline__ void mbar_wait(uint32_t a, uint32_t ph) {
    asm volatile("{\n.reg .pred p, q;\n.reg .u32 it;\n"
                 "mbarrier.try_wait.parity.shared::cta.b64 p, [%0], %1;\n"
                 "@p bra DONE;\n"
                 "mov.u32 it, 0;\n"
                 "LOOP:\n"
                 "mbarrier.try_wait.parity.shared::cta.b64 p, [%0], %1;\n"
                 "@p bra DONE;\n"
                 "add.u32 it, it, 1;\n"
                 "setp.gt.u32 q, it, %2;\n"
                 "@q trap;\n"
                 "bra LOOP;\n"
                 "DONE:\n}" ::"r"(a), "r"(ph), "n"(SPIN_LIMIT) : "memory");
}
__device__ __forceinline__ void mbar_wait31(uint32_t a, uint32_t ph) {
    asm volatile("{\n.reg .pred p, q;\n.reg .u32 it;\n.reg .b64 s;\n"
                 "mov.b64 s, {0, %1};\n"
                 "mbarrier.try_wait.shared::cta.b64 p, [%0], s;\n"
                 "@p bra DONE;\n"
                 "mov.u32 it, 0;\n"
                 "LOOP:\n"
                 "mbarrier.try_wait.shared::cta.b64 p, [%0], s;\n"
                 "@p bra DONE;\n"
                 "add.u32 it, it, 1;\n"
                 "setp.gt.u32 q, it, %2;\n"
                 "@q trap;\n"
                 "bra LOOP;\n"
                 "DONE:\n}" ::"r"(a), "r"(ph), "n"(SPIN_LIMIT) : "memory");
}
__device__ __forceinline__ void spin_check(int it) {
    asm volatile("{\n.reg .pred q;\nsetp.gt.s32 q, %0, %1;\n@q trap;\n}" ::"r"(it), "n"(SPIN_LIMIT));
}
__device__ __forceinline__ void tma2d(uint32_t dst, const CUtensorMap* m, int c0, int c1, uint32_t bar) {
    asm volatile("cp.async.bulk.tensor.2d.shared::cluster.global.mbarrier::complete_tx::bytes [%0], [%1, {%3, %4}], [%2];"
                 ::"r"(dst), "l"(m), "r"(bar), "r"(c0), "r"(c1) : "memory");
}
__device__ __forceinline__ void ldsm4(uint32_t* r, uint32_t a) { asm volatile("ldmatrix.sync.aligned.m8n8.x4.shared.b16 {%0,%1,%2,%3}, [%4];" : "=r"(r[0]), "=r"(r[1]), "=r"(r[2]), "=r"(r[3]) : "r"(a) : "memory"); }
__device__ __forceinline__ void ldsm4t(uint32_t* r, uint32_t a) { asm volatile("ldmatrix.sync.aligned.m8n8.x4.trans.shared.b16 {%0,%1,%2,%3}, [%4];" : "=r"(r[0]), "=r"(r[1]), "=r"(r[2]), "=r"(r[3]) : "r"(a) : "memory"); }
__device__ __forceinline__ void stsm4t(uint32_t a, uint32_t r0, uint32_t r1, uint32_t r2, uint32_t r3) { asm volatile("stmatrix.sync.aligned.m8n8.x4.trans.shared.b16 [%0], {%1,%2,%3,%4};" ::"r"(a), "r"(r0), "r"(r1), "r"(r2), "r"(r3) : "memory"); }
__device__ __forceinline__ void stsm2t(uint32_t a, uint32_t r0, uint32_t r1) { asm volatile("stmatrix.sync.aligned.m8n8.x2.trans.shared.b16 [%0], {%1,%2};" ::"r"(a), "r"(r0), "r"(r1) : "memory"); }
__device__ __forceinline__ void mma16(float* d, const uint32_t* a, uint32_t b0, uint32_t b1) {
    asm("mma.sync.aligned.m16n8k16.row.col.f32.bf16.bf16.f32 {%0,%1,%2,%3}, {%4,%5,%6,%7}, {%8,%9}, {%0,%1,%2,%3};"
        : "+f"(d[0]), "+f"(d[1]), "+f"(d[2]), "+f"(d[3]) : "r"(a[0]), "r"(a[1]), "r"(a[2]), "r"(a[3]), "r"(b0), "r"(b1));
}
__device__ __forceinline__ void mma8(float* d, uint32_t a0, uint32_t a1, uint32_t b0) {
    asm("mma.sync.aligned.m16n8k8.row.col.f32.bf16.bf16.f32 {%0,%1,%2,%3}, {%4,%5}, {%6}, {%0,%1,%2,%3};"
        : "+f"(d[0]), "+f"(d[1]), "+f"(d[2]), "+f"(d[3]) : "r"(a0), "r"(a1), "r"(b0));
}
__device__ __forceinline__ void mma16z(float* d, const uint32_t* a, uint32_t b0, uint32_t b1) {
    asm("mma.sync.aligned.m16n8k16.row.col.f32.bf16.bf16.f32 {%0,%1,%2,%3}, {%4,%5,%6,%7}, {%8,%9}, {%10,%10,%10,%10};"
        : "=f"(d[0]), "=f"(d[1]), "=f"(d[2]), "=f"(d[3]) : "r"(a[0]), "r"(a[1]), "r"(a[2]), "r"(a[3]), "r"(b0), "r"(b1), "f"(0.f));
}
__device__ __forceinline__ uint32_t pack(float lo, float hi) { uint32_t r; asm("cvt.rn.bf16x2.f32 %0, %1, %2;" : "=r"(r) : "f"(hi), "f"(lo)); return r; }
__device__ __forceinline__ uint32_t hmul(uint32_t a, uint32_t b) { uint32_t r; asm("mul.rn.bf16x2 %0, %1, %2;" : "=r"(r) : "r"(a), "r"(b)); return r; }
__device__ __forceinline__ uint32_t hfma(uint32_t a, uint32_t b, uint32_t c) { uint32_t r; asm("fma.rn.bf16x2 %0, %1, %2, %3;" : "=r"(r) : "r"(a), "r"(b), "r"(c)); return r; }
__device__ __forceinline__ uint4 lds128(uint32_t a) { uint4 v; asm volatile("ld.shared.v4.u32 {%0,%1,%2,%3}, [%4];" : "=r"(v.x), "=r"(v.y), "=r"(v.z), "=r"(v.w) : "r"(a) : "memory"); return v; }
__device__ __forceinline__ void sts128(uint32_t a, uint4 v) { asm volatile("st.shared.v4.u32 [%0], {%1,%2,%3,%4};" ::"r"(a), "r"(v.x), "r"(v.y), "r"(v.z), "r"(v.w) : "memory"); }
__device__ __forceinline__ int lds32(uint32_t a) { int v; asm volatile("ld.shared.u32 %0, [%1];" : "=r"(v) : "r"(a) : "memory"); return v; }
__device__ __forceinline__ void sts32(uint32_t a, int v) { asm volatile("st.shared.u32 [%0], %1;" ::"r"(a), "r"(v) : "memory"); }
__device__ __forceinline__ int atoms_add(uint32_t a, int v) { int r; asm volatile("atom.shared.add.u32 %0, [%1], %2;" : "=r"(r) : "r"(a), "r"(v) : "memory"); return r; }
__device__ __forceinline__ uint32_t ld_rlx(const void* p) { uint32_t v; asm volatile("ld.relaxed.gpu.global.u32 %0, [%1];" : "=r"(v) : "l"(p) : "memory"); return v; }
__device__ __forceinline__ void st_rlx(void* p, uint32_t v) { asm volatile("st.relaxed.gpu.global.u32 [%0], %1;" ::"l"(p), "r"(v) : "memory"); }
__device__ __forceinline__ void bulk(uint32_t dst, const void* g, int n, uint32_t bar) {
    asm volatile("cp.async.bulk.shared::cluster.global.mbarrier::complete_tx::bytes [%0], [%1], %2, [%3];" ::"r"(dst), "l"(g), "r"(n), "r"(bar) : "memory");
}
__device__ __forceinline__ void bulk_st(void* g, uint32_t src, int n) {
    asm volatile("cp.async.bulk.global.shared::cta.bulk_group [%0], [%1], %2;\ncp.async.bulk.commit_group;" ::"l"(g), "r"(src), "r"(n) : "memory");
}
__device__ __forceinline__ uint2 lds64(uint32_t a) { uint2 v; asm volatile("ld.shared.v2.u32 {%0,%1}, [%2];" : "=r"(v.x), "=r"(v.y) : "r"(a) : "memory"); return v; }
__device__ __forceinline__ void sts64(uint32_t a, uint32_t x, uint32_t y) { asm volatile("st.shared.v2.u32 [%0], {%1,%2};" ::"r"(a), "r"(x), "r"(y) : "memory"); }
__device__ __forceinline__ void tma3d(uint32_t dst, const CUtensorMap* m, int c2, uint32_t bar) {
    asm volatile("cp.async.bulk.tensor.3d.shared::cluster.global.mbarrier::complete_tx::bytes [%0], [%1, {%3, %3, %4}], [%2];"
                 ::"r"(dst), "l"(m), "r"(bar), "r"(0), "r"(c2) : "memory");
}
__device__ __forceinline__ void pf_l2(const void* g, int n) {
    asm volatile("{.reg .pred p; setp.gt.s32 p, %1, 0; @p cp.async.bulk.prefetch.L2.global [%0], %1;}" ::"l"(g), "r"(n) : "memory");
}
__device__ __forceinline__ void fence_async() { asm volatile("fence.proxy.async.shared::cta;" ::: "memory"); }
__device__ __forceinline__ uint64_t madw(uint32_t a, uint32_t b, uint64_t c) { uint64_t r; asm("mad.wide.u32 %0, %1, %2, %3;" : "=l"(r) : "r"(a), "r"(b), "l"(c)); return r; }
__device__ __forceinline__ uint32_t opaque(uint32_t v, int lane) { return __shfl_sync(0xffffffffu, v, lane); }
__device__ __forceinline__ void bar_sync(int id, int n) { asm volatile("bar.sync %0, %1;" ::"r"(id), "r"(n) : "memory"); }

__device__ __forceinline__ void wg_rs16(float* d, const uint32_t* a, uint64_t db, int sc) {
    asm volatile("{.reg .pred p; setp.ne.b32 p, %13, 0;\n"
                 "wgmma.mma_async.sync.aligned.m64n16k16.f32.bf16.bf16 {%0,%1,%2,%3,%4,%5,%6,%7}, {%8,%9,%10,%11}, %12, p, 1, 1, 0;}"
                 : "+f"(d[0]), "+f"(d[1]), "+f"(d[2]), "+f"(d[3]), "+f"(d[4]), "+f"(d[5]), "+f"(d[6]), "+f"(d[7])
                 : "r"(a[0]), "r"(a[1]), "r"(a[2]), "r"(a[3]), "l"(db), "r"(sc));
}
__device__ __forceinline__ void wg_ss48(float* d, uint64_t da, uint64_t db, int sc) {
    asm volatile("{.reg .pred p; setp.ne.b32 p, %26, 0;\n"
                 "wgmma.mma_async.sync.aligned.m64n48k16.f32.bf16.bf16 {%0,%1,%2,%3,%4,%5,%6,%7,%8,%9,%10,%11,%12,%13,%14,%15,%16,%17,%18,%19,%20,%21,%22,%23}, %24, %25, p, 1, 1, 1, 0;}"
                 : "+f"(d[0]), "+f"(d[1]), "+f"(d[2]), "+f"(d[3]), "+f"(d[4]), "+f"(d[5]), "+f"(d[6]), "+f"(d[7]),
                   "+f"(d[8]), "+f"(d[9]), "+f"(d[10]), "+f"(d[11]), "+f"(d[12]), "+f"(d[13]), "+f"(d[14]), "+f"(d[15]),
                   "+f"(d[16]), "+f"(d[17]), "+f"(d[18]), "+f"(d[19]), "+f"(d[20]), "+f"(d[21]), "+f"(d[22]), "+f"(d[23])
                 : "l"(da), "l"(db), "r"(sc));
}

__device__ __forceinline__ int warp_incl(int v) {
#pragma unroll
    for (int o = 1; o < 32; o <<= 1)
        asm volatile("{.reg .pred p; .reg .b32 u; shfl.sync.up.b32 u|p, %0, %1, 0, 0xffffffff; @p add.s32 %0, %0, u;}" : "+r"(v) : "r"(o));
    return v;
}
__device__ __forceinline__ void ldg128(uint32_t* r, const void* p, bool on) {
    asm volatile("{.reg .pred p; setp.ne.u32 p, %5, 0; @p ld.global.nc.v4.u32 {%0,%1,%2,%3}, [%4];}"
                 : "=r"(r[0]), "=r"(r[1]), "=r"(r[2]), "=r"(r[3]) : "l"(p), "r"((uint32_t)on));
}

struct Acc {
    uint32_t p00[4], p110[4], p10[3][4];
    float t01[4], m[3][4];
};

#define LF(m) ldsm4t(f[m], so + xa + m * 256)
#define LY() ldsm4(yb, so + ya)
#define LC() ldsm4(yb + 4, so + yc)
#define LN() ph = lds32(so + S_N)
#define ADV() { asm volatile("@lane0 mbarrier.arrive.shared::cta.b64 _, [%0];" ::"r"(so + S_EMPTY) : "memory"); \
                so = so == sm + O_RING + (NSLOT - 1) * SLOT ? sm + O_RING : so + SLOT; }
#define LA() asm volatile("{\n.reg .pred p, q;\n.reg .b64 s;\n.reg .f32 n;\nmov.b64 s, {0, %7};\nmbarrier.test_wait.shared::cta.b64 p, [%6], s;\n" \
                          "abs.f32 n, %7;\nsetp.gt.and.f32 q, n, 0f00000001, p;\nselp.u32 %4, 1, 0, p;\nselp.u32 %5, 1, 0, q;\n" \
                          "@p ldmatrix.sync.aligned.m8n8.x4.shared.b16 {%0,%1,%2,%3}, [%8];\n}" \
                          : "+r"(a[0]), "+r"(a[1]), "+r"(a[2]), "+r"(a[3]), "=r"(ok), "=r"(go) : "r"(so + S_FULL), "r"(ph), "r"(so + aa) : "memory")
#define RAD(p, s) { float c[4]; mma16z(c, wr[p], a[2 * s], a[2 * s + 1]); R[p][2 * s] = pack(c[0], c[1]); R[p][2 * s + 1] = pack(c[2], c[3]); }
#define MUL(n, x, y) (XS >> n & 1 ? hmul(y, x) : hmul(x, y))
#define FMA(n, x, y, z) (XS >> n & 1 ? hfma(y, x, z) : hfma(x, y, z))
#define ACC(n, x, y, z) z = F ? MUL(n, x, y) : FMA(n, x, y, z)
#define P00(i) ACC(0, f[0][i], R[0][i], A.p00[i ^ XA])
#define P10(k, i) ACC(1, f[1 + k][i], R[3][i], A.p10[k][i ^ XA])
#define S0(k, i) sd[i] = MUL(2, f[1 + k][i], yb[2 * k + (i >> 1)])
#define SD(k, i) sd[i] = FMA(2, f[1 + k][i], yb[2 * k + (i >> 1)], sd[i])
#define P110(i) ACC(3, sd[i], R[1][i], A.p110[i ^ XA])
#define TU(i) u[3][i ^ XU] = MUL(4, f[0][i], R[2][i])
#define TM() if (F) mma16z(A.t01, u[3], yb[6], yb[7]); else mma16(A.t01, u[3], yb[6], yb[7])
#define MU(k, i) u[k][i ^ XU] = MUL(5, f[1 + k][i], R[4][i])
#define MM(k) if (F) mma16z(A.m[k], u[k], yb[6], yb[7]); else mma16(A.m[k], u[k], yb[6], yb[7])
#define PK(v, h) pack(v[2 * (h)], v[2 * (h) + 1])
#define LM() { sts32(na + sof, mt); asm volatile("ld.shared.u16 %0, [%1];" : "=r"(mt) : "r"(so + ma) : "memory"); }
#define FY(k) if (k == 0) mma16z(y, A.p10[0], oh[0][0], oh[0][1]); else mma16(y, k < 3 ? A.p10[k % 3] : A.p00, oh[k][0], oh[k][1])
#define FZ(k) if (k == 0) mma16z(z, A.p110, oh[3][0], oh[3][1]); \
              else if (k == 1) { const uint32_t mp[4] = {PK(A.m[0], XA ^ XU), PK(A.m[0], 1 ^ XA ^ XU), PK(A.m[1], XA ^ XU), PK(A.m[1], 1 ^ XA ^ XU)}; mma16(z, mp, eb[0], eb[1]); } \
              else mma8(z, PK(A.m[2], XA ^ XU), PK(A.m[2], 1 ^ XA ^ XU), eb[2])
#define SX() stsm2t(fx + sof, PK(A.t01, XU), PK(A.t01, 1 ^ XU))
#define SY() stsm4t(fyz + sof, PK(y, XA), PK(y, 1 ^ XA), PK(z, XA), PK(z, 1 ^ XA))
#define X4(op) op(0); op(1); op(2); op(3)
#define Y4(op, k) op(k, 0); op(k, 1); op(k, 2); op(k, 3)
#define XA 1
#define XU 0
#define XS_R 63
#define SEQ_R LN(); LF(1); LF(3); LF(0); LF(2); LC(); RAD(1,0); RAD(1,1); RAD(2,0); RAD(0,0); RAD(0,1); RAD(2,1); RAD(3,0); P00(0); TU(0); \
    P10(0,0); P10(0,1); TU(2); TU(3); RAD(4,1); MU(2,2); MU(2,3); TU(1); TM(); P00(1); RAD(4,0); MU(2,0); MU(2,1); MU(0,0); MU(0,2); \
    RAD(3,1); P10(0,2); P10(0,3); LY(); ADV(); LA(); P00(2); MU(0,3); P00(3); MM(2); MU(0,1); MM(0); P10(2,0); P10(2,2); P10(2,3); P10(2,1); \
    P10(1,0); P10(1,1); P10(1,2); P10(1,3); MU(1,2); S0(2,0); SD(1,0); SD(0,0); P110(0); S0(2,1); SD(1,1); SD(0,1); P110(1); S0(2,2); \
    SD(1,2); SD(0,2); P110(2); MU(1,3); S0(2,3); SD(1,3); SD(0,3); P110(3); MU(1,0); MU(1,1); MM(1);
#define XS_F 0
#define SEQ_F LN(); LM(); LF(0); LC(); LF(1); LF(2); LF(3); LY(); ADV(); FY(0); FZ(0); FY(1); FZ(1); FY(2); FZ(2); FY(3); SX(); SY(); \
    RAD(0, 0); RAD(0, 1); RAD(1, 0); RAD(1, 1); RAD(2, 0); RAD(2, 1); RAD(3, 0); RAD(3, 1); RAD(4, 0); RAD(4, 1); LA(); \
    X4(P00); X4(TU); TM(); Y4(P10, 0); Y4(MU, 0); MM(0); Y4(P10, 1); Y4(MU, 1); MM(1); Y4(P10, 2); Y4(MU, 2); MM(2); \
    Y4(S0, 0); Y4(SD, 1); Y4(SD, 2); X4(P110);

__global__ void __launch_bounds__(NT, 1)
tp_kernel(const int4* __restrict__ dst, const int4* __restrict__ src, const char* __restrict__ rhat, Scratch* __restrict__ gs,
          const char* __restrict__ x, const char* __restrict__ ea, const __nv_bfloat16* __restrict__ eps, char* __restrict__ out,
          const __grid_constant__ CUtensorMap m_wr, const __grid_constant__ CUtensorMap m_w0, const __grid_constant__ CUtensorMap m_w1) {
    extern __shared__ __align__(1024) char smem_raw[];
    constexpr uint32_t sm = 1024;
    spin_check((uint32_t)__cvta_generic_to_shared(smem_raw) == sm ? 0 : 2 * SPIN_LIMIT);
    int t;
    asm volatile("mov.u32 %0, %%tid.x;" : "=r"(t));
    const int w = t >> 5, lane = t & 31, b = blockIdx.x;

    const int g = lane >> 2, q = lane & 3, mat = lane >> 3, r = lane & 7;
    const int e0 = b * CH + t * 8, ne = min(CH, NE - b * CH);
    const bool act = t * 8 < ne;
    uint32_t d[8];
#pragma unroll
    for (int k = 0; k < 2; k++) ldg128(d + 4 * k, dst + e0 / 4 + k, act);
    uint32_t tag = ld_rlx(&gs->epoch[b * 32]), epl;
    asm volatile("ld.global.nc.u16 %0, [%1];" : "=r"(epl) : "l"(eps + min(lane, 26)));
    if (t < 60) sts128(sm + O_BCNT + 16 * t, make_uint4(0, 0, 0, 0));
    if (t == NT - 1) {
#pragma unroll
        for (int i = 0; i < 4; i++) mbar_init(sm + O_WBA + 8 * i, 1);
        fence_async();
        mbar_expect(sm + O_WBC, ne * 10); mbar_expect(sm + O_WBA, 20480); mbar_expect(sm + O_WBB, 98304); mbar_expect(sm + O_WBD, 65536);
        spin_check(tag);
        bulk(sm + O_RH, rhat + b * (CH * 6), ne * 6, sm + O_WBC);
        bulk(sm + O_SRC, src + b * (CH / 4), ne * 4, sm + O_WBC);
        tma3d(sm + O_WR0, &m_wr, 0, sm + O_WBA);
        tma3d(sm + O_WR1, &m_wr, 5, sm + O_WBA);
        tma3d(sm + O_W0S, &m_w0, 0, sm + O_WBD);
    }
    if (t == 320) {
#pragma unroll
        for (int i = 0; i < NSLOT; i++) {
            sts128(sm + O_RING + i * SLOT + S_C + 64, make_uint4(0, 0, 0, 0));
            mbar_init(sm + O_RING + i * SLOT + S_FULL, 32); mbar_init(sm + O_RING + i * SLOT + S_EMPTY, 8);
        }
    }
#pragma unroll
    for (int k = 0; k < LZ; k++) sts128(sm + O_L + 16 * (t + k * NT), make_uint4(0, 0, 0, 0));
    if (t < 80) sts32(sm + O_NCNT + 4 * t, t <= NLOC ? 4 * t : 0);
    if (t < 100) sts32(sm + O_NODE + 4 * t, 0);
    uint32_t ba[8], rk[8];
    auto pfx = [&](int r0, int n) {
        if (n) pf_l2(x + (b * NLOC + r0) * 1024, min(n, NN - b * NLOC - r0) * 1024);
    };
    if (w < 10) bar_sync(1, 320);
    tag = (tag + 1) << 30;
    if (act) {
#pragma unroll
        for (int i = 0; i < 8; i++) {
            const uint32_t l = __umulhi(d[i], (uint32_t)((1ull << 32) / G + 1));
            ba[i] = d[i] * 4 - l * (4 * G);
            d[i] = l * 4 + (tag + ((e0 + i + 1) << 9) + 4);
            rk[i] = atoms_add(sm + O_BCNT + ba[i], 4);
        }
#pragma unroll
        for (int i = 0; i < 8; i++)
            asm volatile("{.reg .pred p; setp.lt.u32 p, %2, 124; @p st.shared.u32 [%0], %1;}"
                         ::"r"(sm + O_KT + ba[i] * 32 + ((ba[i] + rk[i]) & 127)), "r"(d[i]), "r"(rk[i]) : "memory");
    }
    TS(0);
    __syncthreads();
    {
        int v[5], sum = 0;
#pragma unroll
        for (int i = 0; i < 5; i++) { v[i] = lds32(sm + O_BCNT + 4 * (lane * 5 + i)); sum += v[i]; }
        int e = warp_incl(sum) - sum;
        if (w == 10) {
#pragma unroll
            for (int i = 0; i < 5; i++) {
                const int k = lane * 5 + i;
                if (k < G) sts32(sm + O_KT + k * 128 + ((k * 4 + 124) & 127), tag | v[i] << 10 | e >> 2);
                e += v[i];
            }
            __syncwarp();
            if (lane == 0) {
                fence_async();
                bulk_st(&gs->keys[b * (G * 32)], sm + O_KT, G * 128);
                pfx(0, PFA);
            }
        } else {
#pragma unroll
            for (int i = 0; i < 5; i++) { sts32(sm + O_BOFF + 4 * (lane * 5 + i), e); e += v[i]; }
        }
        __syncwarp();
    }
    TS(11);
    const uint32_t sw = (uint32_t)(((2 * (w & 3) + (mat & 1)) ^ r) * 16 + ((mat >> 1) * 8 + r) * 128);
    uint32_t wr[5][4];
    const uint32_t* kp = &gs->keys[(w * SEGW * G + b) * 32 + ((lane + b) & 31)];
    uint32_t kv[SEGW + 1], ho[SEGW + 1], nk[SEGW + 1], old;
    if (act) {
        uint32_t mx = 0;
#pragma unroll
        for (int i = 0; i < 8; i++) { mx = max(mx, rk[i]); ba[i] = rk[i] + lds32(sm + O_BOFF + ba[i]); }
        if (mx >= 124) {
#pragma unroll
            for (int i = 0; i < 8; i++)
                if (rk[i] >= 124) st_rlx(&gs->more[b * CH + (ba[i] >> 2)], d[i]);
        }
    }
    if (w < 8) {
        mbar_wait(sm + O_WBA, 0);
#pragma unroll
        for (int p = 0; p < 5; p++) {
            const int c = 2 * p + (w >> 2);
            ldsm4t(wr[p], sm + (c < 5 ? O_WR0 : O_WR1 - 5 * 2048) + c * 2048 + sw);
        }
    } else {
        const uint64_t xl = (uint64_t)(x - 1024 + r * 16) - (tag >> 6), al = (uint64_t)(ea - 32 + (lane & 1) * 16) - (tag >> 4);
        const uint64_t ml = (uint64_t)gs->list + lane * 8;
        const uint32_t row = 0x76b821a3u >> 4 * r & 15, row0 = 0xc5bfe0cbu >> 4 * r & 15;
        const uint32_t c[13] = {(uint32_t)xl, (uint32_t)(xl >> 32), (uint32_t)al, (uint32_t)(al >> 32), (uint32_t)ml, (uint32_t)(ml >> 32),
            mat * 2048u + (r ^ 2 * mat) * 16, mat * 2048u + 1024 + (r ^ 2 * mat ^ 1) * 16,
            S_A + (lane & 2) * 128u + g * 32 + ((lane ^ lane >> 4) & 1) * 16, S_C + (mat & 1 ? row : row0) * 16, lane & 1 ? 16u : 9u, lane & 30u,
            lane == 4 ? 0xffff0000u : 0u};
#pragma unroll
        for (int i = 0; i < 20; i++) wr[i >> 2][i & 3] = i < 13 ? opaque(c[i % 13], lane) : 0;
    }
    TS(21);
    mbar_wait(sm + O_WBC, 0);
    TS(22);
    if (act) {
        uint32_t s[8], y[12];
#pragma unroll
        for (int k = 0; k < 3; k++) *(uint4*)&y[4 * k] = lds128(sm + O_RH + t * 48 + k * 16);
#pragma unroll
        for (int k = 0; k < 2; k++) *(uint4*)&s[4 * k] = lds128(sm + O_SRC + t * 32 + k * 16);
#pragma unroll
        for (int i = 0; i < 8; i++) {
            const int k = 3 * i / 2;
            sts64(sm + O_OUT + ba[i] * 2, __byte_perm(y[k], s[i] + (tag >> 16) + 1, i & 1 ? 0x5432 : 0x5410),
                  i & 1 ? y[k + 1] : __byte_perm(y[k], y[k + 1], 0x5432));
        }
    }
    TS(12);
    if (w < 10) asm volatile("bar.arrive 4, 352;" ::: "memory");
    if (w == 11) {
        bar_sync(4, 352);
        if (lane == 0) { fence_async(); bulk_st(&gs->vals[b * CH], sm + O_OUT, ne * 8); pfx(PFA, PFB); }
        __syncwarp();
    }

    const uint32_t am = lane < 31 ? 511 : 0, none = tag | (320 + 4 * lane);
    auto check = [&]() {
        old = 0;
#pragma unroll
        for (int j = 0; j < SEGW; j++) {
            ho[j] = __shfl_sync(0xffffffffu, kv[j], 31);
            kv[j] = ho[j] >= (lane < 31 ? tag + ((lane + 1) << 12) : 0u) ? kv[j] : none;
            old |= kv[j] ^ tag;
        }
        return __any_sync(0xffffffffu, old >> 30);
    };
#pragma unroll
    for (int j = 0; j < SEGW; j++) kv[j] = ld_rlx(kp + j * (G * 32));
    TS(1);
    TV(19, 0);
    for (int it = 0; check(); it++) {
        spin_check(it);
        if (it == 0) TS(20);
        TV(19, (it + 1) * 100);
#pragma unroll
        for (int j = 0; j < SEGW; j++)
            if (__any_sync(0xffffffffu, (kv[j] ^ tag) >> 30)) kv[j] = ld_rlx(kp + j * (G * 32));
    }
    TS(3);
    kv[SEGW] = none; ho[SEGW] = 0;
    bool slow = false;
    const bool more = __any_sync(0xffffffffu, lane == 31 && (old & 0xfe0000));
    if (more) {
        int c = lane;
#pragma unroll
        for (int j = 0; j < SEGW; j++) {
            const int n = max((int)(ho[j] >> 12 & 0xfff) - 31, 0);
            if ((unsigned)c < (unsigned)n) ho[SEGW] = j * CH + (ho[j] & 0xfff) + 31 + c - lane;
            c -= n;
        }
        slow = lane == 31 && c < 0;
        if (c < 0 && lane < 31)
            for (int it = 0; ((kv[SEGW] = ld_rlx(&gs->more[w * SEGW * CH + lane + ho[SEGW]])) ^ tag) >> 30; it++) spin_check(it);
        __syncwarp();
    }
    uint32_t na_[SEGW + 1];
#pragma unroll
    for (int j = 0; j <= SEGW; j++) {
        na_[j] = (kv[j] & am) | (none & 511 & ~am);
        nk[j] = atoms_add(sm + O_NCNT + na_[j], 512);
    }
    auto visit = [&](auto f) {
#pragma unroll 1
        for (int j = 0; j < SEGW; j++) {
            const uint32_t* kl = &gs->keys[((w * SEGW + j) * G + b) * 32];
            const uint32_t h = ld_rlx(kl + ((31 + b) & 31));
#pragma unroll 1
            for (int i = lane; i < (h >> 12 & 0xfff); i += 32) {
                const int o = (w * SEGW + j) * CH + (h & 0xfff) + i;
                uint32_t k;
                int it = 0;
                do { k = ld_rlx(i < 31 ? kl + ((i + b) & 31) : &gs->more[o]); spin_check(it++); } while ((k ^ tag) >> 30);
                f(k, o, i);
            }
        }
    };
    slow = __syncthreads_or(slow);
    if (slow) {
        if (t < 80) sts32(sm + O_NCNT + 4 * t, t <= NLOC ? 4 * t : 0);
        __syncthreads();
        visit([&](uint32_t k, int, int) { atoms_add(sm + O_NCNT + (k & 511), 512); });
        __syncthreads();
    }
    TS(4);
    if (t == 352) pfx(PFA + PFB, PFC);
    uint64_t vp = (uint64_t)&gs->vals[w * SEGW * CH + lane], vv[SEGW + 1];
#pragma unroll
    for (int j = 0; j <= SEGW; j++) vv[j] = tag;
    auto ldv = [&](bool again) {
#pragma unroll
        for (int j = 0; j <= SEGW; j++)
            asm volatile("{.reg .pred p; setp.lt.u32 p, %2, 320; @p ld.relaxed.gpu.global.b64 %0, [%1];}" : "+l"(vv[j])
                         : "l"(madw(j < SEGW ? ho[j] & 0xfff : ho[j], 8, vp) + (j < SEGW ? j * CH * 8 : 0)),
                           "r"(again ? (((uint32_t)vv[j] ^ tag) >> 30 ? 0 : 320) : na_[j]) : "memory");
    };
    if (w < 10) {
        const uint32_t key = lds32(sm + O_NCNT + 4 + (t & ~3));
        uint4 k[5];
#pragma unroll
        for (int i = 0; i < 5; i++) k[i] = lds128(sm + O_NCNT + q * 80 + i * 16);
        uint32_t c[4] = {0, 0, 0, 0};
#pragma unroll
        for (int i = 0; i < 5; i++) { c[0] += (key - k[i].x) >> 31; c[1] += (key - k[i].y) >> 31; c[2] += (key - k[i].z) >> 31; c[3] += (key - k[i].w) >> 31; }
        int rank = c[0] + c[1] + c[2] + c[3];
        rank += __shfl_xor_sync(0xffffffffu, rank, 1);
        rank += __shfl_xor_sync(0xffffffffu, rank, 2);
        if (ASC && rank < 2 * NPRIV) rank = (2 * NPRIV - 1 - rank) ^ 1;
        if (t < NLOC * 4) sts32(sm + O_SORT + 4 * rank, key);
    }
    __syncthreads();
    TS(2);
    const bool on = lane < NLOC / 4;
    const uint4 k4 = lds128(sm + O_SORT + 16 * (on ? lane : 0));
    const uint32_t ks[4] = {k4.x, k4.y, k4.z, k4.w};
    const int n0 = on ? max(1u, (ks[0] + 3584) >> 12) : 0, n1 = on ? max(1u, (ks[2] + 3584) >> 12) : 0;
    const int u2 = warp_incl(n0 + n1), u1 = u2 - n1, u0 = u1 - n0;
    const int total = __shfl_sync(0xffffffffu, u2, 31);
    slow |= total > CAPT;
    int gbase = b * CAPT + 1;
    if (on) {
#pragma unroll
        for (int i = 0; i < 4; i++) {
            const int a = ks[i] & 511, node = a * (G / 4) - G + b, o = (i >> 1 ? u1 : u0) * 256 + (i & 1) * 16;
            const uint32_t mk = (node < NN ? node + 1 : 0) + ((i >> 1 ? n1 : n0) << 16);
            sts64(sm + O_NOFF + 2 * a, o - (a >> 4), mk + a * 16);
            if (!slow) sts32(sm + O_L + 4 + o, mk);
        }
    }
    __syncwarp();
    if (!slow) {
        uint32_t mk[SEGW + 1];
        TS(13);
        if (t == 352) { pfx(PFA + PFB + PFC, PFD); asm volatile("cp.async.bulk.wait_group.read 0;" ::: "memory"); }
        ldv(false);
#pragma unroll
        for (int j = 0; j <= SEGW; j++) {
            const uint2 o = lds64(sm + O_NOFF + 2 * na_[j]);
            mk[j] = o.y - nk[j] * 16; nk[j] = o.x + (nk[j] >> 4);
        }
        for (int it = 0;; it++) {
            old = 0;
#pragma unroll
            for (int j = 0; j <= SEGW; j++) old |= (uint32_t)vv[j] ^ tag;
            if (!__any_sync(0xffffffffu, old >> 30)) break;
            spin_check(it);
            vp = __shfl_sync(0xffffffffu, vp, lane);
            ldv(true);
        }
#pragma unroll
        for (int j = 0; j <= SEGW; j++)
            asm volatile("{.reg .pred p; setp.ne.u32 p, %3, %5; @p st.shared.v4.u32 [%0], {%1,%2,%3,%4};}"
                         ::"r"(sm + O_L + nk[j]), "r"(kv[j]), "r"(mk[j]), "r"((uint32_t)vv[j]), "r"((uint32_t)(vv[j] >> 32)), "r"(tag) : "memory");
        if (na_[SEGW] < 320) gs->more[w * SEGW * CH + lane + ho[SEGW]] = 0;
    } else {
        int so = 0;
#pragma unroll
        for (int j = 0; j < SEGW; j++) so += ho[j] & 0xfff;
        if (lane == 0) atoms_add(sm + O_SUM, so);
        if (t == 352) asm volatile("cp.async.bulk.wait_group.read 0;" ::: "memory");
        __syncthreads();
        gbase = TBIG + (lds32(sm + O_SUM) >> 3) + (NLOC + 5) * b;
        auto put = [&](uint32_t k, uint64_t e, uint32_t a, int rank) {
            const uint2 o = lds64(sm + O_NOFF + 2 * a);
            gs->list[gbase * 16 + ((o.x + (a >> 4)) >> 4) + rank * 2] = make_uint4(k, o.y - a * 16 - (rank << 13), e, e >> 32);
        };
        visit([&](uint32_t k, int o, int i) {
            uint64_t e;
            int it = 0;
            do {
                asm volatile("ld.relaxed.gpu.global.b64 %0, [%1];" : "=l"(e) : "l"(&gs->vals[o]) : "memory");
                spin_check(it++);
            } while (((uint32_t)e ^ tag) >> 30);
            if (i >= 31) gs->more[o] = 0;
            put(k, e, k & 511, atoms_add(sm + O_NCUR + (k & 511), 1));
        });
#pragma unroll 1
        for (int i = 0; i < 4; i++) {
            const uint32_t k = i == 0 ? ks[0] : i == 1 ? ks[1] : i == 2 ? ks[2] : ks[3];
#pragma unroll 1
            for (int p = (k >> 9) + w; p < (i >> 1 ? n1 : n0) * 8; p += NT / 32) put(0, 0, k & 511, p);
        }
        __threadfence();
    }
    __syncthreads();
    TS(5);

    if (w >= 8) {
        asm volatile("setmaxnreg.dec.sync.aligned.u32 " STR(PREG) ";");
        const int h = __reduce_max_sync(0xffffffffu, w & 3);
        gbase = __reduce_max_sync(0xffffffffu, gbase);
        int pos = gbase + h, end = gbase + __reduce_max_sync(0xffffffffu, lane == (NPRIV - 1) / 2 ? (NPRIV & 1 ? u1 : u2) : 0);
        const uint32_t ring = sm + O_RING;
        const uint64_t xl = wr[0][0] | (uint64_t)wr[0][1] << 32, al = wr[0][2] | (uint64_t)wr[0][3] << 32, ml = wr[1][0] | (uint64_t)wr[1][1] << 32;
        const uint32_t xoff[2] = {wr[1][2], wr[1][3]}, aoff = wr[2][0], coff = wr[2][1], sh = wr[2][2], ial = wr[2][3], sel = wr[3][0];
        auto lde = [&](uint2& e, int p) {
            asm volatile("{.reg .pred p; setp.gt.s32 p, %3, 0; @p ld.relaxed.gpu.global.v2.u32 {%0,%1}, [%2];}" : "+r"(e.x), "+r"(e.y) : "l"(madw(p, 256, ml)), "r"(p) : "memory");
        };
        uint2 e0[3] = {};
#pragma unroll
        for (int k = 0; k < 3; k++) {
            e0[k] = lds64(sm + O_L - 2048 + k * 1024 + t * 8);
            lde(e0[k], slow ? pos + 4 * k : 0);
        }
        if (h == 3) fence_async();
        pos += 4;

        int ev = 0, state = -2, tk = 0, nr = 0;
        uint32_t inf = 0;
        int ii = 0;
        auto take = [&]() {
            int v = 0;
            asm volatile("{.reg .pred p; setp.eq.s32 p, %2, 0; @p atom.relaxed.gpu.global.add.u32 %0, [%1], 1;}" : "+r"(v) : "l"(&gs->ticket), "r"(lane) : "memory");
            return v;
        };
        auto resolve = [&]() {
            const int k = __reduce_max_sync(0xffffffffu, tk);
            inf = tag;
            if (k < G * NPOOL) { const int l = k / G; ii = (k - l * G) * NPOOL + l; inf = ld_rlx(&gs->info[ii]);
                tk = (STAG) && ((NPRIV + 1 + nr + (STAG)) & 7) == 0 && k >= G * NPOOL - THETA ? G * NPOOL : take(); }
        };
        uint32_t so = ring + h * SLOT, ph = 0x80000000u;
        uint32_t spins = 0;
        asm volatile(".reg .pred z<5>;");
        while (true) {
            const uint2 e = e0[0];
            const uint32_t o = e.x >> sh, id = __shfl_sync(0xffffffffu, o, ial);
            uint32_t s[4];
#pragma unroll
            for (int j = 0; j < 4; j++) s[j] = __shfl_sync(0xffffffffu, o, 2 * j + 1, 8);
            const uint32_t nx = so == ring + (NSLOT - 1) * SLOT ? ph : ph ^ 0x80000000u, ey = (e.y & ~sel) | (nx & sel);
            const uint64_t ga = madw(id, 32, al);
            uint64_t gx[4];
#pragma unroll
            for (int j = 0; j < 4; j++) gx[j] = madw(s[j], 1024, xl);
            const uint32_t da = so + aoff, dx[2] = {so + xoff[0], so + xoff[1]}, dc = so + coff;
            asm volatile("setp.eq.u32 z0, %0, 0;\nsetp.eq.u32 z1, %1, 0;\nsetp.eq.u32 z2, %2, 0;\nsetp.eq.u32 z3, %3, 0;\nsetp.eq.u32 z4, %4, 0;\n"
                         PFI
                         ::"r"(NULLP(s[0])), "r"(NULLP(s[1])), "r"(NULLP(s[2])), "r"(NULLP(s[3])), "r"(id), "l"(ga), "r"(da), "r"(dx[0]), "r"(dx[1]), "r"(dc));
            lde(e0[0], state < 0 ? 0 : pos);
            asm volatile("{\n.reg .pred p;\n.reg .b64 s;\nmov.b64 s, {0, %2};\n"
                         "LOOP:\nmbarrier.try_wait.shared::cta.b64 p, [%1], s;\n@p bra DONE;\n"
                         "add.u32 %0, %0, 1;\nsetp.gt.u32 p, %0, %3;\n@p trap;\nbra LOOP;\nDONE:\n}"
                         : "+r"(spins) : "r"(so + S_EMPTY), "r"(ph), "n"(SPIN_LIMIT) : "memory");
            asm volatile("cp.async.cg.shared.global [%0], [%1], 16, z4;" ::"r"(da), "l"(ga) : "memory");
#define ROW(j) _Pragma("unroll") for (int k = 0; k < 8; k++) \
                asm volatile("cp.async.cg.shared.global [%0], [%1], 16, z" #j ";" ::"r"(dx[j >> 1] + (j & 1) * 8192 + k * 128), "l"(gx[j] + k * 128) : "memory")
            X4(ROW);
            stsm2t(dc, e.x, ey);
            asm volatile("cp.async.mbarrier.arrive.noinc.shared::cta.b64 [%0];" ::"r"(so + S_FULL) : "memory");
            const bool wrap = NSLOT == 5 ? so != ring : so >= ring + (NSLOT - 4) * SLOT;
            ph ^= wrap ? 0x80000000u : 0u;
            so = wrap ? so - (NSLOT - 4) * SLOT : so + 4 * SLOT;
            pos += 4;
            if (pos >= ev) {
                if (state < 0) {
                    e0[0] = e0[1]; e0[1] = e0[2];
                    if (state == -2) {
                        if (h == 0) TSW(24);
                        if (h == 3) TSW(25);
                        if (h < 3) asm volatile("bar.arrive 7, %0;" ::"n"(NT) : "memory");
                        else {
                            bar_sync(7, NT);
                            if (lane == 0) {
                                if (!slow) bulk_st(gs->list + gbase * 16, sm + O_L, total * 256);
                                asm volatile("cp.async.bulk.wait_group.read 0;" ::: "memory");
                            }
                            __syncwarp();
                            if (lane == 0) {
                                for (int j = 0; j < 4; j++) tma2d(sm + O_W1 + j * 24576, &m_w1, 64 * (j >> 1), 192 * (j & 1), sm + O_WBB);
                            }
                            __syncwarp();
                        }
                        state = -1;
                    } else {
                        if (h == 3) {
                            if (lane == 0) asm volatile("cp.async.bulk.wait_group 0;\nfence.proxy.async;" ::: "memory");
                            __syncwarp();
                            if (on && 2 * lane >= NPRIV) st_rlx(&gs->info[b * NPOOL + 2 * lane - NPRIV], tag | (gbase + u0) << 12 | n0);
                            if (on && 2 * lane + 1 >= NPRIV) st_rlx(&gs->info[b * NPOOL + 2 * lane + 1 - NPRIV], tag | (gbase + u1) << 12 | n1);
                        }
                        bar_sync(6, 128);
                        ev = h ? end : end - 12; state = h ? 2 : 0;
                    }
                } else if (state == 0) { ev = end - 6; state = 1; tk = take(); }
                else if (state == 1) { resolve(); ev = end; state = 2; }
                else {
                    if (state == 3) break;
                    do {
                        const uint32_t mb = sm + O_MB + (nr & 31) * 8;
                        uint32_t rg;
                        nr++;
                        if (h == 0) {
                            for (int it = 0; (rg = __reduce_max_sync(0xffffffffu, inf ^ tag)) >> 30; it++) { spin_check(it); inf = ld_rlx(&gs->info[ii]); }
                            asm volatile("st.release.cta.shared.b64 [%0], %1;" ::"r"(mb), "l"(rg | (uint64_t)nr << 32) : "memory");
                            if (rg) resolve();
                        } else {
                            uint64_t m;
                            for (int it = 0;; it++) {
                                asm volatile("ld.acquire.cta.shared.b64 %0, [%1];" : "=l"(m) : "r"(mb) : "memory");
                                if (__all_sync(0xffffffffu, (int)(m >> 32) == nr)) break;
                                spin_check(it);
                            }
                            rg = __reduce_max_sync(0xffffffffu, (uint32_t)m);
                        }
                        pos = rg ? (int)(rg >> 12) + pos - end : 0;
                        end = rg ? (rg >> 12) + (rg & 0xfff) : 1;
                        state = rg ? 2 : 3;
                    } while (pos >= end);
                    ev = end;
                }
            }
        }
        mbar_wait31(so + S_EMPTY, ph);
        TSW(8 + (h & 1));
        if (lane == 0) sts32(so + S_N, 0);
        mbar_arrive(so + S_FULL);
        if (t == 256) {
            gs->epoch[b * 32] = (tag >> 30) % 3;
            if (atomicInc(&gs->done, G - 1) == G - 1) gs->ticket = 0;
        }
        asm volatile("cp.async.wait_all;" ::: "memory");
    } else {
        asm volatile("setmaxnreg.inc.sync.aligned.u32 " STR(CREG) ";");
        const uint32_t xa = opaque(((mat >> 1) * 8 + r) * 1024 + (w >> 2) * 128 + (((2 * (w & 3) + (mat & 1)) ^ r) * 16), lane);
        const uint32_t aa = opaque(S_A + ((mat >> 1) * 8 + r) * 32 + (((mat & 1) ^ (r >> 2)) * 16), lane);
        const uint32_t ya = opaque(S_C + (mat & 1) * 80 + (mat >> 1) * 16, lane);
        const uint32_t yc = opaque(S_C + (mat < 2 ? mat * 80 + 32 : (r >> 2) == (mat & 1) && q < 3 ? (mat & 1) * 80 + q * 16 : 64), lane);
        const uint32_t ma = opaque(S_C + 48 + (mat & 1) * 80, lane), na = opaque(sm + O_NODE + mat * 4, lane);
        const uint32_t pw = sm + O_P + w * PW;
        const uint32_t fx = opaque((q < 3 ? pw + P_1P0 + 2 * q * PSBO + (mat & 1) * 128 : sm + O_TRASH + ((pw - sm - O_TRASH + 96) & 127)) + (r >> 2) * PSBO, lane);
        const uint32_t fyz = opaque(pw + (q < 3 ? (mat < 2 ? P_1P1 : P_1P2) + 2 * q * PSBO : mat < 2 ? P_0P0 : P_0P1) + (mat & 1) * 128 + (r >> 2) * PSBO, lane);
        uint32_t oh[4][2];
#pragma unroll
        for (int c = 0; c < 8; c++) oh[c & 3][c >> 2] = opaque(g == c ? 0x3F803F80u : 0u, lane);
        uint32_t eb[3];
#pragma unroll
        for (int k = 0; k < 3; k++) {
            const int i = (g & 3) * 9 + (q & 1) * 6 + k;
            const uint32_t lo = __shfl_sync(0xffffffffu, epl, i), hi = __shfl_sync(0xffffffffu, epl, i + 3);
            eb[k] = (g & 3) < 3 && (q >> 1) == (g >> 2) ? (q & 1 ? lo : lo | hi << 16) : 0u;
        }
        asm volatile(".reg .pred lane0;\nsetp.eq.u32 lane0, %0, 0;" ::"r"(lane));
        uint32_t w0[16][4];
        mbar_wait(sm + O_WBD, 0);
#pragma unroll
        for (int k = 0; k < 16; k++) ldsm4t(w0[k], sm + O_W0S + (w >> 2) * 32768 + k * 2048 + sw);
        bar_sync(7, NT);
        TS(6);
        Acc A;
#pragma unroll
        for (int i = 0; i < 4; i++) { A.p00[i] = A.p110[i] = A.p10[0][i] = A.p10[1][i] = A.p10[2][i] = 0; A.t01[i] = A.m[0][i] = A.m[1][i] = A.m[2][i] = 0.f; }
        uint32_t room = 144 - (STAG) * 16;
        uint32_t so = sm + O_RING, ph, a[4], ok, go, mt = 0;
        mbar_wait(so + S_FULL, 0);
        ldsm4(a, so + aa);
        TS(7);
        while (true) {
            {
                constexpr int F = 1, XS = XS_F;
                uint32_t yb[8], f[4][4], R[5][4], u[4][4], sd[4];
                float y[4], z[4];
                const uint32_t sof = room & 112;
                SEQ_F
                room -= 16;
            }
            if (!(go && room)) {
                const uint32_t pu = __reduce_max_sync(0xffffffffu, ph);
                if (!room || !pu) {
                    asm volatile("fence.proxy.async.shared::cta;" ::: "memory");
                    mbar_wait(sm + O_WBB, 0);
                    bar_sync(1, 256);
                    float d0[8], d1[24];
                    const uint32_t wg = __reduce_max_sync(0xffffffffu, w >> 2);
                    const uint64_t db = (uint64_t)((sm + O_P) >> 4) | (8ull << 16) | ((uint64_t)(PSBO / 16) << 32);
                    const uint32_t da = ((sm + O_W1) >> 4 | 1 << 16) + wg * 3072;
                    asm volatile("wgmma.fence.sync.aligned;" ::: "memory");
#pragma unroll
                    for (int k = 0; k < 16; k++) wg_rs16(d0, w0[k], db + (((k & 7) * PW + ((k >> 3) ? P_0P1 : P_0P0)) >> 4), k);
                    asm volatile("wgmma.commit_group.sync.aligned;" ::: "memory");
#pragma unroll
                    for (int k = 0; k < 24; k++)
                        wg_ss48(d1, (da + k * 128) | (64ull << 32) | (1ull << 62), db + (((k & 7) * PW + ((k >> 3) == 0 ? P_1P0 : (k >> 3) == 1 ? P_1P1 : P_1P2)) >> 4), k);
                    asm volatile("wgmma.commit_group.sync.aligned;" ::: "memory");
                    const uint2 n0 = lds64(sm + O_NODE + mat * 16), n1 = lds64(sm + O_NODE + 64 + mat * 16);
                    const bool v0 = (mat * 16 - 16 & 112) >= room, v1 = mat * 16 + 48 >= room;
                    const uint32_t nd[4] = {v0 ? n0.x : 0, v1 ? n1.x : 0, v0 ? n0.y : 0, v1 ? n1.y : 0};
                    const uint64_t op = (uint64_t)(out - 1024 + (w & 3) * 256 + (w >> 2) * 128 + r * 16);
                    uint64_t oa[4];
#pragma unroll
                    for (int it = 0; it < 4; it++) oa[it] = madw(nd[it], 1024, op);
                    uint32_t sg = sm + O_P + (w & 4) * PW + ((mat >> 1) * 8 + r) * 128 + (((2 * (w & 3) + (mat & 1)) ^ r) * 16);
                    uint32_t sl = pw + mat * 128 + (r ^ mat) * 16, sl2 = pw + 512 + mat * 128 + (r ^ mat ^ 4) * 16;
                    asm volatile("wgmma.wait_group.sync.aligned 1;" ::: "memory");
#pragma unroll
                    for (int i = 0; i < 8; i++) asm volatile("" : "+f"(d0[i])::"memory");
                    uint32_t o[4][4], chk = sg & sl & sl2;
                    float gt[8];
#pragma unroll
                    for (int i = 0; i < 8; i++) {
                        asm("ex2.approx.ftz.f32 %0, %1;" : "=f"(gt[i]) : "f"(d0[i] * -1.4426950408889634f));
                        asm("rcp.approx.ftz.f32 %0, %1;" : "=f"(gt[i]) : "f"(gt[i] + 1.f));
                        chk &= __float_as_uint(gt[i]);
                    }
#pragma unroll
                    for (int i = 0; i < 4; i++) { o[0][i] = pack(d0[2 * i], d0[2 * i + 1]); chk &= o[0][i] & (uint32_t)(oa[i] >> 32); }
                    sts32(sm + O_TRASH, chk);
                    asm volatile("wgmma.wait_group.sync.aligned 0;" ::: "memory");
#pragma unroll
                    for (int i = 0; i < 24; i++) asm volatile("" : "+f"(d1[i])::"memory");
                    bar_sync(1, 256);
#pragma unroll
                    for (int i = 0; i < 4; i++)
#pragma unroll
                        for (int j = 0; j < 3; j++) o[1 + j][i] = pack(d1[8 * j + 2 * i] * gt[2 * i], d1[8 * j + 2 * i + 1] * gt[2 * i + 1]);
#pragma unroll
                    for (int j = 0; j < 4; j++) stsm4t(sg + j * PW, o[j][0], o[j][1], o[j][2], o[j][3]);
                    bar_sync(2 + wg, 128);
                    uint4 v[4];
#pragma unroll
                    for (int it = 0; it < 4; it++) v[it] = lds128((it & 1 ? sl2 : sl) + (it >> 1) * 1024);
#pragma unroll
                    for (int it = 0; it < 4; it++)
                        asm volatile("{.reg .pred p; setp.ne.u32 p, %5, 0; @p st.global.v4.u32 [%0], {%1,%2,%3,%4};}"
                                     ::"l"(oa[it]), "r"(v[it].x), "r"(v[it].y), "r"(v[it].z), "r"(v[it].w), "r"(nd[it]) : "memory");
                    __syncwarp();
                    room = 128;
                    if (!pu) break;
                }
                if (!ok) { mbar_wait31(so + S_FULL, pu); ldsm4(a, so + aa); }
                if (!(pu & 0xfffe)) continue;
            }
            while (true) {
                do {
                    constexpr int F = 0, XS = XS_R;
                    uint32_t yb[8], f[4][4], R[5][4], u[4][4], sd[4];
                    SEQ_R
                } while (go);
                if (ok) break;
                const uint32_t pu = __reduce_max_sync(0xffffffffu, ph);
                mbar_wait31(so + S_FULL, pu); ldsm4(a, so + aa);
                if (!(pu & 0xfffe)) break;
            }
        }
        TS(10);
    }
}

typedef CUresult (*EncFn)(CUtensorMap*, CUtensorMapDataType, cuuint32_t, void*, const cuuint64_t*, const cuuint64_t*,
                          const cuuint32_t*, const cuuint32_t*, CUtensorMapInterleave, CUtensorMapSwizzle,
                          CUtensorMapL2promotion, CUtensorMapFloatOOBfill);

void make_map(EncFn fn, CUtensorMap* m, void* p, int rows, int cols, int brows, int rank, int bblk, CUtensorMapSwizzle swz) {
    cuuint64_t dims[3] = {(cuuint64_t)(rank == 3 ? 64 : cols), (cuuint64_t)rows, (cuuint64_t)cols / 64}, strides[2] = {(cuuint64_t)cols * 2, 128};
    cuuint32_t box[3] = {64, (cuuint32_t)brows, (cuuint32_t)bblk}, es[3] = {1, 1, 1};
    fn(m, CU_TENSOR_MAP_DATA_TYPE_BFLOAT16, rank, p, dims, strides, box, es, CU_TENSOR_MAP_INTERLEAVE_NONE,
       swz, CU_TENSOR_MAP_L2_PROMOTION_NONE, CU_TENSOR_MAP_FLOAT_OOB_FILL_NONE);
}

}

extern "C" void kernel_launch(void* const* d_in, const int* in_sizes, int n_in, void* d_out, int out_size) {
    static EncFn enc = nullptr;
    static void* scratch = nullptr;
    if (!enc) {
        void* fn = nullptr;
        cudaDriverEntryPointQueryResult qr;
        cudaGetDriverEntryPoint("cuTensorMapEncodeTiled", &fn, cudaEnableDefault, &qr);
        enc = (EncFn)fn;
        cudaGetSymbolAddress(&scratch, g_scratch);
        cudaFuncSetAttribute(tp_kernel, cudaFuncAttributeMaxDynamicSharedMemorySize, SMEM_BYTES);
    }
    CUtensorMap m_wr, m_w0, m_w1;
    make_map(enc, &m_wr, d_in[5], 16, 640, 16, 3, 5, CU_TENSOR_MAP_SWIZZLE_128B);
    make_map(enc, &m_w0, d_in[6], 256, 128, 256, 3, 2, CU_TENSOR_MAP_SWIZZLE_128B);
    make_map(enc, &m_w1, d_in[7], 384, 128, 192, 2, 1, CU_TENSOR_MAP_SWIZZLE_128B);
    tp_kernel<<<G, NT, SMEM_BYTES>>>((const int4*)d_in[4], (const int4*)d_in[3], (const char*)d_in[1], (Scratch*)scratch,
                                     (const char*)d_in[0], (const char*)d_in[2], (const __nv_bfloat16*)d_in[8], (char*)d_out,
                                     m_wr, m_w0, m_w1);
}
```

```cpp
#include <cuda_runtime.h>
#include <cuda_bf16.h>
#include <cuda.h>
#include <stdint.h>
#include <stddef.h>

namespace {

constexpr int NN = 10000;
constexpr int NE = 320000;
constexpr int G = 132;
constexpr int NT = 384;
constexpr int CH = 2432;
constexpr int NLOC = (NN + G - 1) / G;
#define NPOOL 4
constexpr int NPAIR = NLOC / 2, NPRIV = NPAIR - NPOOL;
constexpr int SEGW = 11;

#define NSLOT 6
#define PFA 16
#define PFB 20
#define PFC 20
#define PFD 20
#define STAG (b & 7)
#define ASC (b & 1)
#define THETA G
#define PFI "@!z4 prefetch.global.L2 [%5];"
#define NULLP(v) v
#define CREG 224
#define PREG 56
#define STR2(x) #x
#define STR(x) STR2(x)

constexpr int S_A = 16384, S_C = S_A + 512, S_FULL = S_C + 144, S_EMPTY = S_FULL + 8, S_N = S_C + 160, SLOT = S_C + 256;

constexpr int PSBO = 272;
constexpr int PB1 = 5 * PSBO + 256, PB0 = PSBO + 256;
constexpr int P_1P0 = 0, P_1P1 = PB1, P_0P1 = 2 * PB1, P_0P0 = P_0P1 + PB0, P_1P2 = P_0P0 + PB0;
constexpr int PW = P_1P2 + PB1;

constexpr int up1k(int a) { return (a + 1023) / 1024 * 1024; }
constexpr int O_W1 = 0;
constexpr int O_P = 81920;
constexpr int O_RING = O_P + 8 * PW;
constexpr int O_WBA = O_RING + 6 * SLOT, O_WBB = O_WBA + 8, O_WBC = O_WBA + 16, O_WBD = O_WBA + 24, O_TRASH = O_WBA + 32, O_NODE = O_WBA + 48;
constexpr int O_SUM = O_NODE + 128, O_MB = O_SUM + 16;
constexpr int SMEM_BYTES = O_MB + 128;
constexpr int CAPT = 192;
constexpr int O_L = 0, LZ = CAPT * 256 / (NT * 16), O_W0S = O_L + CAPT * 256, O_OUT = O_W0S + 65536, O_SRC = O_OUT + CH * 8;
constexpr int O_KT = O_RING + SLOT, O_RH = O_RING + 2 * SLOT;
constexpr int O_WR0 = up1k(O_RING + 3 * SLOT), O_WR1 = up1k(O_RING + 4 * SLOT), O_W1S = up1k(O_RING + 5 * SLOT);
constexpr int O_BCNT = O_WR0 + 10240, O_NCUR = O_BCNT + 640, O_NCNT = O_NCUR + 320;
constexpr int O_BOFF = O_NCNT + 512, O_SORT = O_BOFF + 640, O_NOFF = O_SORT + 320;
constexpr int TBIG = G * CAPT + 8, NTILE = TBIG + NE / 8 + G * (NLOC + 5);
static_assert(SMEM_BYTES <= 232448 && CAPT % 16 == 0 && NTILE < (1 << 18), "smem");
static_assert(LZ * NT * 16 == CAPT * 256 && O_W0S % 1024 == 0 && O_OUT <= O_RING && O_SRC + CH * 4 <= O_RING + S_C && G * 128 <= S_C, "staging");
static_assert(O_NOFF + 1024 <= O_RING + 3 * SLOT + S_C && O_W1S + 16384 <= O_RING + 5 * SLOT + S_C, "staging");
static_assert(O_RING % 128 == 0 && SLOT % 128 == 0 && O_W0S <= O_P && O_NOFF % 8 == 0, "layout");
static_assert(G * CH >= NE && NE % 8 == 0 && CH < 4096 && CH / 8 <= 320 && NE < (1 << 21), "chunks");
static_assert(SEGW * (NT / 32) == G && G <= 160 && G % 4 == 0, "segments");
static_assert(NLOC % 4 == 0 && NLOC < 80 && NLOC * 4 <= 320 && NN < 0x3fff && NE / 8 < 0xbfff && NPRIV >= 30, "scan width");

struct __align__(128) Scratch {
    uint32_t keys[G * G * 32];
    uint64_t vals[G * CH];
    uint32_t more[G * CH];
    uint32_t epoch[G * 32];
    uint32_t info[G * NPOOL];
    unsigned done, pad0[31], ticket, pad1[31 + 32 - G * NPOOL % 32];
    uint4 list[NTILE * 16];
};
static_assert(offsetof(Scratch, list) % 128 == 0, "list");
__device__ Scratch g_scratch;
#define TS(i)
#define TSW(i)
#define TV(i, v)

constexpr int SPIN_LIMIT = 1 << 24;

__device__ __forceinline__ void mbar_init(uint32_t a, int c) { asm volatile("mbarrier.init.shared::cta.b64 [%0], %1;" ::"r"(a), "r"(c) : "memory"); }
__device__ __forceinline__ void mbar_expect(uint32_t a, int b) { asm volatile("mbarrier.arrive.expect_tx.shared::cta.b64 _, [%0], %1;" ::"r"(a), "r"(b) : "memory"); }
__device__ __forceinline__ void mbar_arrive(uint32_t a) { asm volatile("mbarrier.arrive.shared::cta.b64 _, [%0];" ::"r"(a) : "memory"); }
__device__ __forceinline__ void mbar_wait(uint32_t a, uint32_t ph) {
    asm volatile("{\n.reg .pred p, q;\n.reg .u32 it;\n"
                 "mbarrier.try_wait.parity.shared::cta.b64 p, [%0], %1;\n"
                 "@p bra DONE;\n"
                 "mov.u32 it, 0;\n"
                 "LOOP:\n"
                 "mbarrier.try_wait.parity.shared::cta.b64 p, [%0], %1;\n"
                 "@p bra DONE;\n"
                 "add.u32 it, it, 1;\n"
                 "setp.gt.u32 q, it, %2;\n"
                 "@q trap;\n"
                 "bra LOOP;\n"
                 "DONE:\n}" ::"r"(a), "r"(ph), "n"(SPIN_LIMIT) : "memory");
}
__device__ __forceinline__ void mbar_wait31(uint32_t a, uint32_t ph) {
    asm volatile("{\n.reg .pred p, q;\n.reg .u32 it;\n.reg .b64 s;\n"
                 "mov.b64 s, {0, %1};\n"
                 "mbarrier.try_wait.shared::cta.b64 p, [%0], s;\n"
                 "@p bra DONE;\n"
                 "mov.u32 it, 0;\n"
                 "LOOP:\n"
                 "mbarrier.try_wait.shared::cta.b64 p, [%0], s;\n"
                 "@p bra DONE;\n"
                 "add.u32 it, it, 1;\n"
                 "setp.gt.u32 q, it, %2;\n"
                 "@q trap;\n"
                 "bra LOOP;\n"
                 "DONE:\n}" ::"r"(a), "r"(ph), "n"(SPIN_LIMIT) : "memory");
}
__device__ __forceinline__ void spin_check(int it) {
    asm volatile("{\n.reg .pred q;\nsetp.gt.s32 q, %0, %1;\n@q trap;\n}" ::"r"(it), "n"(SPIN_LIMIT));
}
__device__ __forceinline__ void ldsm4(uint32_t* r, uint32_t a) { asm volatile("ldmatrix.sync.aligned.m8n8.x4.shared.b16 {%0,%1,%2,%3}, [%4];" : "=r"(r[0]), "=r"(r[1]), "=r"(r[2]), "=r"(r[3]) : "r"(a) : "memory"); }
__device__ __forceinline__ void ldsm4t(uint32_t* r, uint32_t a) { asm volatile("ldmatrix.sync.aligned.m8n8.x4.trans.shared.b16 {%0,%1,%2,%3}, [%4];" : "=r"(r[0]), "=r"(r[1]), "=r"(r[2]), "=r"(r[3]) : "r"(a) : "memory"); }
__device__ __forceinline__ void stsm4t(uint32_t a, uint32_t r0, uint32_t r1, uint32_t r2, uint32_t r3) { asm volatile("stmatrix.sync.aligned.m8n8.x4.trans.shared.b16 [%0], {%1,%2,%3,%4};" ::"r"(a), "r"(r0), "r"(r1), "r"(r2), "r"(r3) : "memory"); }
__device__ __forceinline__ void stsm2t(uint32_t a, uint32_t r0, uint32_t r1) { asm volatile("stmatrix.sync.aligned.m8n8.x2.trans.shared.b16 [%0], {%1,%2};" ::"r"(a), "r"(r0), "r"(r1) : "memory"); }
__device__ __forceinline__ void mma16(float* d, const uint32_t* a, uint32_t b0, uint32_t b1) {
    asm("mma.sync.aligned.m16n8k16.row.col.f32.bf16.bf16.f32 {%0,%1,%2,%3}, {%4,%5,%6,%7}, {%8,%9}, {%0,%1,%2,%3};"
        : "+f"(d[0]), "+f"(d[1]), "+f"(d[2]), "+f"(d[3]) : "r"(a[0]), "r"(a[1]), "r"(a[2]), "r"(a[3]), "r"(b0), "r"(b1));
}
__device__ __forceinline__ void mma8(float* d, uint32_t a0, uint32_t a1, uint32_t b0) {
    asm("mma.sync.aligned.m16n8k8.row.col.f32.bf16.bf16.f32 {%0,%1,%2,%3}, {%4,%5}, {%6}, {%0,%1,%2,%3};"
        : "+f"(d[0]), "+f"(d[1]), "+f"(d[2]), "+f"(d[3]) : "r"(a0), "r"(a1), "r"(b0));
}
__device__ __forceinline__ void mma16z(float* d, const uint32_t* a, uint32_t b0, uint32_t b1) {
    asm("mma.sync.aligned.m16n8k16.row.col.f32.bf16.bf16.f32 {%0,%1,%2,%3}, {%4,%5,%6,%7}, {%8,%9}, {%10,%10,%10,%10};"
        : "=f"(d[0]), "=f"(d[1]), "=f"(d[2]), "=f"(d[3]) : "r"(a[0]), "r"(a[1]), "r"(a[2]), "r"(a[3]), "r"(b0), "r"(b1), "f"(0.f));
}
__device__ __forceinline__ uint32_t pack(float lo, float hi) { uint32_t r; asm("cvt.rn.bf16x2.f32 %0, %1, %2;" : "=r"(r) : "f"(hi), "f"(lo)); return r; }
__device__ __forceinline__ uint32_t hmul(uint32_t a, uint32_t b) { uint32_t r; asm("mul.rn.bf16x2 %0, %1, %2;" : "=r"(r) : "r"(a), "r"(b)); return r; }
__device__ __forceinline__ uint32_t hfma(uint32_t a, uint32_t b, uint32_t c) { uint32_t r; asm("fma.rn.bf16x2 %0, %1, %2, %3;" : "=r"(r) : "r"(a), "r"(b), "r"(c)); return r; }
__device__ __forceinline__ uint4 lds128(uint32_t a) { uint4 v; asm volatile("ld.shared.v4.u32 {%0,%1,%2,%3}, [%4];" : "=r"(v.x), "=r"(v.y), "=r"(v.z), "=r"(v.w) : "r"(a) : "memory"); return v; }
__device__ __forceinline__ void sts128(uint32_t a, uint4 v) { asm volatile("st.shared.v4.u32 [%0], {%1,%2,%3,%4};" ::"r"(a), "r"(v.x), "r"(v.y), "r"(v.z), "r"(v.w) : "memory"); }
__device__ __forceinline__ int lds32(uint32_t a) { int v; asm volatile("ld.shared.u32 %0, [%1];" : "=r"(v) : "r"(a) : "memory"); return v; }
__device__ __forceinline__ void sts32(uint32_t a, int v) { asm volatile("st.shared.u32 [%0], %1;" ::"r"(a), "r"(v) : "memory"); }
__device__ __forceinline__ int atoms_add(uint32_t a, int v) { int r; asm volatile("atom.shared.add.u32 %0, [%1], %2;" : "=r"(r) : "r"(a), "r"(v) : "memory"); return r; }
__device__ __forceinline__ uint32_t ld_rlx(const void* p) { uint32_t v; asm volatile("ld.relaxed.gpu.global.u32 %0, [%1];" : "=r"(v) : "l"(p) : "memory"); return v; }
__device__ __forceinline__ void st_rlx(void* p, uint32_t v) { asm volatile("st.relaxed.gpu.global.u32 [%0], %1;" ::"l"(p), "r"(v) : "memory"); }
__device__ __forceinline__ void bulk(uint32_t dst, const void* g, int n, uint32_t bar) {
    asm volatile("cp.async.bulk.shared::cluster.global.mbarrier::complete_tx::bytes [%0], [%1], %2, [%3];" ::"r"(dst), "l"(g), "r"(n), "r"(bar) : "memory");
}
__device__ __forceinline__ void bulk_st(void* g, uint32_t src, int n) {
    asm volatile("cp.async.bulk.global.shared::cta.bulk_group [%0], [%1], %2;\ncp.async.bulk.commit_group;" ::"l"(g), "r"(src), "r"(n) : "memory");
}
__device__ __forceinline__ uint2 lds64(uint32_t a) { uint2 v; asm volatile("ld.shared.v2.u32 {%0,%1}, [%2];" : "=r"(v.x), "=r"(v.y) : "r"(a) : "memory"); return v; }
__device__ __forceinline__ void sts64(uint32_t a, uint32_t x, uint32_t y) { asm volatile("st.shared.v2.u32 [%0], {%1,%2};" ::"r"(a), "r"(x), "r"(y) : "memory"); }
__device__ __forceinline__ void tma3d(uint32_t dst, const CUtensorMap* m, int c1, int c2, uint32_t bar) {
    asm volatile("cp.async.bulk.tensor.3d.shared::cluster.global.mbarrier::complete_tx::bytes [%0], [%1, {0, %3, %4}], [%2];"
                 ::"r"(dst), "l"(m), "r"(bar), "r"(c1), "r"(c2) : "memory");
}
__device__ __forceinline__ void pf_l2(const void* g, int n) {
    asm volatile("{.reg .pred p; setp.gt.s32 p, %1, 0; @p cp.async.bulk.prefetch.L2.global [%0], %1;}" ::"l"(g), "r"(n) : "memory");
}
__device__ __forceinline__ void fence_async() { asm volatile("fence.proxy.async.shared::cta;" ::: "memory"); }
__device__ __forceinline__ uint64_t madw(uint32_t a, uint32_t b, uint64_t c) { uint64_t r; asm("mad.wide.u32 %0, %1, %2, %3;" : "=l"(r) : "r"(a), "r"(b), "l"(c)); return r; }
__device__ __forceinline__ uint32_t lop_sel(uint32_t a, uint32_t b, uint32_t m) { uint32_t r; asm("lop3.b32 %0, %1, %2, %3, 0xd8;" : "=r"(r) : "r"(a), "r"(b), "r"(m)); return r; }
__device__ __forceinline__ uint32_t opaque(uint32_t v, int lane) { return __shfl_sync(0xffffffffu, v, lane); }
__device__ __forceinline__ void bar_sync(int id, int n) { asm volatile("bar.sync %0, %1;" ::"r"(id), "r"(n) : "memory"); }

__device__ __forceinline__ void wg_rs16(float* d, const uint32_t* a, uint64_t db, int sc) {
    asm volatile("{.reg .pred p; setp.ne.b32 p, %13, 0;\n"
                 "wgmma.mma_async.sync.aligned.m64n16k16.f32.bf16.bf16 {%0,%1,%2,%3,%4,%5,%6,%7}, {%8,%9,%10,%11}, %12, p, 1, 1, 0;}"
                 : "+f"(d[0]), "+f"(d[1]), "+f"(d[2]), "+f"(d[3]), "+f"(d[4]), "+f"(d[5]), "+f"(d[6]), "+f"(d[7])
                 : "r"(a[0]), "r"(a[1]), "r"(a[2]), "r"(a[3]), "l"(db), "r"(sc));
}
__device__ __forceinline__ void wg_rs48(float* d, const uint32_t* a, uint64_t db, int sc) {
    asm volatile("{.reg .pred p; setp.ne.b32 p, %29, 0;\n"
                 "wgmma.mma_async.sync.aligned.m64n48k16.f32.bf16.bf16 {%0,%1,%2,%3,%4,%5,%6,%7,%8,%9,%10,%11,%12,%13,%14,%15,%16,%17,%18,%19,%20,%21,%22,%23}, {%24,%25,%26,%27}, %28, p, 1, 1, 0;}"
                 : "+f"(d[0]), "+f"(d[1]), "+f"(d[2]), "+f"(d[3]), "+f"(d[4]), "+f"(d[5]), "+f"(d[6]), "+f"(d[7]),
                   "+f"(d[8]), "+f"(d[9]), "+f"(d[10]), "+f"(d[11]), "+f"(d[12]), "+f"(d[13]), "+f"(d[14]), "+f"(d[15]),
                   "+f"(d[16]), "+f"(d[17]), "+f"(d[18]), "+f"(d[19]), "+f"(d[20]), "+f"(d[21]), "+f"(d[22]), "+f"(d[23])
                 : "r"(a[0]), "r"(a[1]), "r"(a[2]), "r"(a[3]), "l"(db), "r"(sc));
}
__device__ __forceinline__ void wg_ss48(float* d, uint64_t da, uint64_t db, int sc) {
    asm volatile("{.reg .pred p; setp.ne.b32 p, %26, 0;\n"
                 "wgmma.mma_async.sync.aligned.m64n48k16.f32.bf16.bf16 {%0,%1,%2,%3,%4,%5,%6,%7,%8,%9,%10,%11,%12,%13,%14,%15,%16,%17,%18,%19,%20,%21,%22,%23}, %24, %25, p, 1, 1, 1, 0;}"
                 : "+f"(d[0]), "+f"(d[1]), "+f"(d[2]), "+f"(d[3]), "+f"(d[4]), "+f"(d[5]), "+f"(d[6]), "+f"(d[7]),
                   "+f"(d[8]), "+f"(d[9]), "+f"(d[10]), "+f"(d[11]), "+f"(d[12]), "+f"(d[13]), "+f"(d[14]), "+f"(d[15]),
                   "+f"(d[16]), "+f"(d[17]), "+f"(d[18]), "+f"(d[19]), "+f"(d[20]), "+f"(d[21]), "+f"(d[22]), "+f"(d[23])
                 : "l"(da), "l"(db), "r"(sc));
}

__device__ __forceinline__ int warp_incl(int v) {
#pragma unroll
    for (int o = 1; o < 32; o <<= 1)
        asm volatile("{.reg .pred p; .reg .b32 u; shfl.sync.up.b32 u|p, %0, %1, 0, 0xffffffff; @p add.s32 %0, %0, u;}" : "+r"(v) : "r"(o));
    return v;
}
__device__ __forceinline__ void ldg128(uint32_t* r, const void* p, bool on) {
    asm volatile("{.reg .pred p; setp.ne.u32 p, %5, 0; @p ld.global.nc.v4.u32 {%0,%1,%2,%3}, [%4];}"
                 : "=r"(r[0]), "=r"(r[1]), "=r"(r[2]), "=r"(r[3]) : "l"(p), "r"((uint32_t)on));
}

struct Acc {
    uint32_t p00[4], p110[4], p10[3][4];
    float t01[4], m[3][4];
};

#define LF(m) ldsm4t(f[m], so + xa + m * 256)
#define LY() ldsm4(yb, so + ya)
#define LC() ldsm4(yb + 4, so + yc)
#define LN() ph = lds32(so + S_N)
#define ADV() { asm volatile("@lane0 mbarrier.arrive.shared::cta.b64 _, [%0];" ::"r"(so + S_EMPTY) : "memory"); \
                so = so == sm + O_RING + (NSLOT - 1) * SLOT ? sm + O_RING : so + SLOT; }
#define LA() asm volatile("{\n.reg .pred p, q;\n.reg .b64 s;\n.reg .f32 n;\nmov.b64 s, {0, %7};\nmbarrier.test_wait.shared::cta.b64 p, [%6], s;\n" \
                          "abs.f32 n, %7;\nsetp.gt.and.f32 q, n, 0f00000001, p;\nselp.u32 %4, 1, 0, p;\nselp.u32 %5, 1, 0, q;\n" \
                          "@p ldmatrix.sync.aligned.m8n8.x4.shared.b16 {%0,%1,%2,%3}, [%8];\n}" \
                          : "+r"(a[0]), "+r"(a[1]), "+r"(a[2]), "+r"(a[3]), "=r"(ok), "=r"(go) : "r"(so + S_FULL), "r"(ph), "r"(so + aa) : "memory")
#define RAD(p, s) { float c[4]; mma16z(c, wr[p], a[2 * s], a[2 * s + 1]); R[p][2 * s] = pack(c[0], c[1]); R[p][2 * s + 1] = pack(c[2], c[3]); }
#define MUL(n, x, y) (XS >> n & 1 ? hmul(y, x) : hmul(x, y))
#define FMA(n, x, y, z) (XS >> n & 1 ? hfma(y, x, z) : hfma(x, y, z))
#define ACC(n, x, y, z) z = F ? MUL(n, x, y) : FMA(n, x, y, z)
#define P00(i) ACC(0, f[0][i], R[0][i], A.p00[i ^ XA])
#define P10(k, i) ACC(1, f[1 + k][i], R[3][i], A.p10[k][i ^ XA])
#define S0(k, i) sd[i] = MUL(2, f[1 + k][i], yb[2 * k + (i >> 1)])
#define SD(k, i) sd[i] = FMA(2, f[1 + k][i], yb[2 * k + (i >> 1)], sd[i])
#define P110(i) ACC(3, sd[i], R[1][i], A.p110[i ^ XA])
#define TU(i) u[3][i ^ XU] = MUL(4, f[0][i], R[2][i])
#define TM() if (F) mma16z(A.t01, u[3], yb[6], yb[7]); else mma16(A.t01, u[3], yb[6], yb[7])
#define MU(k, i) u[k][i ^ XU] = MUL(5, f[1 + k][i], R[4][i])
#define MM(k) if (F) mma16z(A.m[k], u[k], yb[6], yb[7]); else mma16(A.m[k], u[k], yb[6], yb[7])
#define PK(v, h) pack(v[2 * (h)], v[2 * (h) + 1])
#define LM() { sts32(na + sof, mt); asm volatile("ld.shared.u16 %0, [%1];" : "=r"(mt) : "r"(so + ma) : "memory"); }
#define FY(k) if (k == 0) mma16z(y, A.p10[0], oh[0][0], oh[0][1]); else mma16(y, k < 3 ? A.p10[k % 3] : A.p00, oh[k][0], oh[k][1])
#define FZ(k) if (k == 0) mma16z(z, A.p110, oh[3][0], oh[3][1]); \
              else if (k == 1) { const uint32_t mp[4] = {PK(A.m[0], XA ^ XU), PK(A.m[0], 1 ^ XA ^ XU), PK(A.m[1], XA ^ XU), PK(A.m[1], 1 ^ XA ^ XU)}; mma16(z, mp, eb[0], eb[1]); } \
              else mma8(z, PK(A.m[2], XA ^ XU), PK(A.m[2], 1 ^ XA ^ XU), eb[2])
#define SX() stsm2t(fx + sof, PK(A.t01, XU), PK(A.t01, 1 ^ XU))
#define SY() stsm4t(fyz + sof, PK(y, XA), PK(y, 1 ^ XA), PK(z, XA), PK(z, 1 ^ XA))
#define X4(op) op(0); op(1); op(2); op(3)
#define Y4(op, k) op(k, 0); op(k, 1); op(k, 2); op(k, 3)
#define XA 1
#define XU 0
#define XS_R 63
#define SEQ_R LN(); LF(1); LF(3); LF(0); LF(2); LC(); RAD(1,0); RAD(1,1); RAD(2,0); RAD(0,0); RAD(0,1); RAD(2,1); RAD(3,0); P00(0); TU(0); \
    P10(0,0); P10(0,1); TU(2); TU(3); RAD(4,1); MU(2,2); MU(2,3); TU(1); TM(); P00(1); RAD(4,0); MU(2,0); MU(2,1); MU(0,0); MU(0,2); \
    RAD(3,1); P10(0,2); P10(0,3); LY(); ADV(); LA(); P00(2); MU(0,3); P00(3); MM(2); MU(0,1); MM(0); P10(2,0); P10(2,2); P10(2,3); P10(2,1); \
    P10(1,0); P10(1,1); P10(1,2); P10(1,3); MU(1,2); S0(2,0); SD(1,0); SD(0,0); P110(0); S0(2,1); SD(1,1); SD(0,1); P110(1); S0(2,2); \
    SD(1,2); SD(0,2); P110(2); MU(1,3); S0(2,3); SD(1,3); SD(0,3); P110(3); MU(1,0); MU(1,1); MM(1);
#define XS_F 0
#define SEQ_F LN(); LM(); LF(0); LC(); LF(1); LF(2); LF(3); LY(); ADV(); FY(0); FZ(0); FY(1); FZ(1); FY(2); FZ(2); FY(3); SX(); SY(); \
    RAD(0, 0); RAD(0, 1); RAD(1, 0); RAD(1, 1); RAD(2, 0); RAD(2, 1); RAD(3, 0); RAD(3, 1); RAD(4, 0); RAD(4, 1); LA(); \
    X4(P00); X4(TU); TM(); Y4(P10, 0); Y4(MU, 0); MM(0); Y4(P10, 1); Y4(MU, 1); MM(1); Y4(P10, 2); Y4(MU, 2); MM(2); \
    Y4(S0, 0); Y4(SD, 1); Y4(SD, 2); X4(P110);

__global__ void __launch_bounds__(NT, 1)
tp_kernel(const int4* __restrict__ dst, const int4* __restrict__ src, const char* __restrict__ rhat, Scratch* __restrict__ gs,
          const char* __restrict__ x, const char* __restrict__ ea, const __nv_bfloat16* __restrict__ eps, char* __restrict__ out,
          const __grid_constant__ CUtensorMap m_wr, const __grid_constant__ CUtensorMap m_w0, const __grid_constant__ CUtensorMap m_w1) {
    extern __shared__ __align__(1024) char smem_raw[];
    constexpr uint32_t sm = 1024;
    spin_check((uint32_t)__cvta_generic_to_shared(smem_raw) == sm ? 0 : 2 * SPIN_LIMIT);
    int t;
    asm volatile("mov.u32 %0, %%tid.x;" : "=r"(t));
    const int w = t >> 5, lane = t & 31, b = blockIdx.x;

    const int g = lane >> 2, q = lane & 3, mat = lane >> 3, r = lane & 7;
    const int e0 = b * CH + t * 8, ne = min(CH, NE - b * CH);
    const bool act = t * 8 < ne;
    uint32_t d[8];
#pragma unroll
    for (int k = 0; k < 2; k++) ldg128(d + 4 * k, dst + e0 / 4 + k, act);
    uint32_t tag = ld_rlx(&gs->epoch[b * 32]), epl;
    asm volatile("ld.global.nc.u16 %0, [%1];" : "=r"(epl) : "l"(eps + min(lane, 26)));
    if (t < 60) sts128(sm + O_BCNT + 16 * t, make_uint4(0, 0, 0, 0));
    if (t == NT - 1) {
#pragma unroll
        for (int i = 0; i < 4; i++) mbar_init(sm + O_WBA + 8 * i, 1);
        fence_async();
        mbar_expect(sm + O_WBC, ne * 10); mbar_expect(sm + O_WBA, 20480); mbar_expect(sm + O_WBB, 81920); mbar_expect(sm + O_WBD, 81920);
        spin_check(tag);
        bulk(sm + O_RH, rhat + b * (CH * 6), ne * 6, sm + O_WBC);
        bulk(sm + O_SRC, src + b * (CH / 4), ne * 4, sm + O_WBC);
        tma3d(sm + O_WR0, &m_wr, 0, 0, sm + O_WBA);
        tma3d(sm + O_WR1, &m_wr, 0, 5, sm + O_WBA);
        tma3d(sm + O_W0S, &m_w0, 0, 0, sm + O_WBD);
        tma3d(sm + O_W1S, &m_w1, 0, 0, sm + O_WBD);
    }
    if (t == 320) {
#pragma unroll
        for (int i = 0; i < NSLOT; i++) {
            sts128(sm + O_RING + i * SLOT + S_C + 64, make_uint4(0, 0, 0, 0));
            mbar_init(sm + O_RING + i * SLOT + S_FULL, 32); mbar_init(sm + O_RING + i * SLOT + S_EMPTY, 8);
        }
    }
#pragma unroll
    for (int k = 0; k < LZ; k++) sts128(sm + O_L + 16 * (t + k * NT), make_uint4(0, 0, 0, 0));
    if (t < 80) sts32(sm + O_NCNT + 4 * t, t <= NLOC ? 4 * t : 0);
    if (t < 68) sts32(sm + O_NODE + 4 * t, 0);
    uint32_t ba[8], rk[8];
    auto pfx = [&](int r0, int n) {
        if (n) pf_l2(x + (b * NLOC + r0) * 1024, min(n, NN - b * NLOC - r0) * 1024);
    };
    if (w < 10) bar_sync(1, 320);
    tag = (tag + 1) << 30;
    if (act) {
#pragma unroll
        for (int i = 0; i < 8; i++) {
            const uint32_t l = __umulhi(d[i], (uint32_t)((1ull << 32) / G + 1));
            ba[i] = d[i] * 4 - l * (4 * G);
            d[i] = l * 4 + (tag + ((e0 + i + 1) << 9) + 4);
            rk[i] = atoms_add(sm + O_BCNT + ba[i], 4);
        }
#pragma unroll
        for (int i = 0; i < 8; i++)
            asm volatile("{.reg .pred p; setp.lt.u32 p, %2, 124; @p st.shared.u32 [%0], %1;}"
                         ::"r"(sm + O_KT + ba[i] * 32 + ((ba[i] + rk[i]) & 127)), "r"(d[i]), "r"(rk[i]) : "memory");
    }
    TS(0);
    __syncthreads();
    {
        int v[5], sum = 0;
#pragma unroll
        for (int i = 0; i < 5; i++) { v[i] = lds32(sm + O_BCNT + 4 * (lane * 5 + i)); sum += v[i]; }
        int e = warp_incl(sum) - sum;
        if (w == 10) {
#pragma unroll
            for (int i = 0; i < 5; i++) {
                const int k = lane * 5 + i;
                if (k < G) sts32(sm + O_KT + k * 128 + ((k * 4 + 124) & 127), tag | v[i] << 10 | e >> 2);
                e += v[i];
            }
            __syncwarp();
            if (lane == 0) {
                fence_async();
                bulk_st(&gs->keys[b * (G * 32)], sm + O_KT, G * 128);
                pfx(0, PFA);
            }
        } else {
#pragma unroll
            for (int i = 0; i < 5; i++) { sts32(sm + O_BOFF + 4 * (lane * 5 + i), e); e += v[i]; }
        }
        __syncwarp();
    }
    TS(11);
    const uint32_t sw = (uint32_t)(((2 * (w & 3) + (mat & 1)) ^ r) * 16 + ((mat >> 1) * 8 + r) * 128);
    uint32_t wr[5][4];
    const uint32_t* kp = &gs->keys[(w * SEGW * G + b) * 32 + ((lane + b) & 31)];
    uint32_t kv[SEGW + 1], ho[SEGW + 1], nk[SEGW + 1], old;
    if (act) {
        uint32_t mx = 0;
#pragma unroll
        for (int i = 0; i < 8; i++) { mx = max(mx, rk[i]); ba[i] = rk[i] + lds32(sm + O_BOFF + ba[i]); }
        if (mx >= 124) {
#pragma unroll
            for (int i = 0; i < 8; i++)
                if (rk[i] >= 124) st_rlx(&gs->more[b * CH + (ba[i] >> 2)], d[i]);
        }
    }
    if (w < 8) {
        mbar_wait(sm + O_WBA, 0);
#pragma unroll
        for (int p = 0; p < 5; p++) {
            const int c = 2 * p + (w >> 2);
            ldsm4t(wr[p], sm + (c < 5 ? O_WR0 : O_WR1 - 5 * 2048) + c * 2048 + sw);
        }
    } else {
        const uint64_t xl = (uint64_t)(x - 1024 + r * 16) - (tag >> 6), al = (uint64_t)(ea - 32 + (lane & 1) * 16) - (tag >> 4);
        const uint64_t ml = (uint64_t)gs->list + lane * 8;
        const uint32_t row = 0x76b821a3u >> 4 * r & 15, row0 = 0xc5bfe0cbu >> 4 * r & 15;
        const uint32_t c[13] = {(uint32_t)xl, (uint32_t)(xl >> 32), (uint32_t)al, (uint32_t)(al >> 32), (uint32_t)ml, (uint32_t)(ml >> 32),
            mat * 2048u + (r ^ 2 * mat) * 16, mat * 2048u + 1024 + (r ^ 2 * mat ^ 1) * 16,
            S_A + (lane & 2) * 128u + g * 32 + ((lane ^ lane >> 4) & 1) * 16, S_C + (mat & 1 ? row : row0) * 16, lane & 1 ? 16u : 9u, lane & 30u,
            lane == 4 ? 0xffff0000u : 0u};
#pragma unroll
        for (int i = 0; i < 20; i++) wr[i >> 2][i & 3] = i < 13 ? opaque(c[i % 13], lane) : 0;
    }
    TS(21);
    mbar_wait(sm + O_WBC, 0);
    TS(22);
    if (act) {
        uint32_t s[8], y[12];
#pragma unroll
        for (int k = 0; k < 3; k++) *(uint4*)&y[4 * k] = lds128(sm + O_RH + t * 48 + k * 16);
#pragma unroll
        for (int k = 0; k < 2; k++) *(uint4*)&s[4 * k] = lds128(sm + O_SRC + t * 32 + k * 16);
#pragma unroll
        for (int i = 0; i < 8; i++) {
            const int k = 3 * i / 2;
            sts64(sm + O_OUT + ba[i] * 2, __byte_perm(y[k], s[i] + (tag >> 16) + 1, i & 1 ? 0x5432 : 0x5410),
                  i & 1 ? y[k + 1] : __byte_perm(y[k], y[k + 1], 0x5432));
        }
    }
    TS(12);
    if (w < 10) asm volatile("bar.arrive 4, 352;" ::: "memory");
    if (w == 11) {
        bar_sync(4, 352);
        if (lane == 0) { fence_async(); bulk_st(&gs->vals[b * CH], sm + O_OUT, ne * 8); pfx(PFA, PFB); }
        __syncwarp();
    }

    const uint32_t am = lane < 31 ? 511 : 0, none = tag | (320 + 4 * lane);
    auto check = [&]() {
        old = 0;
#pragma unroll
        for (int j = 0; j < SEGW; j++) {
            ho[j] = __shfl_sync(0xffffffffu, kv[j], 31);
            kv[j] = ho[j] >= (lane < 31 ? tag + ((lane + 1) << 12) : 0u) ? kv[j] : none;
            old |= kv[j] ^ tag;
        }
        return __any_sync(0xffffffffu, old >> 30);
    };
#pragma unroll
    for (int j = 0; j < SEGW; j++) kv[j] = ld_rlx(kp + j * (G * 32));
    TS(1);
    TV(19, 0);
    for (int it = 0; check(); it++) {
        spin_check(it);
        if (it == 0) TS(20);
        TV(19, (it + 1) * 100);
#pragma unroll
        for (int j = 0; j < SEGW; j++)
            if (__any_sync(0xffffffffu, (kv[j] ^ tag) >> 30)) kv[j] = ld_rlx(kp + j * (G * 32));
    }
    TS(3);
    kv[SEGW] = none; ho[SEGW] = 0;
    bool slow = false;
    const bool more = __any_sync(0xffffffffu, lane == 31 && (old & 0xfe0000));
    if (more) {
        int c = lane;
#pragma unroll
        for (int j = 0; j < SEGW; j++) {
            const int n = max((int)(ho[j] >> 12 & 0xfff) - 31, 0);
            if ((unsigned)c < (unsigned)n) ho[SEGW] = j * CH + (ho[j] & 0xfff) + 31 + c - lane;
            c -= n;
        }
        slow = lane == 31 && c < 0;
        if (c < 0 && lane < 31)
            for (int it = 0; ((kv[SEGW] = ld_rlx(&gs->more[w * SEGW * CH + lane + ho[SEGW]])) ^ tag) >> 30; it++) spin_check(it);
        __syncwarp();
    }
    uint32_t na_[SEGW + 1];
#pragma unroll
    for (int j = 0; j <= SEGW; j++) {
        na_[j] = (kv[j] & am) | (none & 511 & ~am);
        nk[j] = atoms_add(sm + O_NCNT + na_[j], 512);
    }
    auto visit = [&](auto f) {
#pragma unroll 1
        for (int j = 0; j < SEGW; j++) {
            const uint32_t* kl = &gs->keys[((w * SEGW + j) * G + b) * 32];
            const uint32_t h = ld_rlx(kl + ((31 + b) & 31));
#pragma unroll 1
            for (int i = lane; i < (h >> 12 & 0xfff); i += 32) {
                const int o = (w * SEGW + j) * CH + (h & 0xfff) + i;
                uint32_t k;
                int it = 0;
                do { k = ld_rlx(i < 31 ? kl + ((i + b) & 31) : &gs->more[o]); spin_check(it++); } while ((k ^ tag) >> 30);
                f(k, o, i);
            }
        }
    };
    slow = __syncthreads_or(slow);
    if (slow) {
        if (t < 80) sts32(sm + O_NCNT + 4 * t, t <= NLOC ? 4 * t : 0);
        __syncthreads();
        visit([&](uint32_t k, int, int) { atoms_add(sm + O_NCNT + (k & 511), 512); });
        __syncthreads();
    }
    TS(4);
    if (t == 352) pfx(PFA + PFB, PFC);
    uint64_t vp = (uint64_t)&gs->vals[w * SEGW * CH + lane], vv[SEGW + 1];
#pragma unroll
    for (int j = 0; j <= SEGW; j++) vv[j] = tag;
    auto ldv = [&](bool again) {
#pragma unroll
        for (int j = 0; j <= SEGW; j++)
            asm volatile("{.reg .pred p; setp.lt.u32 p, %2, 320; @p ld.relaxed.gpu.global.b64 %0, [%1];}" : "+l"(vv[j])
                         : "l"(madw(j < SEGW ? ho[j] & 0xfff : ho[j], 8, vp) + (j < SEGW ? j * CH * 8 : 0)),
                           "r"(again ? (((uint32_t)vv[j] ^ tag) >> 30 ? 0 : 320) : na_[j]) : "memory");
    };
    if (w < 10) {
        const uint32_t key = lds32(sm + O_NCNT + 4 + (t & ~3));
        uint4 k[5];
#pragma unroll
        for (int i = 0; i < 5; i++) k[i] = lds128(sm + O_NCNT + q * 80 + i * 16);
        uint32_t c[4] = {0, 0, 0, 0};
#pragma unroll
        for (int i = 0; i < 5; i++) { c[0] += (key - k[i].x) >> 31; c[1] += (key - k[i].y) >> 31; c[2] += (key - k[i].z) >> 31; c[3] += (key - k[i].w) >> 31; }
        int rank = c[0] + c[1] + c[2] + c[3];
        rank += __shfl_xor_sync(0xffffffffu, rank, 1);
        rank += __shfl_xor_sync(0xffffffffu, rank, 2);
        if (ASC && rank < 2 * NPRIV) rank = (2 * NPRIV - 1 - rank) ^ 1;
        if (t < NLOC * 4) sts32(sm + O_SORT + 4 * rank, key);
    }
    __syncthreads();
    TS(2);
    const bool on = lane < NLOC / 4;
    const uint4 k4 = lds128(sm + O_SORT + 16 * (on ? lane : 0));
    const uint32_t ks[4] = {k4.x, k4.y, k4.z, k4.w};
    const int n0 = on ? max(1u, (ks[0] + 3584) >> 12) : 0, n1 = on ? max(1u, (ks[2] + 3584) >> 12) : 0;
    const int u2 = warp_incl(n0 + n1), u1 = u2 - n1, u0 = u1 - n0;
    const int total = __shfl_sync(0xffffffffu, u2, 31);
    slow |= total > CAPT;
    int gbase = b * CAPT + 1;
    if (on) {
#pragma unroll
        for (int i = 0; i < 4; i++) {
            const int a = ks[i] & 511, node = a * (G / 4) - G + b, o = (i >> 1 ? u1 : u0) * 256 + (i & 1) * 16;
            const uint32_t mk = (node < NN ? node + 1 : 0) + ((i >> 1 ? n1 : n0) << 16);
            sts64(sm + O_NOFF + 2 * a, o - (a >> 4), mk + a * 16);
            if (!slow) sts32(sm + O_L + 4 + o, mk);
        }
    }
    __syncwarp();
    if (!slow) {
        uint32_t mk[SEGW + 1];
        TS(13);
        if (t == 352) { pfx(PFA + PFB + PFC, PFD); asm volatile("cp.async.bulk.wait_group.read 0;" ::: "memory"); }
        ldv(false);
#pragma unroll
        for (int j = 0; j <= SEGW; j++) {
            const uint2 o = lds64(sm + O_NOFF + 2 * na_[j]);
            mk[j] = o.y - nk[j] * 16; nk[j] = o.x + (nk[j] >> 4);
        }
        for (int it = 0;; it++) {
            old = 0;
#pragma unroll
            for (int j = 0; j <= SEGW; j++) old |= (uint32_t)vv[j] ^ tag;
            if (!__any_sync(0xffffffffu, old >> 30)) break;
            spin_check(it);
            vp = __shfl_sync(0xffffffffu, vp, lane);
            ldv(true);
        }
#pragma unroll
        for (int j = 0; j <= SEGW; j++)
            asm volatile("{.reg .pred p; setp.ne.u32 p, %3, %5; @p st.shared.v4.u32 [%0], {%1,%2,%3,%4};}"
                         ::"r"(sm + O_L + nk[j]), "r"(kv[j]), "r"(mk[j]), "r"((uint32_t)vv[j]), "r"((uint32_t)(vv[j] >> 32)), "r"(tag) : "memory");
        if (na_[SEGW] < 320) gs->more[w * SEGW * CH + lane + ho[SEGW]] = 0;
    } else {
        int so = 0;
#pragma unroll
        for (int j = 0; j < SEGW; j++) so += ho[j] & 0xfff;
        if (lane == 0) atoms_add(sm + O_SUM, so);
        if (t == 352) asm volatile("cp.async.bulk.wait_group.read 0;" ::: "memory");
        __syncthreads();
        gbase = TBIG + (lds32(sm + O_SUM) >> 3) + (NLOC + 5) * b;
        auto put = [&](uint32_t k, uint64_t e, uint32_t a, int rank) {
            const uint2 o = lds64(sm + O_NOFF + 2 * a);
            gs->list[gbase * 16 + ((o.x + (a >> 4)) >> 4) + rank * 2] = make_uint4(k, o.y - a * 16 - (rank << 13), e, e >> 32);
        };
        visit([&](uint32_t k, int o, int i) {
            uint64_t e;
            int it = 0;
            do {
                asm volatile("ld.relaxed.gpu.global.b64 %0, [%1];" : "=l"(e) : "l"(&gs->vals[o]) : "memory");
                spin_check(it++);
            } while (((uint32_t)e ^ tag) >> 30);
            if (i >= 31) gs->more[o] = 0;
            put(k, e, k & 511, atoms_add(sm + O_NCUR + (k & 511), 1));
        });
#pragma unroll 1
        for (int i = 0; i < 4; i++) {
            const uint32_t k = i == 0 ? ks[0] : i == 1 ? ks[1] : i == 2 ? ks[2] : ks[3];
#pragma unroll 1
            for (int p = (k >> 9) + w; p < (i >> 1 ? n1 : n0) * 8; p += NT / 32) put(0, 0, k & 511, p);
        }
        __threadfence();
    }
    const uint32_t iw0 = (gbase + u0) << 12 | n0, iw1 = (gbase + u1) << 12 | n1;
    __syncthreads();
    TS(5);

    if (w >= 8) {
        asm volatile("setmaxnreg.dec.sync.aligned.u32 " STR(PREG) ";");
        const int h = __reduce_max_sync(0xffffffffu, w & 3);
        gbase = __reduce_min_sync(0xffffffffu, iw0) >> 12;
        int pos = gbase + h, end = __reduce_max_sync(0xffffffffu, lane == NPRIV / 2 ? (NPRIV & 1 ? iw1 : iw0) : 0) >> 12;
        const int bytes = gbase < TBIG ? ((__reduce_max_sync(0xffffffffu, iw0) >> 12) - gbase) * 256 : 0;
        const uint32_t ring = sm + O_RING;
        const uint64_t xl = wr[0][0] | (uint64_t)wr[0][1] << 32, al = wr[0][2] | (uint64_t)wr[0][3] << 32, ml = wr[1][0] | (uint64_t)wr[1][1] << 32;
        const uint32_t xoff[2] = {wr[1][2], wr[1][3]}, aoff = wr[2][0], coff = wr[2][1], sh = wr[2][2], ial = wr[2][3], sel = wr[3][0];
        auto lde = [&](uint2& e, int p) {
            asm volatile("{.reg .pred p; setp.gt.s32 p, %3, 0; @p ld.relaxed.gpu.global.v2.u32 {%0,%1}, [%2];}" : "+r"(e.x), "+r"(e.y) : "l"(madw(p, 256, ml)), "r"(p) : "memory");
        };
        uint2 e0[3] = {};
#pragma unroll
        for (int k = 0; k < 3; k++) {
            e0[k] = lds64(sm + O_L - 2048 + k * 1024 + t * 8);
            lde(e0[k], bytes ? 0 : pos + 4 * k);
        }
        if (h == 3) fence_async();
        pos += 4;

        int ev = 0, state = -2, tk = 0, nr = 0;
        uint32_t inf = 0;
        int ii = 0;
        auto take = [&]() {
            int v = 0;
            asm volatile("{.reg .pred p; setp.eq.s32 p, %2, 0; @p atom.relaxed.gpu.global.add.u32 %0, [%1], 1;}" : "+r"(v) : "l"(&gs->ticket), "r"(lane) : "memory");
            return v;
        };
        auto resolve = [&]() {
            const int k = __reduce_max_sync(0xffffffffu, tk);
            inf = tag;
            if (k < G * NPOOL) { const int l = k / G; ii = (k - l * G) * NPOOL + l; inf = ld_rlx(&gs->info[ii]);
                tk = (STAG) && ((NPRIV + 1 + nr + (STAG)) & 7) == 0 && k >= G * NPOOL - THETA ? G * NPOOL : take(); }
        };
        uint32_t so = ring + h * SLOT, ph = 0x80000000u;
        uint32_t spins = 0;
        asm volatile(".reg .pred z<5>;");
        while (true) {
            const uint2 e = e0[0];
            const uint32_t o = e.x >> sh, id = __shfl_sync(0xffffffffu, o, ial);
            uint32_t s[4];
#pragma unroll
            for (int j = 0; j < 4; j++) s[j] = __shfl_sync(0xffffffffu, o, 2 * j + 1, 8);
            const uint32_t nx = so == ring + (NSLOT - 1) * SLOT ? ph : ph ^ 0x80000000u, ey = lop_sel(e.y, nx, sel);
            const uint64_t ga = madw(id, 32, al);
            uint64_t gx[4];
#pragma unroll
            for (int j = 0; j < 4; j++) gx[j] = madw(s[j], 1024, xl);
            const uint32_t da = so + aoff, dx[2] = {so + xoff[0], so + xoff[1]}, dc = so + coff;
            asm volatile("setp.eq.u32 z0, %0, 0;\nsetp.eq.u32 z1, %1, 0;\nsetp.eq.u32 z2, %2, 0;\nsetp.eq.u32 z3, %3, 0;\nsetp.eq.u32 z4, %4, 0;\n"
                         PFI
                         ::"r"(NULLP(s[0])), "r"(NULLP(s[1])), "r"(NULLP(s[2])), "r"(NULLP(s[3])), "r"(id), "l"(ga), "r"(da), "r"(dx[0]), "r"(dx[1]), "r"(dc));
            lde(e0[0], state < 0 ? 0 : pos);
            asm volatile("{\n.reg .pred p;\n.reg .b64 s;\nmov.b64 s, {0, %2};\n"
                         "LOOP:\nmbarrier.try_wait.shared::cta.b64 p, [%1], s;\n@p bra DONE;\n"
                         "add.u32 %0, %0, 1;\nsetp.gt.u32 p, %0, %3;\n@p trap;\nbra LOOP;\nDONE:\n}"
                         : "+r"(spins) : "r"(so + S_EMPTY), "r"(ph), "n"(SPIN_LIMIT) : "memory");
            asm volatile("cp.async.cg.shared.global [%0], [%1], 16, z4;" ::"r"(da), "l"(ga) : "memory");
#define ROW(j) _Pragma("unroll") for (int k = 0; k < 8; k++) \
                asm volatile("cp.async.cg.shared.global [%0], [%1], 16, z" #j ";" ::"r"(dx[j >> 1] + (j & 1) * 8192 + k * 128), "l"(gx[j] + k * 128) : "memory")
            X4(ROW);
            stsm2t(dc, e.x, ey);
            asm volatile("cp.async.mbarrier.arrive.noinc.shared::cta.b64 [%0];" ::"r"(so + S_FULL) : "memory");
            const bool wrap = NSLOT == 5 ? so != ring : so >= ring + (NSLOT - 4) * SLOT;
            ph ^= wrap ? 0x80000000u : 0u;
            so = wrap ? so - (NSLOT - 4) * SLOT : so + 4 * SLOT;
            pos += 4;
            if (pos >= ev) {
                if (state < 0) {
                    e0[0] = e0[1]; e0[1] = e0[2];
                    if (state == -2) {
                        if (h == 0) TSW(24);
                        if (h == 3) TSW(25);
                        if (h & 1) bar_sync(7, NT);
                        else asm volatile("bar.arrive 7, %0;" ::"n"(NT) : "memory");
                        if (h == 3) {
                            if (lane == 0) {
                                if (bytes) bulk_st(gs->list + gbase * 16, sm + O_L, bytes);
                                asm volatile("cp.async.bulk.wait_group.read 0;" ::: "memory");
                            }
                            __syncwarp();
                            if (lane == 0) {
                                for (int j = 0; j < 5; j++) tma3d(sm + O_W1 + j * 16384, &m_w1, 64 + 64 * j, 0, sm + O_WBB);
                            }
                            __syncwarp();
                        }
                        state = -1;
                    } else {
                        if (h == 3) {
                            if (lane == 0) asm volatile("cp.async.bulk.wait_group 0;\nfence.proxy.async;" ::: "memory");
                            __syncwarp();
                            const int i = opaque(2 * lane - NPRIV, lane);
                            if ((unsigned)i < NPOOL) st_rlx(&gs->info[b * NPOOL + i], tag | iw0);
                            if ((unsigned)(i + 1) < NPOOL) st_rlx(&gs->info[b * NPOOL + i + 1], tag | iw1);
                        }
                        bar_sync(6, 128);
                        ev = h ? end : end - 12; state = h ? 2 : 0;
                    }
                } else if (state == 0) { ev = end - 6; state = 1; tk = take(); }
                else if (state == 1) { resolve(); ev = end; state = 2; }
                else {
                    if (state == 3) break;
                    do {
                        const uint32_t mb = sm + O_MB + (nr & 15) * 8;
                        uint32_t rg;
                        nr++;
                        if (h == 0) {
                            for (int it = 0; (rg = __reduce_max_sync(0xffffffffu, inf ^ tag)) >> 30; it++) { spin_check(it); inf = ld_rlx(&gs->info[ii]); }
                            asm volatile("st.release.cta.shared.b64 [%0], %1;" ::"r"(mb), "l"(rg | (uint64_t)nr << 32) : "memory");
                            if (rg) resolve();
                        } else {
                            uint64_t m;
                            for (int it = 0;; it++) {
                                asm volatile("ld.acquire.cta.shared.b64 %0, [%1];" : "=l"(m) : "r"(mb) : "memory");
                                if (__all_sync(0xffffffffu, (int)(m >> 32) == nr)) break;
                                spin_check(it);
                            }
                            rg = __reduce_max_sync(0xffffffffu, (uint32_t)m);
                        }
                        pos = rg ? (int)(rg >> 12) + pos - end : 0;
                        end = rg ? (rg >> 12) + (rg & 0xfff) : 1;
                        state = rg ? 2 : 3;
                    } while (pos >= end);
                    ev = end;
                }
            }
        }
        mbar_wait31(so + S_EMPTY, ph);
        TSW(8 + (h & 1));
        if (lane == 0) sts32(so + S_N, 0);
        mbar_arrive(so + S_FULL);
        if (t == 256) {
            gs->epoch[b * 32] = (tag >> 30) % 3;
            if (atomicInc(&gs->done, G - 1) == G - 1) gs->ticket = 0;
        }
        asm volatile("cp.async.wait_all;" ::: "memory");
    } else {
        asm volatile("setmaxnreg.inc.sync.aligned.u32 " STR(CREG) ";");
        const uint32_t xa = opaque(((mat >> 1) * 8 + r) * 1024 + (w >> 2) * 128 + (((2 * (w & 3) + (mat & 1)) ^ r) * 16), lane);
        const uint32_t aa = opaque(S_A + ((mat >> 1) * 8 + r) * 32 + (((mat & 1) ^ (r >> 2)) * 16), lane);
        const uint32_t ya = opaque(S_C + (mat & 1) * 80 + (mat >> 1) * 16, lane);
        const uint32_t yc = opaque(S_C + (mat < 2 ? mat * 80 + 32 : (r >> 2) == (mat & 1) && q < 3 ? (mat & 1) * 80 + q * 16 : 64), lane);
        const uint32_t ma = opaque(S_C + 48 + (mat & 1) * 80, lane), na = opaque(sm + O_NODE + mat * 4, lane);
        const uint32_t pw = sm + O_P + w * PW;
        const uint32_t fx = opaque(pw + (q < 3 ? P_1P0 + 2 * q * PSBO : P_1P1 + PSBO) + (mat & 1) * 128 + (r >> 2) * PSBO, lane);
        const uint32_t fyz = opaque(pw + (q < 3 ? (mat < 2 ? P_1P1 : P_1P2) + 2 * q * PSBO : mat < 2 ? P_0P0 : P_0P1) + (mat & 1) * 128 + (r >> 2) * PSBO, lane);
        uint32_t oh[4][2];
#pragma unroll
        for (int c = 0; c < 8; c++) oh[c & 3][c >> 2] = opaque(g == c ? 0x3F803F80u : 0u, lane);
        uint32_t eb[3];
#pragma unroll
        for (int k = 0; k < 3; k++) {
            const int i = (g & 3) * 9 + (q & 1) * 6 + k;
            const uint32_t lo = __shfl_sync(0xffffffffu, epl, i), hi = __shfl_sync(0xffffffffu, epl, i + 3);
            eb[k] = (g & 3) < 3 && (q >> 1) == (g >> 2) ? (q & 1 ? lo : lo | hi << 16) : 0u;
        }
        asm volatile(".reg .pred lane0;\nsetp.eq.u32 lane0, %0, 0;" ::"r"(lane));
        uint32_t w0[16][4], w1[4][4];
        mbar_wait(sm + O_WBD, 0);
#pragma unroll
        for (int k = 0; k < 16; k++) ldsm4t(w0[k], sm + O_W0S + (w >> 2) * 32768 + k * 2048 + sw);
#pragma unroll
        for (int k = 0; k < 4; k++) ldsm4t(w1[k], sm + O_W1S + (w >> 2) * 8192 + k * 2048 + sw);
        bar_sync(7, NT);
        TS(6);
        Acc A;
#pragma unroll
        for (int i = 0; i < 4; i++) { A.p00[i] = A.p110[i] = A.p10[0][i] = A.p10[1][i] = A.p10[2][i] = 0; A.t01[i] = A.m[0][i] = A.m[1][i] = A.m[2][i] = 0.f; }
        uint32_t room = 144 - (STAG) * 16;
        uint32_t so = sm + O_RING, ph, a[4], ok, go, mt = 0;
        mbar_wait(so + S_FULL, 0);
        ldsm4(a, so + aa);
        TS(7);
        while (true) {
            {
                constexpr int F = 1, XS = XS_F;
                uint32_t yb[8], f[4][4], R[5][4], u[4][4], sd[4];
                float y[4], z[4];
                const uint32_t sof = room & 112;
                SEQ_F
                room -= 16;
            }
            if (!(go && room)) {
                const uint32_t pu = __reduce_max_sync(0xffffffffu, ph);
                if (!room || !pu) {
                    asm volatile("fence.proxy.async.shared::cta;" ::: "memory");
                    mbar_wait(sm + O_WBB, 0);
                    bar_sync(1, 256);
                    float d0[8], d1[24];
                    const uint32_t wg = __reduce_max_sync(0xffffffffu, w >> 2);
                    const uint64_t db = (uint64_t)((sm + O_P) >> 4) | (8ull << 16) | ((uint64_t)(PSBO / 16) << 32);
                    const uint32_t da = ((sm + O_W1) >> 4 | 1 << 16) + wg * 512;
                    asm volatile("wgmma.fence.sync.aligned;" ::: "memory");
#pragma unroll
                    for (int k = 0; k < 16; k++) wg_rs16(d0, w0[k], db + (((k & 7) * PW + ((k >> 3) ? P_0P1 : P_0P0)) >> 4), k);
                    asm volatile("wgmma.commit_group.sync.aligned;" ::: "memory");
#pragma unroll
                    for (int k = 0; k < 4; k++) wg_rs48(d1, w1[k], db + ((k * PW + P_1P0) >> 4), k);
#pragma unroll
                    for (int k = 4; k < 24; k++)
                        wg_ss48(d1, (da + (k / 4 - 1) * 1024 + (k & 3) * 128) | (64ull << 32) | (1ull << 62), db + (((k & 7) * PW + ((k >> 3) == 0 ? P_1P0 : (k >> 3) == 1 ? P_1P1 : P_1P2)) >> 4), k);
                    asm volatile("wgmma.commit_group.sync.aligned;" ::: "memory");
                    const uint2 n0 = lds64(sm + O_NODE + mat * 16), n1 = lds64(sm + O_NODE + 64 + mat * 16);
                    const bool v0 = (mat * 16 - 16 & 112) >= room, v1 = mat * 16 + 48 >= room;
                    const uint32_t nd[4] = {v0 ? n0.x : 0, v1 ? n1.x : 0, v0 ? n0.y : 0, v1 ? n1.y : 0};
                    const uint64_t op = (uint64_t)(out - 1024 + (w & 3) * 256 + (w >> 2) * 128 + r * 16);
                    uint64_t oa[4];
#pragma unroll
                    for (int it = 0; it < 4; it++) oa[it] = madw(nd[it], 1024, op);
                    uint32_t sg = sm + O_P + (w & 4) * PW + ((mat >> 1) * 8 + r) * 128 + (((2 * (w & 3) + (mat & 1)) ^ r) * 16);
                    uint32_t sl = pw + mat * 128 + (r ^ mat) * 16, sl2 = pw + 512 + mat * 128 + (r ^ mat ^ 4) * 16;
                    asm volatile("wgmma.wait_group.sync.aligned 1;" ::: "memory");
#pragma unroll
                    for (int i = 0; i < 8; i++) asm volatile("" : "+f"(d0[i])::"memory");
                    uint32_t o[4][4], chk = sg & sl & sl2;
                    float gt[8];
#pragma unroll
                    for (int i = 0; i < 8; i++) {
                        asm("ex2.approx.ftz.f32 %0, %1;" : "=f"(gt[i]) : "f"(d0[i] * -1.4426950408889634f));
                        asm("rcp.approx.ftz.f32 %0, %1;" : "=f"(gt[i]) : "f"(gt[i] + 1.f));
                        chk &= __float_as_uint(gt[i]);
                    }
#pragma unroll
                    for (int i = 0; i < 4; i++) { o[0][i] = pack(d0[2 * i], d0[2 * i + 1]); chk &= o[0][i] & (uint32_t)(oa[i] >> 32); }
                    sts32(sm + O_TRASH, chk);
                    asm volatile("wgmma.wait_group.sync.aligned 0;" ::: "memory");
#pragma unroll
                    for (int i = 0; i < 24; i++) asm volatile("" : "+f"(d1[i])::"memory");
                    bar_sync(1, 256);
#pragma unroll
                    for (int i = 0; i < 4; i++)
#pragma unroll
                        for (int j = 0; j < 3; j++) o[1 + j][i] = pack(d1[8 * j + 2 * i] * gt[2 * i], d1[8 * j + 2 * i + 1] * gt[2 * i + 1]);
#pragma unroll
                    for (int j = 0; j < 4; j++) stsm4t(sg + j * PW, o[j][0], o[j][1], o[j][2], o[j][3]);
                    bar_sync(2 + wg, 128);
                    uint4 v[4];
#pragma unroll
                    for (int it = 0; it < 4; it++) v[it] = lds128((it & 1 ? sl2 : sl) + (it >> 1) * 1024);
#pragma unroll
                    for (int it = 0; it < 4; it++)
                        asm volatile("{.reg .pred p; setp.ne.u32 p, %5, 0; @p st.global.v4.u32 [%0], {%1,%2,%3,%4};}"
                                     ::"l"(oa[it]), "r"(v[it].x), "r"(v[it].y), "r"(v[it].z), "r"(v[it].w), "r"(nd[it]) : "memory");
                    __syncwarp();
                    room = 128;
                    if (!pu) break;
                }
                if (!ok) { mbar_wait31(so + S_FULL, pu); ldsm4(a, so + aa); }
                if (!(pu & 0xfffe)) continue;
            }
            while (true) {
                do {
                    constexpr int F = 0, XS = XS_R;
                    uint32_t yb[8], f[4][4], R[5][4], u[4][4], sd[4];
                    SEQ_R
                } while (go);
                if (ok) break;
                const uint32_t pu = __reduce_max_sync(0xffffffffu, ph);
                mbar_wait31(so + S_FULL, pu); ldsm4(a, so + aa);
                if (!(pu & 0xfffe)) break;
            }
        }
        TS(10);
    }
}

typedef CUresult (*EncFn)(CUtensorMap*, CUtensorMapDataType, cuuint32_t, void*, const cuuint64_t*, const cuuint64_t*,
                          const cuuint32_t*, const cuuint32_t*, CUtensorMapInterleave, CUtensorMapSwizzle,
                          CUtensorMapL2promotion, CUtensorMapFloatOOBfill);

void make_map(EncFn fn, CUtensorMap* m, void* p, int rows, int cols, int brows, int rank, int bblk, CUtensorMapSwizzle swz) {
    cuuint64_t dims[3] = {(cuuint64_t)(rank == 3 ? 64 : cols), (cuuint64_t)rows, (cuuint64_t)cols / 64}, strides[2] = {(cuuint64_t)cols * 2, 128};
    cuuint32_t box[3] = {64, (cuuint32_t)brows, (cuuint32_t)bblk}, es[3] = {1, 1, 1};
    fn(m, CU_TENSOR_MAP_DATA_TYPE_BFLOAT16, rank, p, dims, strides, box, es, CU_TENSOR_MAP_INTERLEAVE_NONE,
       swz, CU_TENSOR_MAP_L2_PROMOTION_NONE, CU_TENSOR_MAP_FLOAT_OOB_FILL_NONE);
}

}

extern "C" void kernel_launch(void* const* d_in, const int* in_sizes, int n_in, void* d_out, int out_size) {
    static EncFn enc = nullptr;
    static void* scratch = nullptr;
    if (!enc) {
        void* fn = nullptr;
        cudaDriverEntryPointQueryResult qr;
        cudaGetDriverEntryPoint("cuTensorMapEncodeTiled", &fn, cudaEnableDefault, &qr);
        enc = (EncFn)fn;
        cudaGetSymbolAddress(&scratch, g_scratch);
        cudaFuncSetAttribute(tp_kernel, cudaFuncAttributeMaxDynamicSharedMemorySize, SMEM_BYTES);
    }
    CUtensorMap m_wr, m_w0, m_w1;
    make_map(enc, &m_wr, d_in[5], 16, 640, 16, 3, 5, CU_TENSOR_MAP_SWIZZLE_128B);
    make_map(enc, &m_w0, d_in[6], 256, 128, 256, 3, 2, CU_TENSOR_MAP_SWIZZLE_128B);
    make_map(enc, &m_w1, d_in[7], 384, 128, 64, 3, 2, CU_TENSOR_MAP_SWIZZLE_128B);
    tp_kernel<<<G, NT, SMEM_BYTES>>>((const int4*)d_in[4], (const int4*)d_in[3], (const char*)d_in[1], (Scratch*)scratch,
                                     (const char*)d_in[0], (const char*)d_in[2], (const __nv_bfloat16*)d_in[8], (char*)d_out,
                                     m_wr, m_w0, m_w1);
}
```

```cpp
#include <cuda_runtime.h>
#include <cuda_bf16.h>
#include <cuda.h>
#include <stdint.h>
#include <stddef.h>

namespace {

constexpr int NN = 10000;
constexpr int NE = 320000;
constexpr int G = 132;
constexpr int NT = 384;
constexpr int CH = 2432;
constexpr int NLOC = (NN + G - 1) / G;
#define NPOOL 4
constexpr int NPAIR = NLOC / 2, NPRIV = NPAIR - NPOOL;
constexpr int SEGW = 11;

#define NSLOT 6
#define PFA 16
#define PFB 20
#define PFC 20
#define PFD 20
#define STAG (b & 7)
#define ASC (b & 1)
#define THETA G
#define PFI "@!z4 prefetch.global.L2 [%5];"
#define W0P 2
#define W1P 2
#define WLD(p) { if (W0P == p) tma3d(sm + O_W0S, &m_w0, 0, 0, sm + O_WBD); if (W1P == p) tma3d(sm + O_W1S, &m_w1, 0, 0, sm + O_WBD); }
#define INV 0
#define NULLP(v) v
#define CREG 224
#define PREG 56
#define STR2(x) #x
#define STR(x) STR2(x)

constexpr int S_A = 16384, S_C = S_A + 512, S_FULL = S_C + 144, S_EMPTY = S_FULL + 8, S_N = S_C + 160, SLOT = S_C + 256;

constexpr int PSBO = 272;
constexpr int PB1 = 5 * PSBO + 256, PB0 = PSBO + 256;
constexpr int P_1P0 = 0, P_1P1 = PB1, P_0P1 = 2 * PB1, P_0P0 = P_0P1 + PB0, P_1P2 = P_0P0 + PB0;
constexpr int PW = P_1P2 + PB1;

constexpr int up1k(int a) { return (a + 1023) / 1024 * 1024; }
constexpr int O_W1 = 0;
constexpr int O_P = 81920;
constexpr int O_RING = O_P + 8 * PW;
constexpr int O_WBA = O_RING + 6 * SLOT, O_WBB = O_WBA + 8, O_WBC = O_WBA + 16, O_WBD = O_WBA + 24, O_TRASH = O_WBA + 32, O_NODE = O_WBA + 48;
constexpr int O_SUM = O_NODE + 128, O_MB = O_SUM + 16;
constexpr int SMEM_BYTES = O_MB + 128;
constexpr int CAPT = 192;
constexpr int O_L = 0, LZ = CAPT * 256 / (NT * 16), O_W0S = O_L + CAPT * 256, O_OUT = O_W0S + 65536, O_SRC = O_OUT + CH * 8;
constexpr int O_KT = O_RING + SLOT, O_RH = O_RING + 2 * SLOT;
constexpr int O_WR0 = up1k(O_RING + 3 * SLOT), O_WR1 = up1k(O_RING + 4 * SLOT), O_W1S = up1k(O_RING + 5 * SLOT);
constexpr int O_BCNT = O_WR0 + 10240, O_NCUR = O_BCNT + 640, O_NCNT = O_NCUR + 320;
constexpr int O_BOFF = O_NCNT + 512, O_SORT = O_BOFF + 640, O_NOFF = O_SORT + 320;
constexpr int TBIG = G * CAPT + 8, NTILE = TBIG + NE / 8 + G * (NLOC + 5);
static_assert(SMEM_BYTES <= 232448 && CAPT % 16 == 0 && NTILE < (1 << 18), "smem");
static_assert(LZ * NT * 16 == CAPT * 256 && O_W0S % 1024 == 0 && O_OUT <= O_RING && O_SRC + CH * 4 <= O_RING + S_C && G * 128 <= S_C, "staging");
static_assert(O_NOFF + 1024 <= O_RING + 3 * SLOT + S_C && O_W1S + 16384 <= O_RING + 5 * SLOT + S_C, "staging");
static_assert(O_RING % 128 == 0 && SLOT % 128 == 0 && O_W0S <= O_P && O_NOFF % 8 == 0, "layout");
static_assert(G * CH >= NE && NE % 8 == 0 && CH < 4096 && CH / 8 <= 320 && NE < (1 << 21), "chunks");
static_assert(SEGW * (NT / 32) == G && G <= 160 && G % 4 == 0, "segments");
static_assert(NLOC % 4 == 0 && NLOC < 80 && NLOC * 4 <= 320 && NN < 0x3fff && NE / 8 < 0xbfff && NPRIV >= 30, "scan width");

struct __align__(128) Scratch {
    uint32_t keys[G * G * 32];
    uint64_t vals[G * CH];
    uint32_t more[G * CH];
    uint32_t epoch[G * 32];
    uint32_t info[G * NPOOL];
    unsigned done, pad0[31], ticket, pad1[31 + 32 - G * NPOOL % 32];
    uint4 list[NTILE * 16];
};
static_assert(offsetof(Scratch, list) % 128 == 0, "list");
__device__ Scratch g_scratch;
#define TS(i)
#define TSW(i)
#define TV(i, v)

constexpr int SPIN_LIMIT = 1 << 24;

__device__ __forceinline__ void mbar_init(uint32_t a, int c) { asm volatile("mbarrier.init.shared::cta.b64 [%0], %1;" ::"r"(a), "r"(c) : "memory"); }
__device__ __forceinline__ void mbar_expect(uint32_t a, int b) { asm volatile("mbarrier.arrive.expect_tx.shared::cta.b64 _, [%0], %1;" ::"r"(a), "r"(b) : "memory"); }
__device__ __forceinline__ void mbar_arrive(uint32_t a) { asm volatile("mbarrier.arrive.shared::cta.b64 _, [%0];" ::"r"(a) : "memory"); }
__device__ __forceinline__ void mbar_wait(uint32_t a, uint32_t ph) {
    asm volatile("{\n.reg .pred p, q;\n.reg .u32 it;\n"
                 "mbarrier.try_wait.parity.shared::cta.b64 p, [%0], %1;\n"
                 "@p bra DONE;\n"
                 "mov.u32 it, 0;\n"
                 "LOOP:\n"
                 "mbarrier.try_wait.parity.shared::cta.b64 p, [%0], %1;\n"
                 "@p bra DONE;\n"
                 "add.u32 it, it, 1;\n"
                 "setp.gt.u32 q, it, %2;\n"
                 "@q trap;\n"
                 "bra LOOP;\n"
                 "DONE:\n}" ::"r"(a), "r"(ph), "n"(SPIN_LIMIT) : "memory");
}
__device__ __forceinline__ void mbar_wait31(uint32_t a, uint32_t ph) {
    asm volatile("{\n.reg .pred p, q;\n.reg .u32 it;\n.reg .b64 s;\n"
                 "mov.b64 s, {0, %1};\n"
                 "mbarrier.try_wait.shared::cta.b64 p, [%0], s;\n"
                 "@p bra DONE;\n"
                 "mov.u32 it, 0;\n"
                 "LOOP:\n"
                 "mbarrier.try_wait.shared::cta.b64 p, [%0], s;\n"
                 "@p bra DONE;\n"
                 "add.u32 it, it, 1;\n"
                 "setp.gt.u32 q, it, %2;\n"
                 "@q trap;\n"
                 "bra LOOP;\n"
                 "DONE:\n}" ::"r"(a), "r"(ph), "n"(SPIN_LIMIT) : "memory");
}
__device__ __forceinline__ void spin_check(int it) {
    asm volatile("{\n.reg .pred q;\nsetp.gt.s32 q, %0, %1;\n@q trap;\n}" ::"r"(it), "n"(SPIN_LIMIT));
}
__device__ __forceinline__ void ldsm4(uint32_t* r, uint32_t a) { asm volatile("ldmatrix.sync.aligned.m8n8.x4.shared.b16 {%0,%1,%2,%3}, [%4];" : "=r"(r[0]), "=r"(r[1]), "=r"(r[2]), "=r"(r[3]) : "r"(a) : "memory"); }
__device__ __forceinline__ void ldsm4t(uint32_t* r, uint32_t a) { asm volatile("ldmatrix.sync.aligned.m8n8.x4.trans.shared.b16 {%0,%1,%2,%3}, [%4];" : "=r"(r[0]), "=r"(r[1]), "=r"(r[2]), "=r"(r[3]) : "r"(a) : "memory"); }
__device__ __forceinline__ void stsm4t(uint32_t a, uint32_t r0, uint32_t r1, uint32_t r2, uint32_t r3) { asm volatile("stmatrix.sync.aligned.m8n8.x4.trans.shared.b16 [%0], {%1,%2,%3,%4};" ::"r"(a), "r"(r0), "r"(r1), "r"(r2), "r"(r3) : "memory"); }
__device__ __forceinline__ void stsm2t(uint32_t a, uint32_t r0, uint32_t r1) { asm volatile("stmatrix.sync.aligned.m8n8.x2.trans.shared.b16 [%0], {%1,%2};" ::"r"(a), "r"(r0), "r"(r1) : "memory"); }
__device__ __forceinline__ void mma16(float* d, const uint32_t* a, uint32_t b0, uint32_t b1) {
    asm("mma.sync.aligned.m16n8k16.row.col.f32.bf16.bf16.f32 {%0,%1,%2,%3}, {%4,%5,%6,%7}, {%8,%9}, {%0,%1,%2,%3};"
        : "+f"(d[0]), "+f"(d[1]), "+f"(d[2]), "+f"(d[3]) : "r"(a[0]), "r"(a[1]), "r"(a[2]), "r"(a[3]), "r"(b0), "r"(b1));
}
__device__ __forceinline__ void mma8(float* d, uint32_t a0, uint32_t a1, uint32_t b0) {
    asm("mma.sync.aligned.m16n8k8.row.col.f32.bf16.bf16.f32 {%0,%1,%2,%3}, {%4,%5}, {%6}, {%0,%1,%2,%3};"
        : "+f"(d[0]), "+f"(d[1]), "+f"(d[2]), "+f"(d[3]) : "r"(a0), "r"(a1), "r"(b0));
}
__device__ __forceinline__ void mma16z(float* d, const uint32_t* a, uint32_t b0, uint32_t b1) {
    asm("mma.sync.aligned.m16n8k16.row.col.f32.bf16.bf16.f32 {%0,%1,%2,%3}, {%4,%5,%6,%7}, {%8,%9}, {%10,%10,%10,%10};"
        : "=f"(d[0]), "=f"(d[1]), "=f"(d[2]), "=f"(d[3]) : "r"(a[0]), "r"(a[1]), "r"(a[2]), "r"(a[3]), "r"(b0), "r"(b1), "f"(0.f));
}
__device__ __forceinline__ uint32_t pack(float lo, float hi) { uint32_t r; asm("cvt.rn.bf16x2.f32 %0, %1, %2;" : "=r"(r) : "f"(hi), "f"(lo)); return r; }
__device__ __forceinline__ uint32_t hmul(uint32_t a, uint32_t b) { uint32_t r; asm("mul.rn.bf16x2 %0, %1, %2;" : "=r"(r) : "r"(a), "r"(b)); return r; }
__device__ __forceinline__ uint32_t hfma(uint32_t a, uint32_t b, uint32_t c) { uint32_t r; asm("fma.rn.bf16x2 %0, %1, %2, %3;" : "=r"(r) : "r"(a), "r"(b), "r"(c)); return r; }
__device__ __forceinline__ uint4 lds128(uint32_t a) { uint4 v; asm volatile("ld.shared.v4.u32 {%0,%1,%2,%3}, [%4];" : "=r"(v.x), "=r"(v.y), "=r"(v.z), "=r"(v.w) : "r"(a) : "memory"); return v; }
__device__ __forceinline__ void sts128(uint32_t a, uint4 v) { asm volatile("st.shared.v4.u32 [%0], {%1,%2,%3,%4};" ::"r"(a), "r"(v.x), "r"(v.y), "r"(v.z), "r"(v.w) : "memory"); }
__device__ __forceinline__ int lds32(uint32_t a) { int v; asm volatile("ld.shared.u32 %0, [%1];" : "=r"(v) : "r"(a) : "memory"); return v; }
__device__ __forceinline__ void sts32(uint32_t a, int v) { asm volatile("st.shared.u32 [%0], %1;" ::"r"(a), "r"(v) : "memory"); }
__device__ __forceinline__ int atoms_add(uint32_t a, int v) { int r; asm volatile("atom.shared.add.u32 %0, [%1], %2;" : "=r"(r) : "r"(a), "r"(v) : "memory"); return r; }
__device__ __forceinline__ uint32_t ld_rlx(const void* p) { uint32_t v; asm volatile("ld.relaxed.gpu.global.u32 %0, [%1];" : "=r"(v) : "l"(p) : "memory"); return v; }
__device__ __forceinline__ void st_rlx(void* p, uint32_t v) { asm volatile("st.relaxed.gpu.global.u32 [%0], %1;" ::"l"(p), "r"(v) : "memory"); }
__device__ __forceinline__ void bulk(uint32_t dst, const void* g, int n, uint32_t bar) {
    asm volatile("cp.async.bulk.shared::cluster.global.mbarrier::complete_tx::bytes [%0], [%1], %2, [%3];" ::"r"(dst), "l"(g), "r"(n), "r"(bar) : "memory");
}
__device__ __forceinline__ void bulk_st(void* g, uint32_t src, int n) {
    asm volatile("cp.async.bulk.global.shared::cta.bulk_group [%0], [%1], %2;\ncp.async.bulk.commit_group;" ::"l"(g), "r"(src), "r"(n) : "memory");
}
__device__ __forceinline__ uint2 lds64(uint32_t a) { uint2 v; asm volatile("ld.shared.v2.u32 {%0,%1}, [%2];" : "=r"(v.x), "=r"(v.y) : "r"(a) : "memory"); return v; }
__device__ __forceinline__ void sts64(uint32_t a, uint32_t x, uint32_t y) { asm volatile("st.shared.v2.u32 [%0], {%1,%2};" ::"r"(a), "r"(x), "r"(y) : "memory"); }
__device__ __forceinline__ void tma3d(uint32_t dst, const CUtensorMap* m, int c1, int c2, uint32_t bar) {
    asm volatile("cp.async.bulk.tensor.3d.shared::cluster.global.mbarrier::complete_tx::bytes [%0], [%1, {0, %3, %4}], [%2];"
                 ::"r"(dst), "l"(m), "r"(bar), "r"(c1), "r"(c2) : "memory");
}
__device__ __forceinline__ void pf_l2(const void* g, int n) {
    asm volatile("{.reg .pred p; setp.gt.s32 p, %1, 0; @p cp.async.bulk.prefetch.L2.global [%0], %1;}" ::"l"(g), "r"(n) : "memory");
}
__device__ __forceinline__ void fence_async() { asm volatile("fence.proxy.async.shared::cta;" ::: "memory"); }
__device__ __forceinline__ uint64_t madw(uint32_t a, uint32_t b, uint64_t c) { uint64_t r; asm("mad.wide.u32 %0, %1, %2, %3;" : "=l"(r) : "r"(a), "r"(b), "l"(c)); return r; }
__device__ __forceinline__ uint32_t lop_sel(uint32_t a, uint32_t b, uint32_t m) { uint32_t r; asm("lop3.b32 %0, %1, %2, %3, 0xd8;" : "=r"(r) : "r"(a), "r"(b), "r"(m)); return r; }
__device__ __forceinline__ uint32_t opaque(uint32_t v, int lane) { return __shfl_sync(0xffffffffu, v, lane); }
__device__ __forceinline__ void bar_sync(int id, int n) { asm volatile("bar.sync %0, %1;" ::"r"(id), "r"(n) : "memory"); }

__device__ __forceinline__ void wg_rs16(float* d, const uint32_t* a, uint64_t db, int sc) {
    asm volatile("{.reg .pred p; setp.ne.b32 p, %13, 0;\n"
                 "wgmma.mma_async.sync.aligned.m64n16k16.f32.bf16.bf16 {%0,%1,%2,%3,%4,%5,%6,%7}, {%8,%9,%10,%11}, %12, p, 1, 1, 0;}"
                 : "+f"(d[0]), "+f"(d[1]), "+f"(d[2]), "+f"(d[3]), "+f"(d[4]), "+f"(d[5]), "+f"(d[6]), "+f"(d[7])
                 : "r"(a[0]), "r"(a[1]), "r"(a[2]), "r"(a[3]), "l"(db), "r"(sc));
}
__device__ __forceinline__ void wg_rs48(float* d, const uint32_t* a, uint64_t db, int sc) {
    asm volatile("{.reg .pred p; setp.ne.b32 p, %29, 0;\n"
                 "wgmma.mma_async.sync.aligned.m64n48k16.f32.bf16.bf16 {%0,%1,%2,%3,%4,%5,%6,%7,%8,%9,%10,%11,%12,%13,%14,%15,%16,%17,%18,%19,%20,%21,%22,%23}, {%24,%25,%26,%27}, %28, p, 1, 1, 0;}"
                 : "+f"(d[0]), "+f"(d[1]), "+f"(d[2]), "+f"(d[3]), "+f"(d[4]), "+f"(d[5]), "+f"(d[6]), "+f"(d[7]),
                   "+f"(d[8]), "+f"(d[9]), "+f"(d[10]), "+f"(d[11]), "+f"(d[12]), "+f"(d[13]), "+f"(d[14]), "+f"(d[15]),
                   "+f"(d[16]), "+f"(d[17]), "+f"(d[18]), "+f"(d[19]), "+f"(d[20]), "+f"(d[21]), "+f"(d[22]), "+f"(d[23])
                 : "r"(a[0]), "r"(a[1]), "r"(a[2]), "r"(a[3]), "l"(db), "r"(sc));
}
__device__ __forceinline__ void wg_ss48(float* d, uint64_t da, uint64_t db, int sc) {
    asm volatile("{.reg .pred p; setp.ne.b32 p, %26, 0;\n"
                 "wgmma.mma_async.sync.aligned.m64n48k16.f32.bf16.bf16 {%0,%1,%2,%3,%4,%5,%6,%7,%8,%9,%10,%11,%12,%13,%14,%15,%16,%17,%18,%19,%20,%21,%22,%23}, %24, %25, p, 1, 1, 1, 0;}"
                 : "+f"(d[0]), "+f"(d[1]), "+f"(d[2]), "+f"(d[3]), "+f"(d[4]), "+f"(d[5]), "+f"(d[6]), "+f"(d[7]),
                   "+f"(d[8]), "+f"(d[9]), "+f"(d[10]), "+f"(d[11]), "+f"(d[12]), "+f"(d[13]), "+f"(d[14]), "+f"(d[15]),
                   "+f"(d[16]), "+f"(d[17]), "+f"(d[18]), "+f"(d[19]), "+f"(d[20]), "+f"(d[21]), "+f"(d[22]), "+f"(d[23])
                 : "l"(da), "l"(db), "r"(sc));
}

__device__ __forceinline__ int warp_incl(int v) {
#pragma unroll
    for (int o = 1; o < 32; o <<= 1)
        asm volatile("{.reg .pred p; .reg .b32 u; shfl.sync.up.b32 u|p, %0, %1, 0, 0xffffffff; @p add.s32 %0, %0, u;}" : "+r"(v) : "r"(o));
    return v;
}
__device__ __forceinline__ void ldg128(uint32_t* r, const void* p, bool on) {
    asm volatile("{.reg .pred p; setp.ne.u32 p, %5, 0; @p ld.global.nc.v4.u32 {%0,%1,%2,%3}, [%4];}"
                 : "=r"(r[0]), "=r"(r[1]), "=r"(r[2]), "=r"(r[3]) : "l"(p), "r"((uint32_t)on));
}

struct Acc {
    uint32_t p00[4], p110[4], p10[3][4];
    float t01[4], m[3][4];
};

#define LF(m) ldsm4t(f[m], so + xa + m * 256)
#define LY() ldsm4(yb, so + ya)
#define LC() ldsm4(yb + 4, so + yc)
#define LN() ph = lds32(so + S_N)
#define ADV() { asm volatile("@lane0 mbarrier.arrive.shared::cta.b64 _, [%0];" ::"r"(so + S_EMPTY) : "memory"); \
                so = so == sm + O_RING + (NSLOT - 1) * SLOT ? sm + O_RING : so + SLOT; }
#define LA() asm volatile("{\n.reg .pred p, q;\n.reg .b64 s;\n.reg .f32 n;\nmov.b64 s, {0, %7};\nmbarrier.test_wait.shared::cta.b64 p, [%6], s;\n" \
                          "abs.f32 n, %7;\nsetp.gt.and.f32 q, n, 0f00000001, p;\nselp.u32 %4, 1, 0, p;\nselp.u32 %5, 1, 0, q;\n" \
                          "@p ldmatrix.sync.aligned.m8n8.x4.shared.b16 {%0,%1,%2,%3}, [%8];\n}" \
                          : "+r"(a[0]), "+r"(a[1]), "+r"(a[2]), "+r"(a[3]), "=r"(ok), "=r"(go) : "r"(so + S_FULL), "r"(ph), "r"(so + aa) : "memory")
#define RAD(p, s) { float c[4]; mma16z(c, wr[p], a[2 * s], a[2 * s + 1]); R[p][2 * s] = pack(c[0], c[1]); R[p][2 * s + 1] = pack(c[2], c[3]); }
#define MUL(n, x, y) (XS >> n & 1 ? hmul(y, x) : hmul(x, y))
#define FMA(n, x, y, z) (XS >> n & 1 ? hfma(y, x, z) : hfma(x, y, z))
#define ACC(n, x, y, z) z = F ? MUL(n, x, y) : FMA(n, x, y, z)
#define P00(i) ACC(0, f[0][i], R[0][i], A.p00[i ^ XA])
#define P10(k, i) ACC(1, f[1 + k][i], R[3][i], A.p10[k][i ^ XA])
#define S0(k, i) sd[i] = MUL(2, f[1 + k][i], yb[2 * k + (i >> 1)])
#define SD(k, i) sd[i] = FMA(2, f[1 + k][i], yb[2 * k + (i >> 1)], sd[i])
#define P110(i) ACC(3, sd[i], R[1][i], A.p110[i ^ XA])
#define TU(i) u[3][i ^ XU] = MUL(4, f[0][i], R[2][i])
#define TM() if (F) mma16z(A.t01, u[3], yb[6], yb[7]); else mma16(A.t01, u[3], yb[6], yb[7])
#define MU(k, i) u[k][i ^ XU] = MUL(5, f[1 + k][i], R[4][i])
#define MM(k) if (F) mma16z(A.m[k], u[k], yb[6], yb[7]); else mma16(A.m[k], u[k], yb[6], yb[7])
#define PK(v, h) pack(v[2 * (h)], v[2 * (h) + 1])
#define LM() { sts32(na + sof, mt); asm volatile("ld.shared.u16 %0, [%1];" : "=r"(mt) : "r"(so + ya + 48) : "memory"); }
#define FY(k) if (k == 0) mma16z(y, A.p10[0], oh[0][0], oh[0][1]); else mma16(y, k < 3 ? A.p10[k % 3] : A.p00, oh[k][0], oh[k][1])
#define FZ(k) if (k == 0) mma16z(z, A.p110, oh[3][0], oh[3][1]); \
              else if (k == 1) { const uint32_t mp[4] = {PK(A.m[0], XA ^ XU), PK(A.m[0], 1 ^ XA ^ XU), PK(A.m[1], XA ^ XU), PK(A.m[1], 1 ^ XA ^ XU)}; mma16(z, mp, eb[0], eb[1]); } \
              else mma8(z, PK(A.m[2], XA ^ XU), PK(A.m[2], 1 ^ XA ^ XU), eb[2])
#define SX() stsm2t(fx + sof, PK(A.t01, XU), PK(A.t01, 1 ^ XU))
#define SY() stsm4t(fyz + sof, PK(y, XA), PK(y, 1 ^ XA), PK(z, XA), PK(z, 1 ^ XA))
#define X4(op) op(0); op(1); op(2); op(3)
#define Y4(op, k) op(k, 0); op(k, 1); op(k, 2); op(k, 3)
#define XA 1
#define XU 0
#define XS_R 63
#define SEQ_R LN(); LF(1); LF(3); LF(0); LF(2); LC(); RAD(1,0); RAD(1,1); RAD(2,0); RAD(0,0); RAD(0,1); RAD(2,1); RAD(3,0); P00(0); TU(0); \
    P10(0,0); P10(0,1); TU(2); TU(3); RAD(4,1); MU(2,2); MU(2,3); TU(1); TM(); P00(1); RAD(4,0); MU(2,0); MU(2,1); MU(0,0); MU(0,2); \
    RAD(3,1); P10(0,2); P10(0,3); LY(); ADV(); LA(); P00(2); MU(0,3); P00(3); MM(2); MU(0,1); MM(0); P10(2,0); P10(2,2); P10(2,3); P10(2,1); \
    P10(1,0); P10(1,1); P10(1,2); P10(1,3); MU(1,2); S0(2,0); SD(1,0); SD(0,0); P110(0); S0(2,1); SD(1,1); SD(0,1); P110(1); S0(2,2); \
    SD(1,2); SD(0,2); P110(2); MU(1,3); S0(2,3); SD(1,3); SD(0,3); P110(3); MU(1,0); MU(1,1); MM(1);
#define XS_F 0
#define SEQ_F LN(); LM(); LF(0); LC(); LF(1); LF(2); LF(3); LY(); ADV(); FY(0); FZ(0); FY(1); FZ(1); FY(2); FZ(2); FY(3); SX(); SY(); \
    RAD(0, 0); RAD(0, 1); RAD(1, 0); RAD(1, 1); RAD(2, 0); RAD(2, 1); RAD(3, 0); RAD(3, 1); RAD(4, 0); RAD(4, 1); LA(); \
    X4(P00); X4(TU); TM(); Y4(P10, 0); Y4(MU, 0); MM(0); Y4(P10, 1); Y4(MU, 1); MM(1); Y4(P10, 2); Y4(MU, 2); MM(2); \
    Y4(S0, 0); Y4(SD, 1); Y4(SD, 2); X4(P110);

__global__ void __launch_bounds__(NT, 1)
tp_kernel(const int4* __restrict__ dst, const int4* __restrict__ src, const char* __restrict__ rhat, Scratch* __restrict__ gs,
          const char* __restrict__ x, const char* __restrict__ ea, const __nv_bfloat16* __restrict__ eps, char* __restrict__ out,
          const __grid_constant__ CUtensorMap m_wr, const __grid_constant__ CUtensorMap m_w0, const __grid_constant__ CUtensorMap m_w1) {
    extern __shared__ __align__(1024) char smem_raw[];
    constexpr uint32_t sm = 1024;
    spin_check((uint32_t)__cvta_generic_to_shared(smem_raw) == sm ? 0 : 2 * SPIN_LIMIT);
    int t;
    asm volatile("mov.u32 %0, %%tid.x;" : "=r"(t));
    const int w = t >> 5, lane = t & 31, b = blockIdx.x;

    const int g = lane >> 2, q = lane & 3, mat = lane >> 3, r = lane & 7;
    const int e0 = b * CH + t * 8, ne = min(CH, NE - b * CH);
    const bool act = t * 8 < ne;
    uint32_t d[8];
#pragma unroll
    for (int k = 0; k < 2; k++) ldg128(d + 4 * k, dst + e0 / 4 + k, act);
    uint32_t tag = ld_rlx(&gs->epoch[b * 32]), epl;
    asm volatile("ld.global.nc.u16 %0, [%1];" : "=r"(epl) : "l"(eps + min(lane, 26)));
    if (t < 60) sts128(sm + O_BCNT + 16 * t, make_uint4(0, 0, 0, 0));
    if (t == NT - 1) {
#pragma unroll
        for (int i = 0; i < 4; i++) mbar_init(sm + O_WBA + 8 * i, 1);
        fence_async();
        mbar_expect(sm + O_WBC, ne * 10); mbar_expect(sm + O_WBA, 20480); mbar_expect(sm + O_WBB, 81920); mbar_expect(sm + O_WBD, 81920);
        spin_check(tag);
        bulk(sm + O_RH, rhat + b * (CH * 6), ne * 6, sm + O_WBC);
        bulk(sm + O_SRC, src + b * (CH / 4), ne * 4, sm + O_WBC);
        tma3d(sm + O_WR0, &m_wr, 0, 0, sm + O_WBA);
        tma3d(sm + O_WR1, &m_wr, 0, 5, sm + O_WBA);
        WLD(0);
    }
    if (t == 320) {
#pragma unroll
        for (int i = 0; i < NSLOT; i++) {
            sts128(sm + O_RING + i * SLOT + S_C + 64, make_uint4(0, 0, 0, 0));
            mbar_init(sm + O_RING + i * SLOT + S_FULL, 32); mbar_init(sm + O_RING + i * SLOT + S_EMPTY, 8);
        }
    }
#pragma unroll
    for (int k = 0; k < LZ; k++) sts128(sm + O_L + 16 * (t + k * NT), make_uint4(0, 0, 0, 0));
    if (t < 80) sts32(sm + O_NCNT + 4 * t, t <= NLOC ? 4 * t : 0);
    if (t < 68) sts32(sm + O_NODE + 4 * t, 0);
    uint32_t ba[8], rk[8];
    auto pfx = [&](int r0, int n) {
        if (n) pf_l2(x + (b * NLOC + r0) * 1024, min(n, NN - b * NLOC - r0) * 1024);
    };
    if (w < 10) bar_sync(1, 320);
    tag = (tag + 1) << 30;
    if (act) {
#pragma unroll
        for (int i = 0; i < 8; i++) {
            const uint32_t l = __umulhi(d[i], (uint32_t)((1ull << 32) / G + 1));
            ba[i] = d[i] * 4 - l * (4 * G);
            d[i] = l * 4 + (tag + ((e0 + i + 1) << 9) + 4);
            rk[i] = atoms_add(sm + O_BCNT + ba[i], 4);
        }
#pragma unroll
        for (int i = 0; i < 8; i++)
            asm volatile("{.reg .pred p; setp.lt.u32 p, %2, 124; @p st.shared.u32 [%0], %1;}"
                         ::"r"(sm + O_KT + ba[i] * 32 + ((ba[i] + rk[i]) & 127)), "r"(d[i]), "r"(rk[i]) : "memory");
    }
    TS(0);
    __syncthreads();
    {
        int v[5], sum = 0;
#pragma unroll
        for (int i = 0; i < 5; i++) { v[i] = lds32(sm + O_BCNT + 4 * (lane * 5 + i)); sum += v[i]; }
        int e = warp_incl(sum) - sum;
        if (w == 10) {
#pragma unroll
            for (int i = 0; i < 5; i++) {
                const int k = lane * 5 + i;
                if (k < G) sts32(sm + O_KT + k * 128 + ((k * 4 + 124) & 127), tag | v[i] << 10 | e >> 2);
                e += v[i];
            }
            __syncwarp();
            if (lane == 0) {
                fence_async();
                bulk_st(&gs->keys[b * (G * 32)], sm + O_KT, G * 128);
                pfx(0, PFA);
            }
        } else {
#pragma unroll
            for (int i = 0; i < 5; i++) { sts32(sm + O_BOFF + 4 * (lane * 5 + i), e); e += v[i]; }
        }
        __syncwarp();
    }
    TS(11);
    const uint32_t sw = (uint32_t)(((2 * (w & 3) + (mat & 1)) ^ r) * 16 + ((mat >> 1) * 8 + r) * 128);
    uint32_t wr[5][4];
    const uint32_t* kp = &gs->keys[(w * SEGW * G + b) * 32 + ((lane + b) & 31)];
    uint32_t kv[SEGW + 1], ho[SEGW + 1], nk[SEGW + 1], old;
    if (act) {
        uint32_t mx = 0;
#pragma unroll
        for (int i = 0; i < 8; i++) { mx = max(mx, rk[i]); ba[i] = rk[i] + lds32(sm + O_BOFF + ba[i]); }
        if (mx >= 124) {
#pragma unroll
            for (int i = 0; i < 8; i++)
                if (rk[i] >= 124) st_rlx(&gs->more[b * CH + (ba[i] >> 2)], d[i]);
        }
    }
    if (w < 8) {
        mbar_wait(sm + O_WBA, 0);
#pragma unroll
        for (int p = 0; p < 5; p++) {
            const int c = 2 * p + (w >> 2);
            ldsm4t(wr[p], sm + (c < 5 ? O_WR0 : O_WR1 - 5 * 2048) + c * 2048 + sw);
        }
    } else {
        const uint64_t xl = (uint64_t)(x - 1024 + r * 16) - (tag >> 6), al = (uint64_t)(ea - 32 + (lane & 1) * 16) - (tag >> 4);
        const uint64_t ml = (uint64_t)gs->list + lane * 8;
        const uint32_t row = 0x76b821a3u >> 4 * r & 15, row0 = 0xc5bfe0cbu >> 4 * r & 15;
        const uint32_t c[13] = {(uint32_t)xl, (uint32_t)(xl >> 32), (uint32_t)al, (uint32_t)(al >> 32), (uint32_t)ml, (uint32_t)(ml >> 32),
            mat * 2048u + (r ^ 2 * mat) * 16, mat * 2048u + 1024 + (r ^ 2 * mat ^ 1) * 16,
            S_A + (lane & 2) * 128u + g * 32 + ((lane ^ lane >> 4) & 1) * 16, S_C + (mat & 1 ? row : row0) * 16, lane & 1 ? 16u : 9u, lane & 30u,
            lane == 4 ? 0xffff0000u : 0u};
#pragma unroll
        for (int i = 0; i < 20; i++) wr[i >> 2][i & 3] = i < 13 ? opaque(c[i % 13], lane) : 0;
    }
    TS(21);
    mbar_wait(sm + O_WBC, 0);
    TS(22);
    if (act) {
        uint32_t s[8], y[12];
#pragma unroll
        for (int k = 0; k < 3; k++) *(uint4*)&y[4 * k] = lds128(sm + O_RH + t * 48 + k * 16);
#pragma unroll
        for (int k = 0; k < 2; k++) *(uint4*)&s[4 * k] = lds128(sm + O_SRC + t * 32 + k * 16);
#pragma unroll
        for (int i = 0; i < 8; i++) {
            const int k = 3 * i / 2;
            sts64(sm + O_OUT + ba[i] * 2, __byte_perm(y[k], s[i] + (tag >> 16) + 1, i & 1 ? 0x5432 : 0x5410),
                  i & 1 ? y[k + 1] : __byte_perm(y[k], y[k + 1], 0x5432));
        }
    }
    TS(12);
#define VS 0
    auto stv = [&](int p) {
        if (w < 10 && p == (VS & 3)) asm volatile("bar.arrive 4, 352;" ::: "memory");
        if (w == 11 && p == (VS >> 2)) {
            bar_sync(4, 352);
            if (lane == 0) { fence_async(); bulk_st(&gs->vals[b * CH], sm + O_OUT, ne * 8); pfx(PFA, PFB); }
            __syncwarp();
        }
    };
    stv(0);

    const uint32_t am = lane < 31 ? 511 : 0, none = tag | (320 + 4 * lane);
    auto check = [&]() {
        old = 0;
#pragma unroll
        for (int j = 0; j < SEGW; j++) {
            ho[j] = __shfl_sync(0xffffffffu, kv[j], 31);
            kv[j] = ho[j] >= (lane < 31 ? tag + ((lane + 1) << 12) : 0u) ? kv[j] : none;
            old |= kv[j] ^ tag;
        }
        return __any_sync(0xffffffffu, old >> 30);
    };
#pragma unroll
    for (int j = 0; j < SEGW; j++) kv[j] = ld_rlx(kp + j * (G * 32));
    stv(1);
    TS(1);
    if (t == 352) WLD(1);
    TV(19, 0);
    for (int it = 0; check(); it++) {
        spin_check(it);
        if (it == 0) TS(20);
        TV(19, (it + 1) * 100);
#pragma unroll
        for (int j = 0; j < SEGW; j++)
            if (__any_sync(0xffffffffu, (kv[j] ^ tag) >> 30)) kv[j] = ld_rlx(kp + j * (G * 32));
    }
    TS(3);
    stv(2);
    if (t == 352) WLD(2);
    kv[SEGW] = none; ho[SEGW] = 0;
    bool slow = false;
    const bool more = __any_sync(0xffffffffu, lane == 31 && (old & 0xfe0000));
    if (more) {
        int c = lane;
#pragma unroll
        for (int j = 0; j < SEGW; j++) {
            const int n = max((int)(ho[j] >> 12 & 0xfff) - 31, 0);
            if ((unsigned)c < (unsigned)n) ho[SEGW] = j * CH + (ho[j] & 0xfff) + 31 + c - lane;
            c -= n;
        }
        slow = lane == 31 && c < 0;
        if (c < 0 && lane < 31)
            for (int it = 0; ((kv[SEGW] = ld_rlx(&gs->more[w * SEGW * CH + lane + ho[SEGW]])) ^ tag) >> 30; it++) spin_check(it);
        __syncwarp();
    }
    uint32_t na_[SEGW + 1];
#pragma unroll
    for (int j = 0; j <= SEGW; j++) {
        na_[j] = (kv[j] & am) | (none & 511 & ~am);
        nk[j] = atoms_add(sm + O_NCNT + na_[j], 512);
    }
    auto visit = [&](auto f) {
#pragma unroll 1
        for (int j = 0; j < SEGW; j++) {
            const uint32_t* kl = &gs->keys[((w * SEGW + j) * G + b) * 32];
            const uint32_t h = ld_rlx(kl + ((31 + b) & 31));
#pragma unroll 1
            for (int i = lane; i < (h >> 12 & 0xfff); i += 32) {
                const int o = (w * SEGW + j) * CH + (h & 0xfff) + i;
                uint32_t k;
                int it = 0;
                do { k = ld_rlx(i < 31 ? kl + ((i + b) & 31) : &gs->more[o]); spin_check(it++); } while ((k ^ tag) >> 30);
                f(k, o, i);
            }
        }
    };
    slow = __syncthreads_or(slow);
    if (slow) {
        if (t < 80) sts32(sm + O_NCNT + 4 * t, t <= NLOC ? 4 * t : 0);
        __syncthreads();
        visit([&](uint32_t k, int, int) { atoms_add(sm + O_NCNT + (k & 511), 512); });
        __syncthreads();
    }
    TS(4);
    if (t == 352) { WLD(3); pfx(PFA + PFB, PFC); }
    uint64_t vp = (uint64_t)&gs->vals[w * SEGW * CH + lane], vv[SEGW + 1];
#pragma unroll
    for (int j = 0; j <= SEGW; j++) vv[j] = tag;
    auto ldv = [&](bool again) {
#pragma unroll
        for (int j = 0; j <= SEGW; j++)
            asm volatile("{.reg .pred p; setp.lt.u32 p, %2, 320; @p ld.relaxed.gpu.global.b64 %0, [%1];}" : "+l"(vv[j])
                         : "l"(madw(j < SEGW ? ho[j] & 0xfff : ho[j], 8, vp) + (j < SEGW ? j * CH * 8 : 0)),
                           "r"(again ? (((uint32_t)vv[j] ^ tag) >> 30 ? 0 : 320) : na_[j]) : "memory");
    };
    if (w < 10) {
        const uint32_t key = lds32(sm + O_NCNT + 4 + (t & ~3));
        uint4 k[5];
#pragma unroll
        for (int i = 0; i < 5; i++) k[i] = lds128(sm + O_NCNT + q * 80 + i * 16);
        uint32_t c[4] = {0, 0, 0, 0};
#pragma unroll
        for (int i = 0; i < 5; i++) { c[0] += (key - k[i].x) >> 31; c[1] += (key - k[i].y) >> 31; c[2] += (key - k[i].z) >> 31; c[3] += (key - k[i].w) >> 31; }
        int rank = c[0] + c[1] + c[2] + c[3];
        rank += __shfl_xor_sync(0xffffffffu, rank, 1);
        rank += __shfl_xor_sync(0xffffffffu, rank, 2);
        if (ASC && rank < 2 * NPRIV) rank = (2 * NPRIV - 1 - rank) ^ 1;
        if (t < NLOC * 4) sts32(sm + O_SORT + 4 * rank, key);
    }
    __syncthreads();
    TS(2);
    const bool on = lane < NLOC / 4;
    const uint4 k4 = lds128(sm + O_SORT + 16 * (on ? lane : 0));
    const uint32_t ks[4] = {k4.x, k4.y, k4.z, k4.w};
    const int n0 = on ? max(1u, (ks[0] + 3584) >> 12) : 0, n1 = on ? max(1u, (ks[2] + 3584) >> 12) : 0;
    const int u2 = warp_incl(n0 + n1), u1 = u2 - n1, u0 = u1 - n0;
    const int total = __shfl_sync(0xffffffffu, u2, 31);
    slow |= total > CAPT;
    int gbase = b * CAPT + 1;
    if (on) {
#pragma unroll
        for (int i = 0; i < 4; i++) {
            const int a = ks[i] & 511, node = a * (G / 4) - G + b, o = (i >> 1 ? u1 : u0) * 256 + (i & 1) * 16;
            const uint32_t mk = (node < NN ? node + 1 : 0) + ((i >> 1 ? n1 : n0) << 16);
            sts64(sm + O_NOFF + 2 * a, o - (a >> 4), mk + a * 16);
            if (!slow && ks[i] < 512) sts32(sm + O_L + 4 + o, mk);
        }
    }
    __syncwarp();
    if (!slow) {
        uint32_t mk[SEGW + 1];
        TS(13);
        if (t == 352) { pfx(PFA + PFB + PFC, PFD); asm volatile("cp.async.bulk.wait_group.read 0;" ::: "memory"); }
        ldv(false);
        if (t == 352) WLD(4);
#pragma unroll
        for (int j = 0; j <= SEGW; j++) {
            const uint2 o = lds64(sm + O_NOFF + 2 * na_[j]);
            mk[j] = o.y - nk[j] * 16; nk[j] = o.x + (nk[j] >> 4);
        }
        for (int it = 0;; it++) {
            old = 0;
#pragma unroll
            for (int j = 0; j <= SEGW; j++) old |= (uint32_t)vv[j] ^ tag;
            if (!__any_sync(0xffffffffu, old >> 30)) break;
            spin_check(it);
            vp = __shfl_sync(0xffffffffu, vp, lane);
            ldv(true);
        }
#pragma unroll
        for (int j = 0; j <= SEGW; j++)
            asm volatile("{.reg .pred p; setp.ne.u32 p, %3, %5; @p st.shared.v4.u32 [%0], {%1,%2,%3,%4};}"
                         ::"r"(sm + O_L + nk[j]), "r"(kv[j]), "r"(mk[j]), "r"((uint32_t)vv[j]), "r"((uint32_t)(vv[j] >> 32)), "r"(tag) : "memory");
        if (na_[SEGW] < 320) gs->more[w * SEGW * CH + lane + ho[SEGW]] = 0;
    } else {
        int so = 0;
        if (t == 352) WLD(4);
#pragma unroll
        for (int j = 0; j < SEGW; j++) so += ho[j] & 0xfff;
        if (lane == 0) atoms_add(sm + O_SUM, so);
        if (t == 352) asm volatile("cp.async.bulk.wait_group.read 0;" ::: "memory");
        __syncthreads();
        gbase = TBIG + (lds32(sm + O_SUM) >> 3) + (NLOC + 5) * b;
        auto put = [&](uint32_t k, uint64_t e, uint32_t a, int rank) {
            const uint2 o = lds64(sm + O_NOFF + 2 * a);
            gs->list[gbase * 16 + ((o.x + (a >> 4)) >> 4) + rank * 2] = make_uint4(k, o.y - a * 16 - (rank << 13), e, e >> 32);
        };
        visit([&](uint32_t k, int o, int i) {
            uint64_t e;
            int it = 0;
            do {
                asm volatile("ld.relaxed.gpu.global.b64 %0, [%1];" : "=l"(e) : "l"(&gs->vals[o]) : "memory");
                spin_check(it++);
            } while (((uint32_t)e ^ tag) >> 30);
            if (i >= 31) gs->more[o] = 0;
            put(k, e, k & 511, atoms_add(sm + O_NCUR + (k & 511), 1));
        });
#pragma unroll 1
        for (int i = 0; i < 4; i++) {
            const uint32_t k = i == 0 ? ks[0] : i == 1 ? ks[1] : i == 2 ? ks[2] : ks[3];
#pragma unroll 1
            for (int p = (k >> 9) + w; p < (i >> 1 ? n1 : n0) * 8; p += NT / 32) put(0, 0, k & 511, p);
        }
        __threadfence();
    }
    const uint32_t iw0 = (gbase + u0) << 12 | n0, iw1 = (gbase + u1) << 12 | n1;
    __syncthreads();
    TS(5);

    if (w >= 8) {
        asm volatile("setmaxnreg.dec.sync.aligned.u32 " STR(PREG) ";");
        const int h = __reduce_max_sync(0xffffffffu, w & 3);
        gbase = __reduce_min_sync(0xffffffffu, iw0) >> 12;
        int pos = gbase + h, end = __reduce_max_sync(0xffffffffu, lane == NPRIV / 2 ? (NPRIV & 1 ? iw1 : iw0) : 0) >> 12;
        const int bytes = gbase < TBIG ? ((__reduce_max_sync(0xffffffffu, iw0) >> 12) - gbase) * 256 : 0;
        const uint32_t ring = sm + O_RING;
        const uint64_t xl = wr[0][0] | (uint64_t)wr[0][1] << 32, al = wr[0][2] | (uint64_t)wr[0][3] << 32, ml = wr[1][0] | (uint64_t)wr[1][1] << 32;
        const uint32_t xoff[2] = {wr[1][2], wr[1][3]}, aoff = wr[2][0], coff = wr[2][1], sh = wr[2][2], ial = wr[2][3], sel = wr[3][0];
        auto lde = [&](uint2& e, int p) {
            asm volatile("{.reg .pred p; setp.gt.s32 p, %3, 0; @p ld.relaxed.gpu.global.v2.u32 {%0,%1}, [%2];}" : "+r"(e.x), "+r"(e.y) : "l"(madw(p, 256, ml)), "r"(p) : "memory");
        };
        uint2 e0[3] = {};
#pragma unroll
        for (int k = 0; k < 3; k++) {
            e0[k] = lds64(sm + O_L - 2048 + k * 1024 + t * 8);
            lde(e0[k], bytes ? 0 : pos + 4 * k);
        }
        if (h == 3) fence_async();
        pos += 4;

        int ev = 0, state = -2, tk = 0, nr = 0;
        uint32_t inf = 0;
        int ii = 0;
        auto take = [&]() {
            int v = 0;
            asm volatile("{.reg .pred p; setp.eq.s32 p, %2, 0; @p atom.relaxed.gpu.global.add.u32 %0, [%1], 1;}" : "+r"(v) : "l"(&gs->ticket), "r"(lane) : "memory");
            return v;
        };
        auto resolve = [&]() {
            const int k = __reduce_max_sync(0xffffffffu, tk);
            inf = tag;
            if (k < G * NPOOL) { const int l = k / G; ii = (k - l * G) * NPOOL + l; inf = ld_rlx(&gs->info[ii]);
                tk = (STAG) && ((NPRIV + 1 + nr + (STAG)) & 7) == 0 && k >= G * NPOOL - THETA ? G * NPOOL : take(); }
        };
        uint32_t so = ring + h * SLOT, ph = 0x80000000u;
        uint32_t spins = 0;
        asm volatile(".reg .pred z<5>;");
        while (true) {
            const uint2 e = e0[0];
            const uint32_t o = e.x >> sh, id = __shfl_sync(0xffffffffu, o, ial);
            uint32_t s[4];
#pragma unroll
            for (int j = 0; j < 4; j++) s[j] = __shfl_sync(0xffffffffu, o, 2 * j + 1, 8);
            const uint32_t nx = so == ring + (NSLOT - 1) * SLOT ? ph : ph ^ 0x80000000u, ey = lop_sel(e.y, nx, sel);
            const uint64_t ga = madw(id, 32, al);
            uint64_t gx[4];
#pragma unroll
            for (int j = 0; j < 4; j++) gx[j] = madw(s[j], 1024, xl);
            const uint32_t da = so + aoff, dx[2] = {so + xoff[0], so + xoff[1]}, dc = so + coff;
            asm volatile("setp.eq.u32 z0, %0, 0;\nsetp.eq.u32 z1, %1, 0;\nsetp.eq.u32 z2, %2, 0;\nsetp.eq.u32 z3, %3, 0;\nsetp.eq.u32 z4, %4, 0;\n"
                         PFI
                         ::"r"(NULLP(s[0])), "r"(NULLP(s[1])), "r"(NULLP(s[2])), "r"(NULLP(s[3])), "r"(id), "l"(ga), "r"(da), "r"(dx[0]), "r"(dx[1]), "r"(dc));
            lde(e0[0], state < 0 ? 0 : pos);
            asm volatile("{\n.reg .pred p;\n.reg .b64 s;\nmov.b64 s, {0, %2};\n"
                         "LOOP:\nmbarrier.try_wait.shared::cta.b64 p, [%1], s;\n@p bra DONE;\n"
                         "add.u32 %0, %0, 1;\nsetp.gt.u32 p, %0, %3;\n@p trap;\nbra LOOP;\nDONE:\n}"
                         : "+r"(spins) : "r"(so + S_EMPTY), "r"(ph), "n"(SPIN_LIMIT) : "memory");
            asm volatile("cp.async.cg.shared.global [%0], [%1], 16, z4;" ::"r"(da), "l"(ga) : "memory");
#define ROW(j) _Pragma("unroll") for (int k = 0; k < 8; k++) \
                asm volatile("cp.async.cg.shared.global [%0], [%1], 16, z" #j ";" ::"r"(dx[j >> 1] + (j & 1) * 8192 + k * 128), "l"(gx[j] + k * 128) : "memory")
            X4(ROW);
            stsm2t(dc, e.x, ey);
            asm volatile("cp.async.mbarrier.arrive.noinc.shared::cta.b64 [%0];" ::"r"(so + S_FULL) : "memory");
            const bool wrap = NSLOT == 5 ? so != ring : so >= ring + (NSLOT - 4) * SLOT;
            ph ^= wrap ? 0x80000000u : 0u;
            so = wrap ? so - (NSLOT - 4) * SLOT : so + 4 * SLOT;
            pos += 4;
            if (pos >= ev) {
                if (state < 0) {
                    e0[0] = e0[1]; e0[1] = e0[2];
                    if (state == -2) {
                        if (h == 0) TSW(24);
                        if (h == 3) TSW(25);
                        if (h & 1) bar_sync(7, NT);
                        else asm volatile("bar.arrive 7, %0;" ::"n"(NT) : "memory");
                        if (h == 3) {
                            if (lane == 0) {
                                if (bytes) bulk_st(gs->list + gbase * 16, sm + O_L, bytes);
                                asm volatile("cp.async.bulk.wait_group.read 0;" ::: "memory");
                            }
                            __syncwarp();
                            if (lane == 0) {
                                for (int j = 0; j < 5; j++) tma3d(sm + O_W1 + j * 16384, &m_w1, 64 + 64 * j, 0, sm + O_WBB);
                            }
                            __syncwarp();
                        }
                        state = -1;
                    } else {
                        if (h == 3) {
                            if (lane == 0) asm volatile("cp.async.bulk.wait_group 0;\nfence.proxy.async;" ::: "memory");
                            __syncwarp();
                            const int i = opaque(2 * lane - NPRIV, lane);
                            if ((unsigned)i < NPOOL) st_rlx(&gs->info[b * NPOOL + i], tag | iw0);
                            if ((unsigned)(i + 1) < NPOOL) st_rlx(&gs->info[b * NPOOL + i + 1], tag | iw1);
                        }
                        bar_sync(6, 128);
                        ev = h ? end : end - 12; state = h ? 2 : 0;
                    }
                } else if (state == 0) { ev = end - 6; state = 1; tk = take(); }
                else if (state == 1) { resolve(); ev = end; state = 2; }
                else {
                    if (state == 3) break;
                    do {
                        const uint32_t mb = sm + O_MB + (nr & 15) * 8;
                        uint32_t rg;
                        nr++;
                        if (h == 0) {
                            for (int it = 0; (rg = __reduce_max_sync(0xffffffffu, inf ^ tag)) >> 30; it++) { spin_check(it); inf = ld_rlx(&gs->info[ii]); }
                            asm volatile("st.release.cta.shared.b64 [%0], %1;" ::"r"(mb), "l"(rg | (uint64_t)nr << 32) : "memory");
                            if (rg) resolve();
                        } else {
                            uint64_t m;
                            for (int it = 0;; it++) {
                                asm volatile("ld.acquire.cta.shared.b64 %0, [%1];" : "=l"(m) : "r"(mb) : "memory");
                                if (__all_sync(0xffffffffu, (int)(m >> 32) == nr)) break;
                                spin_check(it);
                            }
                            rg = __reduce_max_sync(0xffffffffu, (uint32_t)m);
                        }
                        pos = rg ? (int)(rg >> 12) + pos - end : 0;
                        end = rg ? (rg >> 12) + (rg & 0xfff) : 1;
                        state = rg ? 2 : 3;
                    } while (pos >= end);
                    ev = end;
                }
            }
        }
        mbar_wait31(so + S_EMPTY, ph);
        TSW(8 + (h & 1));
        if (lane == 0) sts32(so + S_N, 0);
        mbar_arrive(so + S_FULL);
        if (t == 256) {
            gs->epoch[b * 32] = (tag >> 30) % 3;
            if (atomicInc(&gs->done, G - 1) == G - 1) gs->ticket = 0;
        }
        asm volatile("cp.async.wait_all;" ::: "memory");
    } else {
        asm volatile("setmaxnreg.inc.sync.aligned.u32 " STR(CREG) ";");
        const uint32_t xa = opaque(((mat >> 1) * 8 + r) * 1024 + (w >> 2) * 128 + (((2 * (w & 3) + (mat & 1)) ^ r) * 16), lane);
        const uint32_t aa = opaque(S_A + ((mat >> 1) * 8 + r) * 32 + (((mat & 1) ^ (r >> 2)) * 16), lane);
        const uint32_t ya = opaque(S_C + (mat & 1) * 80 + (mat >> 1) * 16, lane);
        const uint32_t yc = opaque(S_C + (mat < 2 ? mat * 80 + 32 : (r >> 2) == (mat & 1) && q < 3 ? (mat & 1) * 80 + q * 16 : 64), lane);
        const uint32_t na = opaque(sm + O_NODE + mat * 4, lane);
        const uint32_t pw = sm + O_P + w * PW;
        const uint32_t fx = opaque(pw + (q < 3 ? P_1P0 + 2 * q * PSBO : P_1P1 + PSBO) + (mat & 1) * 128 + (r >> 2) * PSBO, lane);
        const uint32_t fyz = opaque(pw + (q < 3 ? (mat < 2 ? P_1P1 : P_1P2) + 2 * q * PSBO : mat < 2 ? P_0P0 : P_0P1) + (mat & 1) * 128 + (r >> 2) * PSBO, lane);
        uint32_t oh[4][2];
#pragma unroll
        for (int c = 0; c < 8; c++) oh[c & 3][c >> 2] = opaque(g == c ? 0x3F803F80u : 0u, lane);
        uint32_t eb[3];
#pragma unroll
        for (int k = 0; k < 3; k++) {
            const int i = (g & 3) * 9 + (q & 1) * 6 + k;
            const uint32_t lo = __shfl_sync(0xffffffffu, epl, i), hi = __shfl_sync(0xffffffffu, epl, i + 3);
            eb[k] = (g & 3) < 3 && (q >> 1) == (g >> 2) ? (q & 1 ? lo : lo | hi << 16) : 0u;
        }
        asm volatile(".reg .pred lane0;\nsetp.eq.u32 lane0, %0, 0;" ::"r"(lane));
        uint32_t w0[16][4], w1[4][4];
        mbar_wait(sm + O_WBD, 0);
#pragma unroll
        for (int k = 0; k < 16; k++) ldsm4t(w0[k], sm + O_W0S + (w >> 2) * 32768 + k * 2048 + sw);
#pragma unroll
        for (int k = 0; k < 4; k++) ldsm4t(w1[k], sm + O_W1S + (w >> 2) * 8192 + k * 2048 + sw);
        bar_sync(7, NT);
        TS(6);
        Acc A;
#pragma unroll
        for (int i = 0; i < 4; i++) { A.p00[i] = A.p110[i] = A.p10[0][i] = A.p10[1][i] = A.p10[2][i] = 0; A.t01[i] = A.m[0][i] = A.m[1][i] = A.m[2][i] = 0.f; }
        uint32_t room = 144 - (STAG) * 16;
        uint32_t so = sm + O_RING, ph, a[4], ok, go, mt = 0;
        mbar_wait(so + S_FULL, 0);
        ldsm4(a, so + aa);
        TS(7);
        while (true) {
            {
                constexpr int F = 1, XS = XS_F;
                uint32_t yb[8], f[4][4], R[5][4], u[4][4], sd[4];
                float y[4], z[4];
                const uint32_t sof = room & 112;
                SEQ_F
                room -= 16;
            }
            if (!(go && room)) {
                const uint32_t pu = __reduce_max_sync(0xffffffffu, ph);
                if (!room || !pu) {
                    asm volatile("fence.proxy.async.shared::cta;" ::: "memory");
                    mbar_wait(sm + O_WBB, 0);
                    bar_sync(1, 256);
                    float d0[8], d1[24];
                    const uint32_t wg = __reduce_max_sync(0xffffffffu, w >> 2);
                    const uint64_t db = (uint64_t)((sm + O_P) >> 4) | (8ull << 16) | ((uint64_t)(PSBO / 16) << 32);
                    const uint32_t da = ((sm + O_W1) >> 4 | 1 << 16) + wg * 512;
                    asm volatile("wgmma.fence.sync.aligned;" ::: "memory");
#pragma unroll
                    for (int k = 0; k < 16; k++) wg_rs16(d0, w0[k], db + (((k & 7) * PW + ((k >> 3) ? P_0P1 : P_0P0)) >> 4), k);
                    asm volatile("wgmma.commit_group.sync.aligned;" ::: "memory");
#pragma unroll
                    for (int k = 0; k < 4; k++) wg_rs48(d1, w1[k], db + ((k * PW + P_1P0) >> 4), k);
#pragma unroll
                    for (int k = 4; k < 24; k++)
                        wg_ss48(d1, (da + (k / 4 - 1) * 1024 + (k & 3) * 128) | (64ull << 32) | (1ull << 62), db + (((k & 7) * PW + ((k >> 3) == 0 ? P_1P0 : (k >> 3) == 1 ? P_1P1 : P_1P2)) >> 4), k);
                    asm volatile("wgmma.commit_group.sync.aligned;" ::: "memory");
                    const uint2 n0 = lds64(sm + O_NODE + mat * 16), n1 = lds64(sm + O_NODE + 64 + mat * 16);
                    const bool v0 = (mat * 16 - 16 & 112) >= room, v1 = mat * 16 + 48 >= room;
                    const uint32_t nd[4] = {v0 ? n0.x : 0, v1 ? n1.x : 0, v0 ? n0.y : 0, v1 ? n1.y : 0};
                    const uint64_t op = (uint64_t)(out - 1024 + (w & 3) * 256 + (w >> 2) * 128 + r * 16);
                    uint64_t oa[4];
#pragma unroll
                    for (int it = 0; it < 4; it++) oa[it] = madw(nd[it], 1024, op);
                    uint32_t sg = sm + O_P + (w & 4) * PW + ((mat >> 1) * 8 + r) * 128 + (((2 * (w & 3) + (mat & 1)) ^ r) * 16);
                    uint32_t sl = pw + mat * 128 + (r ^ mat) * 16, sl2 = pw + 512 + mat * 128 + (r ^ mat ^ 4) * 16;
                    asm volatile("wgmma.wait_group.sync.aligned 1;" ::: "memory");
#pragma unroll
                    for (int i = 0; i < 8; i++) asm volatile("" : "+f"(d0[i])::"memory");
                    uint32_t o[4][4], chk = sg & sl & sl2;
                    float gt[8];
#pragma unroll
                    for (int i = 0; i < 8; i++) {
                        asm("ex2.approx.ftz.f32 %0, %1;" : "=f"(gt[i]) : "f"(d0[i] * -1.4426950408889634f));
                        asm("rcp.approx.ftz.f32 %0, %1;" : "=f"(gt[i]) : "f"(gt[i] + 1.f));
                        chk &= __float_as_uint(gt[i]);
                    }
#pragma unroll
                    for (int i = 0; i < 4; i++) { o[0][i] = pack(d0[2 * i], d0[2 * i + 1]); chk &= o[0][i] & (uint32_t)(oa[i] >> 32); }
                    sts32(sm + O_TRASH, chk);
                    asm volatile("wgmma.wait_group.sync.aligned 0;" ::: "memory");
#pragma unroll
                    for (int i = 0; i < 24; i++) asm volatile("" : "+f"(d1[i])::"memory");
                    bar_sync(1, 256);
#pragma unroll
                    for (int i = 0; i < 4; i++)
#pragma unroll
                        for (int j = 0; j < 3; j++) o[1 + j][i] = pack(d1[8 * j + 2 * i] * gt[2 * i], d1[8 * j + 2 * i + 1] * gt[2 * i + 1]);
#pragma unroll
                    for (int j = 0; j < 4; j++) stsm4t(sg + j * PW, o[j][0], o[j][1], o[j][2], o[j][3]);
                    bar_sync(2 + wg, 128);
                    uint4 v[4];
#pragma unroll
                    for (int it = 0; it < 4; it++) v[it] = lds128((it & 1 ? sl2 : sl) + (it >> 1) * 1024);
#pragma unroll
                    for (int it = 0; it < 4; it++)
                        asm volatile("{.reg .pred p; setp.ne.u32 p, %5, 0; @p st.global.v4.u32 [%0], {%1,%2,%3,%4};}"
                                     ::"l"(oa[it]), "r"(v[it].x), "r"(v[it].y), "r"(v[it].z), "r"(v[it].w), "r"(nd[it]) : "memory");
                    __syncwarp();
                    room = 128;
                    if (!pu) break;
                }
                if (!ok) { mbar_wait31(so + S_FULL, pu); ldsm4(a, so + aa); }
                if (!(pu & 0xfffe)) continue;
            }
            while (true) {
                do {
                    constexpr int F = 0, XS = XS_R;
                    uint32_t yb[8], f[4][4], R[5][4], u[4][4], sd[4];
                    SEQ_R
                } while (go);
                if (ok) break;
                const uint32_t pu = __reduce_max_sync(0xffffffffu, ph);
                mbar_wait31(so + S_FULL, pu); ldsm4(a, so + aa);
                if (!(pu & 0xfffe)) break;
            }
        }
        TS(10);
    }
}

typedef CUresult (*EncFn)(CUtensorMap*, CUtensorMapDataType, cuuint32_t, void*, const cuuint64_t*, const cuuint64_t*,
                          const cuuint32_t*, const cuuint32_t*, CUtensorMapInterleave, CUtensorMapSwizzle,
                          CUtensorMapL2promotion, CUtensorMapFloatOOBfill);

void make_map(EncFn fn, CUtensorMap* m, void* p, int rows, int cols, int brows, int rank, int bblk, CUtensorMapSwizzle swz) {
    cuuint64_t dims[3] = {(cuuint64_t)(rank == 3 ? 64 : cols), (cuuint64_t)rows, (cuuint64_t)cols / 64}, strides[2] = {(cuuint64_t)cols * 2, 128};
    cuuint32_t box[3] = {64, (cuuint32_t)brows, (cuuint32_t)bblk}, es[3] = {1, 1, 1};
    fn(m, CU_TENSOR_MAP_DATA_TYPE_BFLOAT16, rank, p, dims, strides, box, es, CU_TENSOR_MAP_INTERLEAVE_NONE,
       swz, CU_TENSOR_MAP_L2_PROMOTION_NONE, CU_TENSOR_MAP_FLOAT_OOB_FILL_NONE);
}

}

extern "C" void kernel_launch(void* const* d_in, const int* in_sizes, int n_in, void* d_out, int out_size) {
    static EncFn enc = nullptr;
    static void* scratch = nullptr;
    if (!enc) {
        void* fn = nullptr;
        cudaDriverEntryPointQueryResult qr;
        cudaGetDriverEntryPoint("cuTensorMapEncodeTiled", &fn, cudaEnableDefault, &qr);
        enc = (EncFn)fn;
        cudaGetSymbolAddress(&scratch, g_scratch);
        cudaFuncSetAttribute(tp_kernel, cudaFuncAttributeMaxDynamicSharedMemorySize, SMEM_BYTES);
    }
    CUtensorMap m_wr, m_w0, m_w1;
    make_map(enc, &m_wr, d_in[5], 16, 640, 16, 3, 5, CU_TENSOR_MAP_SWIZZLE_128B);
    make_map(enc, &m_w0, d_in[6], 256, 128, 256, 3, 2, CU_TENSOR_MAP_SWIZZLE_128B);
    make_map(enc, &m_w1, d_in[7], 384, 128, 64, 3, 2, CU_TENSOR_MAP_SWIZZLE_128B);
    tp_kernel<<<G, NT, SMEM_BYTES>>>((const int4*)d_in[4], (const int4*)d_in[3], (const char*)d_in[1], (Scratch*)scratch,
                                     (const char*)d_in[0], (const char*)d_in[2], (const __nv_bfloat16*)d_in[8], (char*)d_out,
                                     m_wr, m_w0, m_w1);
}
```

```cpp
#include <cuda_runtime.h>
#include <cuda_bf16.h>
#include <cuda.h>
#include <stdint.h>
#include <stddef.h>

namespace {

constexpr int NN = 10000;
constexpr int NE = 320000;
constexpr int G = 132;
constexpr int NT = 384;
constexpr int CH = 2432;
constexpr int NLOC = (NN + G - 1) / G;
#define NPOOL 4
constexpr int NPAIR = NLOC / 2, NPRIV = NPAIR - NPOOL;
constexpr int SEGW = 11;

#define NSLOT 6
#define PFA 16
#define PFB 20
#define PFC 20
#define PFD 20
#define STAG (b & 7)
#define ASC (b & 1)
#define THETA G
#define PFI "@!z4 prefetch.global.L2 [%5];"
#define WP 0x22255
#define WLD(p) { _Pragma("unroll") for (int j = 0; j < 5; j++) if ((WP >> 4 * j & 15) == p) \
    tma3d(sm + (j < 4 ? O_W0S + j * 16384 : O_W1S), j < 4 ? &m_w0 : &m_w1, (j & 3) * 64, 0, sm + O_WBD); }
#define INV 0
#define NULLP(v) v
#define CREG 224
#define PREG 56
#define STR2(x) #x
#define STR(x) STR2(x)

constexpr int S_A = 16384, S_C = S_A + 512, S_FULL = S_C + 144, S_EMPTY = S_FULL + 8, S_N = S_C + 160, SLOT = S_C + 256;

constexpr int PSBO = 272;
constexpr int PB1 = 5 * PSBO + 256, PB0 = PSBO + 256;
constexpr int P_1P0 = 0, P_1P1 = PB1, P_0P1 = 2 * PB1, P_0P0 = P_0P1 + PB0, P_1P2 = P_0P0 + PB0;
constexpr int PW = P_1P2 + PB1;

constexpr int up1k(int a) { return (a + 1023) / 1024 * 1024; }
constexpr int O_W1 = 0;
constexpr int O_P = 81920;
constexpr int O_RING = O_P + 8 * PW;
constexpr int O_WBA = O_RING + 6 * SLOT, O_WBB = O_WBA + 8, O_WBC = O_WBA + 16, O_WBD = O_WBA + 24, O_TRASH = O_WBA + 32, O_NODE = O_WBA + 48;
constexpr int O_SUM = O_NODE + 128, O_MB = O_SUM + 16;
constexpr int SMEM_BYTES = O_MB + 128;
constexpr int CAPT = 192;
constexpr int O_L = 0, LZ = CAPT * 256 / (NT * 16), O_W0S = O_L + CAPT * 256, O_OUT = O_W0S + 65536, O_SRC = O_OUT + CH * 8;
constexpr int O_KT = O_RING + SLOT, O_RH = O_RING + 2 * SLOT;
constexpr int O_WR0 = up1k(O_RING + 3 * SLOT), O_WR1 = up1k(O_RING + 4 * SLOT), O_W1S = up1k(O_RING + 5 * SLOT);
constexpr int O_BCNT = O_WR0 + 10240, O_NCUR = O_BCNT + 640, O_NCNT = O_NCUR + 320;
constexpr int O_BOFF = O_NCNT + 512, O_SORT = O_BOFF + 640, O_NOFF = O_SORT + 320;
constexpr int TBIG = G * CAPT + 8, NTILE = TBIG + NE / 8 + G * (NLOC + 5);
static_assert(SMEM_BYTES <= 232448 && CAPT % 16 == 0 && NTILE < (1 << 18), "smem");
static_assert(LZ * NT * 16 == CAPT * 256 && O_W0S % 1024 == 0 && O_OUT <= O_RING && O_SRC + CH * 4 <= O_RING + S_C && G * 128 <= S_C, "staging");
static_assert(O_NOFF + 1024 <= O_RING + 3 * SLOT + S_C && O_W1S + 16384 <= O_RING + 5 * SLOT + S_C, "staging");
static_assert(O_RING % 128 == 0 && SLOT % 128 == 0 && O_W0S <= O_P && O_NOFF % 8 == 0, "layout");
static_assert(G * CH >= NE && NE % 8 == 0 && CH < 4096 && CH / 8 <= 320 && NE < (1 << 21), "chunks");
static_assert(SEGW * (NT / 32) == G && G <= 160 && G % 4 == 0, "segments");
static_assert(NLOC % 4 == 0 && NLOC < 80 && NLOC * 4 <= 320 && NN < 0x3fff && NE / 8 < 0xbfff && NPRIV >= 30, "scan width");

struct __align__(128) Scratch {
    uint32_t keys[G * G * 32];
    uint64_t vals[G * CH];
    uint32_t more[G * CH];
    uint32_t epoch[G * 32];
    uint32_t info[G * NPOOL];
    unsigned done, pad0[31], ticket, pad1[31 + 32 - G * NPOOL % 32];
    uint4 list[NTILE * 16];
};
static_assert(offsetof(Scratch, list) % 128 == 0, "list");
__device__ Scratch g_scratch;
#define TS(i)
#define TSW(i)
#define TV(i, v)

constexpr int SPIN_LIMIT = 1 << 24;

__device__ __forceinline__ void mbar_init(uint32_t a, int c) { asm volatile("mbarrier.init.shared::cta.b64 [%0], %1;" ::"r"(a), "r"(c) : "memory"); }
__device__ __forceinline__ void mbar_expect(uint32_t a, int b) { asm volatile("mbarrier.arrive.expect_tx.shared::cta.b64 _, [%0], %1;" ::"r"(a), "r"(b) : "memory"); }
__device__ __forceinline__ void mbar_arrive(uint32_t a) { asm volatile("mbarrier.arrive.shared::cta.b64 _, [%0];" ::"r"(a) : "memory"); }
__device__ __forceinline__ void mbar_wait(uint32_t a, uint32_t ph) {
    asm volatile("{\n.reg .pred p, q;\n.reg .u32 it;\n"
                 "mbarrier.try_wait.parity.shared::cta.b64 p, [%0], %1;\n"
                 "@p bra DONE;\n"
                 "mov.u32 it, 0;\n"
                 "LOOP:\n"
                 "mbarrier.try_wait.parity.shared::cta.b64 p, [%0], %1;\n"
                 "@p bra DONE;\n"
                 "add.u32 it, it, 1;\n"
                 "setp.gt.u32 q, it, %2;\n"
                 "@q trap;\n"
                 "bra LOOP;\n"
                 "DONE:\n}" ::"r"(a), "r"(ph), "n"(SPIN_LIMIT) : "memory");
}
__device__ __forceinline__ void mbar_wait31(uint32_t a, uint32_t ph) {
    asm volatile("{\n.reg .pred p, q;\n.reg .u32 it;\n.reg .b64 s;\n"
                 "mov.b64 s, {0, %1};\n"
                 "mbarrier.try_wait.shared::cta.b64 p, [%0], s;\n"
                 "@p bra DONE;\n"
                 "mov.u32 it, 0;\n"
                 "LOOP:\n"
                 "mbarrier.try_wait.shared::cta.b64 p, [%0], s;\n"
                 "@p bra DONE;\n"
                 "add.u32 it, it, 1;\n"
                 "setp.gt.u32 q, it, %2;\n"
                 "@q trap;\n"
                 "bra LOOP;\n"
                 "DONE:\n}" ::"r"(a), "r"(ph), "n"(SPIN_LIMIT) : "memory");
}
__device__ __forceinline__ void spin_check(int it) {
    asm volatile("{\n.reg .pred q;\nsetp.gt.s32 q, %0, %1;\n@q trap;\n}" ::"r"(it), "n"(SPIN_LIMIT));
}
__device__ __forceinline__ void ldsm4(uint32_t* r, uint32_t a) { asm volatile("ldmatrix.sync.aligned.m8n8.x4.shared.b16 {%0,%1,%2,%3}, [%4];" : "=r"(r[0]), "=r"(r[1]), "=r"(r[2]), "=r"(r[3]) : "r"(a) : "memory"); }
__device__ __forceinline__ void ldsm4t(uint32_t* r, uint32_t a) { asm volatile("ldmatrix.sync.aligned.m8n8.x4.trans.shared.b16 {%0,%1,%2,%3}, [%4];" : "=r"(r[0]), "=r"(r[1]), "=r"(r[2]), "=r"(r[3]) : "r"(a) : "memory"); }
__device__ __forceinline__ void stsm4t(uint32_t a, uint32_t r0, uint32_t r1, uint32_t r2, uint32_t r3) { asm volatile("stmatrix.sync.aligned.m8n8.x4.trans.shared.b16 [%0], {%1,%2,%3,%4};" ::"r"(a), "r"(r0), "r"(r1), "r"(r2), "r"(r3) : "memory"); }
__device__ __forceinline__ void stsm2t(uint32_t a, uint32_t r0, uint32_t r1) { asm volatile("stmatrix.sync.aligned.m8n8.x2.trans.shared.b16 [%0], {%1,%2};" ::"r"(a), "r"(r0), "r"(r1) : "memory"); }
__device__ __forceinline__ void mma16(float* d, const uint32_t* a, uint32_t b0, uint32_t b1) {
    asm("mma.sync.aligned.m16n8k16.row.col.f32.bf16.bf16.f32 {%0,%1,%2,%3}, {%4,%5,%6,%7}, {%8,%9}, {%0,%1,%2,%3};"
        : "+f"(d[0]), "+f"(d[1]), "+f"(d[2]), "+f"(d[3]) : "r"(a[0]), "r"(a[1]), "r"(a[2]), "r"(a[3]), "r"(b0), "r"(b1));
}
__device__ __forceinline__ void mma8(float* d, uint32_t a0, uint32_t a1, uint32_t b0) {
    asm("mma.sync.aligned.m16n8k8.row.col.f32.bf16.bf16.f32 {%0,%1,%2,%3}, {%4,%5}, {%6}, {%0,%1,%2,%3};"
        : "+f"(d[0]), "+f"(d[1]), "+f"(d[2]), "+f"(d[3]) : "r"(a0), "r"(a1), "r"(b0));
}
__device__ __forceinline__ void mma16z(float* d, const uint32_t* a, uint32_t b0, uint32_t b1) {
    asm("mma.sync.aligned.m16n8k16.row.col.f32.bf16.bf16.f32 {%0,%1,%2,%3}, {%4,%5,%6,%7}, {%8,%9}, {%10,%10,%10,%10};"
        : "=f"(d[0]), "=f"(d[1]), "=f"(d[2]), "=f"(d[3]) : "r"(a[0]), "r"(a[1]), "r"(a[2]), "r"(a[3]), "r"(b0), "r"(b1), "f"(0.f));
}
__device__ __forceinline__ uint32_t pack(float lo, float hi) { uint32_t r; asm("cvt.rn.bf16x2.f32 %0, %1, %2;" : "=r"(r) : "f"(hi), "f"(lo)); return r; }
__device__ __forceinline__ uint32_t hmul(uint32_t a, uint32_t b) { uint32_t r; asm("mul.rn.bf16x2 %0, %1, %2;" : "=r"(r) : "r"(a), "r"(b)); return r; }
__device__ __forceinline__ uint32_t hfma(uint32_t a, uint32_t b, uint32_t c) { uint32_t r; asm("fma.rn.bf16x2 %0, %1, %2, %3;" : "=r"(r) : "r"(a), "r"(b), "r"(c)); return r; }
__device__ __forceinline__ uint4 lds128(uint32_t a) { uint4 v; asm volatile("ld.shared.v4.u32 {%0,%1,%2,%3}, [%4];" : "=r"(v.x), "=r"(v.y), "=r"(v.z), "=r"(v.w) : "r"(a) : "memory"); return v; }
__device__ __forceinline__ void sts128(uint32_t a, uint4 v) { asm volatile("st.shared.v4.u32 [%0], {%1,%2,%3,%4};" ::"r"(a), "r"(v.x), "r"(v.y), "r"(v.z), "r"(v.w) : "memory"); }
__device__ __forceinline__ int lds32(uint32_t a) { int v; asm volatile("ld.shared.u32 %0, [%1];" : "=r"(v) : "r"(a) : "memory"); return v; }
__device__ __forceinline__ void sts32(uint32_t a, int v) { asm volatile("st.shared.u32 [%0], %1;" ::"r"(a), "r"(v) : "memory"); }
__device__ __forceinline__ int atoms_add(uint32_t a, int v) { int r; asm volatile("atom.shared.add.u32 %0, [%1], %2;" : "=r"(r) : "r"(a), "r"(v) : "memory"); return r; }
__device__ __forceinline__ uint32_t ld_rlx(const void* p) { uint32_t v; asm volatile("ld.relaxed.gpu.global.u32 %0, [%1];" : "=r"(v) : "l"(p) : "memory"); return v; }
__device__ __forceinline__ void st_rlx(void* p, uint32_t v) { asm volatile("st.relaxed.gpu.global.u32 [%0], %1;" ::"l"(p), "r"(v) : "memory"); }
__device__ __forceinline__ void bulk(uint32_t dst, const void* g, int n, uint32_t bar) {
    asm volatile("cp.async.bulk.shared::cluster.global.mbarrier::complete_tx::bytes [%0], [%1], %2, [%3];" ::"r"(dst), "l"(g), "r"(n), "r"(bar) : "memory");
}
__device__ __forceinline__ void bulk_st(void* g, uint32_t src, int n) {
    asm volatile("cp.async.bulk.global.shared::cta.bulk_group [%0], [%1], %2;\ncp.async.bulk.commit_group;" ::"l"(g), "r"(src), "r"(n) : "memory");
}
__device__ __forceinline__ uint2 lds64(uint32_t a) { uint2 v; asm volatile("ld.shared.v2.u32 {%0,%1}, [%2];" : "=r"(v.x), "=r"(v.y) : "r"(a) : "memory"); return v; }
__device__ __forceinline__ void sts64(uint32_t a, uint32_t x, uint32_t y) { asm volatile("st.shared.v2.u32 [%0], {%1,%2};" ::"r"(a), "r"(x), "r"(y) : "memory"); }
__device__ __forceinline__ void tma3d(uint32_t dst, const CUtensorMap* m, int c1, int c2, uint32_t bar) {
    asm volatile("cp.async.bulk.tensor.3d.shared::cluster.global.mbarrier::complete_tx::bytes [%0], [%1, {0, %3, %4}], [%2];"
                 ::"r"(dst), "l"(m), "r"(bar), "r"(c1), "r"(c2) : "memory");
}
__device__ __forceinline__ void pf_l2(const void* g, int n) {
    asm volatile("{.reg .pred p; setp.gt.s32 p, %1, 0; @p cp.async.bulk.prefetch.L2.global [%0], %1;}" ::"l"(g), "r"(n) : "memory");
}
__device__ __forceinline__ void fence_async() { asm volatile("fence.proxy.async.shared::cta;" ::: "memory"); }
__device__ __forceinline__ uint64_t madw(uint32_t a, uint32_t b, uint64_t c) { uint64_t r; asm("mad.wide.u32 %0, %1, %2, %3;" : "=l"(r) : "r"(a), "r"(b), "l"(c)); return r; }
__device__ __forceinline__ uint32_t lop_sel(uint32_t a, uint32_t b, uint32_t m) { uint32_t r; asm("lop3.b32 %0, %1, %2, %3, 0xd8;" : "=r"(r) : "r"(a), "r"(b), "r"(m)); return r; }
__device__ __forceinline__ uint32_t opaque(uint32_t v, int lane) { return __shfl_sync(0xffffffffu, v, lane); }
__device__ __forceinline__ void bar_sync(int id, int n) { asm volatile("bar.sync %0, %1;" ::"r"(id), "r"(n) : "memory"); }

__device__ __forceinline__ void wg_rs16(float* d, const uint32_t* a, uint64_t db, int sc) {
    asm volatile("{.reg .pred p; setp.ne.b32 p, %13, 0;\n"
                 "wgmma.mma_async.sync.aligned.m64n16k16.f32.bf16.bf16 {%0,%1,%2,%3,%4,%5,%6,%7}, {%8,%9,%10,%11}, %12, p, 1, 1, 0;}"
                 : "+f"(d[0]), "+f"(d[1]), "+f"(d[2]), "+f"(d[3]), "+f"(d[4]), "+f"(d[5]), "+f"(d[6]), "+f"(d[7])
                 : "r"(a[0]), "r"(a[1]), "r"(a[2]), "r"(a[3]), "l"(db), "r"(sc));
}
__device__ __forceinline__ void wg_rs48(float* d, const uint32_t* a, uint64_t db, int sc) {
    asm volatile("{.reg .pred p; setp.ne.b32 p, %29, 0;\n"
                 "wgmma.mma_async.sync.aligned.m64n48k16.f32.bf16.bf16 {%0,%1,%2,%3,%4,%5,%6,%7,%8,%9,%10,%11,%12,%13,%14,%15,%16,%17,%18,%19,%20,%21,%22,%23}, {%24,%25,%26,%27}, %28, p, 1, 1, 0;}"
                 : "+f"(d[0]), "+f"(d[1]), "+f"(d[2]), "+f"(d[3]), "+f"(d[4]), "+f"(d[5]), "+f"(d[6]), "+f"(d[7]),
                   "+f"(d[8]), "+f"(d[9]), "+f"(d[10]), "+f"(d[11]), "+f"(d[12]), "+f"(d[13]), "+f"(d[14]), "+f"(d[15]),
                   "+f"(d[16]), "+f"(d[17]), "+f"(d[18]), "+f"(d[19]), "+f"(d[20]), "+f"(d[21]), "+f"(d[22]), "+f"(d[23])
                 : "r"(a[0]), "r"(a[1]), "r"(a[2]), "r"(a[3]), "l"(db), "r"(sc));
}
__device__ __forceinline__ void wg_ss48(float* d, uint64_t da, uint64_t db, int sc) {
    asm volatile("{.reg .pred p; setp.ne.b32 p, %26, 0;\n"
                 "wgmma.mma_async.sync.aligned.m64n48k16.f32.bf16.bf16 {%0,%1,%2,%3,%4,%5,%6,%7,%8,%9,%10,%11,%12,%13,%14,%15,%16,%17,%18,%19,%20,%21,%22,%23}, %24, %25, p, 1, 1, 1, 0;}"
                 : "+f"(d[0]), "+f"(d[1]), "+f"(d[2]), "+f"(d[3]), "+f"(d[4]), "+f"(d[5]), "+f"(d[6]), "+f"(d[7]),
                   "+f"(d[8]), "+f"(d[9]), "+f"(d[10]), "+f"(d[11]), "+f"(d[12]), "+f"(d[13]), "+f"(d[14]), "+f"(d[15]),
                   "+f"(d[16]), "+f"(d[17]), "+f"(d[18]), "+f"(d[19]), "+f"(d[20]), "+f"(d[21]), "+f"(d[22]), "+f"(d[23])
                 : "l"(da), "l"(db), "r"(sc));
}

__device__ __forceinline__ int warp_incl(int v) {
#pragma unroll
    for (int o = 1; o < 32; o <<= 1)
        asm volatile("{.reg .pred p; .reg .b32 u; shfl.sync.up.b32 u|p, %0, %1, 0, 0xffffffff; @p add.s32 %0, %0, u;}" : "+r"(v) : "r"(o));
    return v;
}
__device__ __forceinline__ void ldg128(uint32_t* r, const void* p, bool on) {
    asm volatile("{.reg .pred p; setp.ne.u32 p, %5, 0; @p ld.global.nc.v4.u32 {%0,%1,%2,%3}, [%4];}"
                 : "=r"(r[0]), "=r"(r[1]), "=r"(r[2]), "=r"(r[3]) : "l"(p), "r"((uint32_t)on));
}

struct Acc {
    uint32_t p00[4], p110[4], p10[3][4];
    float t01[4], m[3][4];
};

#define LF(m) ldsm4t(f[m], so + xa + m * 256)
#define LY() ldsm4(yb, so + ya)
#define LC() ldsm4(yb + 4, so + yc)
#define LN() ph = lds32(so + S_N)
#define ADV() { asm volatile("@lane0 mbarrier.arrive.shared::cta.b64 _, [%0];" ::"r"(so + S_EMPTY) : "memory"); \
                so = so == sm + O_RING + (NSLOT - 1) * SLOT ? sm + O_RING : so + SLOT; }
#define LA() asm volatile("{\n.reg .pred p, q;\n.reg .b64 s;\n.reg .f32 n;\nmov.b64 s, {0, %7};\nmbarrier.test_wait.shared::cta.b64 p, [%6], s;\n" \
                          "abs.f32 n, %7;\nsetp.gt.and.f32 q, n, 0f00000001, p;\nselp.u32 %4, 1, 0, p;\nselp.u32 %5, 1, 0, q;\n" \
                          "@p ldmatrix.sync.aligned.m8n8.x4.shared.b16 {%0,%1,%2,%3}, [%8];\n}" \
                          : "+r"(a[0]), "+r"(a[1]), "+r"(a[2]), "+r"(a[3]), "=r"(ok), "=r"(go) : "r"(so + S_FULL), "r"(ph), "r"(so + aa) : "memory")
#define RAD(p, s) { float c[4]; mma16z(c, wr[p], a[2 * s], a[2 * s + 1]); R[p][2 * s] = pack(c[0], c[1]); R[p][2 * s + 1] = pack(c[2], c[3]); }
#define MUL(n, x, y) (XS >> n & 1 ? hmul(y, x) : hmul(x, y))
#define FMA(n, x, y, z) (XS >> n & 1 ? hfma(y, x, z) : hfma(x, y, z))
#define ACC(n, x, y, z) z = F ? MUL(n, x, y) : FMA(n, x, y, z)
#define P00(i) ACC(0, f[0][i], R[0][i], A.p00[i ^ XA])
#define P10(k, i) ACC(1, f[1 + k][i], R[3][i], A.p10[k][i ^ XA])
#define S0(k, i) sd[i] = MUL(2, f[1 + k][i], yb[2 * k + (i >> 1)])
#define SD(k, i) sd[i] = FMA(2, f[1 + k][i], yb[2 * k + (i >> 1)], sd[i])
#define P110(i) ACC(3, sd[i], R[1][i], A.p110[i ^ XA])
#define TU(i) u[3][i ^ XU] = MUL(4, f[0][i], R[2][i])
#define TM() if (F) mma16z(A.t01, u[3], yb[6], yb[7]); else mma16(A.t01, u[3], yb[6], yb[7])
#define MU(k, i) u[k][i ^ XU] = MUL(5, f[1 + k][i], R[4][i])
#define MM(k) if (F) mma16z(A.m[k], u[k], yb[6], yb[7]); else mma16(A.m[k], u[k], yb[6], yb[7])
#define PK(v, h) pack(v[2 * (h)], v[2 * (h) + 1])
#define LM() { sts32(na + sof, mt); asm volatile("ld.shared.u16 %0, [%1];" : "=r"(mt) : "r"(so + ya + 48) : "memory"); }
#define FY(k) if (k == 0) mma16z(y, A.p10[0], oh[0][0], oh[0][1]); else mma16(y, k < 3 ? A.p10[k % 3] : A.p00, oh[k][0], oh[k][1])
#define FZ(k) if (k == 0) mma16z(z, A.p110, oh[3][0], oh[3][1]); \
              else if (k == 1) { const uint32_t mp[4] = {PK(A.m[0], XA ^ XU), PK(A.m[0], 1 ^ XA ^ XU), PK(A.m[1], XA ^ XU), PK(A.m[1], 1 ^ XA ^ XU)}; mma16(z, mp, eb[0], eb[1]); } \
              else mma8(z, PK(A.m[2], XA ^ XU), PK(A.m[2], 1 ^ XA ^ XU), eb[2])
#define SX() stsm2t(fx + sof, PK(A.t01, XU), PK(A.t01, 1 ^ XU))
#define SY() stsm4t(fyz + sof, PK(y, XA), PK(y, 1 ^ XA), PK(z, XA), PK(z, 1 ^ XA))
#define X4(op) op(0); op(1); op(2); op(3)
#define Y4(op, k) op(k, 0); op(k, 1); op(k, 2); op(k, 3)
#define XA 0
#define XU 1
#define XS_R 63
#define SEQ_R LC(); LF(2); LF(1); LN(); RAD(2,0); LY(); RAD(2,1); LF(3); LF(0); ADV(); RAD(4,0); RAD(1,0); RAD(4,1); RAD(1,1); MU(1,0); MU(1,2); MU(1,1); \
    MU(1,3); MM(1); RAD(0,1); P00(2); P00(3); RAD(0,0); P00(0); P00(1); TU(0); TU(2); TU(1); TU(3); S0(0,0); SD(2,0); SD(1,0); TM(); S0(0,2); \
    SD(2,2); SD(1,2); S0(0,3); SD(2,3); SD(1,3); S0(0,1); SD(2,1); SD(1,1); MU(0,0); MU(0,2); MU(0,3); MU(0,1); MM(0); P110(0); P110(2); \
    P110(1); P110(3); RAD(3,1); P10(0,2); P10(0,3); RAD(3,0); LA(); P10(0,0); P10(0,1); P10(2,2); P10(2,3); P10(2,0); P10(2,1); P10(1,1); \
    P10(1,0); MU(2,1); MU(2,0); MU(2,3); MU(2,2); MM(2); P10(1,3); P10(1,2);
#define XS_F 0
#define SEQ_F LN(); LM(); LF(0); LC(); LF(1); LF(2); LF(3); LY(); ADV(); FY(0); FZ(0); FY(1); FZ(1); FY(2); FZ(2); FY(3); SX(); SY(); \
    RAD(0, 0); RAD(0, 1); RAD(1, 0); RAD(1, 1); RAD(2, 0); RAD(2, 1); RAD(3, 0); RAD(3, 1); RAD(4, 0); RAD(4, 1); LA(); \
    X4(P00); X4(TU); TM(); Y4(P10, 0); Y4(MU, 0); MM(0); Y4(P10, 1); Y4(MU, 1); MM(1); Y4(P10, 2); Y4(MU, 2); MM(2); \
    Y4(S0, 0); Y4(SD, 1); Y4(SD, 2); X4(P110);

__global__ void __launch_bounds__(NT, 1)
tp_kernel(const int4* __restrict__ dst, const int4* __restrict__ src, const char* __restrict__ rhat, Scratch* __restrict__ gs,
          const char* __restrict__ x, const char* __restrict__ ea, const __nv_bfloat16* __restrict__ eps, char* __restrict__ out,
          const __grid_constant__ CUtensorMap m_wr, const __grid_constant__ CUtensorMap m_w0, const __grid_constant__ CUtensorMap m_w1) {
    extern __shared__ __align__(1024) char smem_raw[];
    constexpr uint32_t sm = 1024;
    spin_check((uint32_t)__cvta_generic_to_shared(smem_raw) == sm ? 0 : 2 * SPIN_LIMIT);
    int t;
    asm volatile("mov.u32 %0, %%tid.x;" : "=r"(t));
    const int w = t >> 5, lane = t & 31, b = blockIdx.x;

    const int g = lane >> 2, q = lane & 3, mat = lane >> 3, r = lane & 7;
    const int e0 = b * CH + t * 8, ne = min(CH, NE - b * CH);
    const bool act = t * 8 < ne;
    uint32_t d[8];
#pragma unroll
    for (int k = 0; k < 2; k++) ldg128(d + 4 * k, dst + e0 / 4 + k, act);
    uint32_t tag = ld_rlx(&gs->epoch[b * 32]), epl;
    asm volatile("ld.global.nc.u16 %0, [%1];" : "=r"(epl) : "l"(eps + min(lane, 26)));
    if (t < 60) sts128(sm + O_BCNT + 16 * t, make_uint4(0, 0, 0, 0));
    if (t == NT - 1) {
#pragma unroll
        for (int i = 0; i < 4; i++) mbar_init(sm + O_WBA + 8 * i, 1);
        fence_async();
        mbar_expect(sm + O_WBC, ne * 10); mbar_expect(sm + O_WBA, 20480); mbar_expect(sm + O_WBB, 81920); mbar_expect(sm + O_WBD, 81920);
        WLD(6);
        spin_check(tag);
        bulk(sm + O_RH, rhat + b * (CH * 6), ne * 6, sm + O_WBC);
        bulk(sm + O_SRC, src + b * (CH / 4), ne * 4, sm + O_WBC);
        tma3d(sm + O_WR0, &m_wr, 0, 0, sm + O_WBA);
        tma3d(sm + O_WR1, &m_wr, 0, 5, sm + O_WBA);
        WLD(0);
    }
    if (t == 320) {
#pragma unroll
        for (int i = 0; i < NSLOT; i++) {
            sts128(sm + O_RING + i * SLOT + S_C + 64, make_uint4(0, 0, 0, 0));
            mbar_init(sm + O_RING + i * SLOT + S_FULL, 32); mbar_init(sm + O_RING + i * SLOT + S_EMPTY, 8);
        }
    }
#pragma unroll
    for (int k = 0; k < LZ; k++) sts128(sm + O_L + 16 * (t + k * NT), make_uint4(0, 0, 0, 0));
    if (t < 80) sts32(sm + O_NCNT + 4 * t, t <= NLOC ? 4 * t : 0);
    if (t < 68) sts32(sm + O_NODE + 4 * t, 0);
    uint32_t ba[8], rk[8];
    auto pfx = [&](int r0, int n) {
        if (n) pf_l2(x + (b * NLOC + r0) * 1024, min(n, NN - b * NLOC - r0) * 1024);
    };
    if (w < 10) bar_sync(1, 320);
    tag = (tag + 1) << 30;
    if (act) {
#pragma unroll
        for (int i = 0; i < 8; i++) {
            const uint32_t l = __umulhi(d[i], (uint32_t)((1ull << 32) / G + 1));
            ba[i] = d[i] * 4 - l * (4 * G);
            d[i] = l * 4 + (tag + ((e0 + i + 1) << 9) + 4);
            rk[i] = atoms_add(sm + O_BCNT + ba[i], 4);
        }
#pragma unroll
        for (int i = 0; i < 8; i++)
            asm volatile("{.reg .pred p; setp.lt.u32 p, %2, 124; @p st.shared.u32 [%0], %1;}"
                         ::"r"(sm + O_KT + ba[i] * 32 + ((ba[i] + rk[i]) & 127)), "r"(d[i]), "r"(rk[i]) : "memory");
    }
    TS(0);
    __syncthreads();
    {
        int v[5], sum = 0;
#pragma unroll
        for (int i = 0; i < 5; i++) { v[i] = lds32(sm + O_BCNT + 4 * (lane * 5 + i)); sum += v[i]; }
        int e = warp_incl(sum) - sum;
        if (w == 10) {
#pragma unroll
            for (int i = 0; i < 5; i++) {
                const int k = lane * 5 + i;
                if (k < G) sts32(sm + O_KT + k * 128 + ((k * 4 + 124) & 127), tag | v[i] << 10 | e >> 2);
                e += v[i];
            }
            __syncwarp();
            if (lane == 0) {
                fence_async();
                bulk_st(&gs->keys[b * (G * 32)], sm + O_KT, G * 128);
                pfx(0, PFA);
                WLD(5);
            }
        } else {
#pragma unroll
            for (int i = 0; i < 5; i++) { sts32(sm + O_BOFF + 4 * (lane * 5 + i), e); e += v[i]; }
        }
        __syncwarp();
    }
    TS(11);
    const uint32_t sw = (uint32_t)(((2 * (w & 3) + (mat & 1)) ^ r) * 16 + ((mat >> 1) * 8 + r) * 128);
    uint32_t wr[5][4];
    const uint32_t* kp = &gs->keys[(w * SEGW * G + b) * 32 + ((lane + b) & 31)];
    uint32_t kv[SEGW + 1], ho[SEGW + 1], nk[SEGW + 1], old;
    if (act) {
        uint32_t mx = 0;
#pragma unroll
        for (int i = 0; i < 8; i++) { mx = max(mx, rk[i]); ba[i] = rk[i] + lds32(sm + O_BOFF + ba[i]); }
        if (mx >= 124) {
#pragma unroll
            for (int i = 0; i < 8; i++)
                if (rk[i] >= 124) st_rlx(&gs->more[b * CH + (ba[i] >> 2)], d[i]);
        }
    }
#define WRP 0
    auto ldwr = [&]() {
    if (w < 8) {
        mbar_wait(sm + O_WBA, 0);
#pragma unroll
        for (int p = 0; p < 5; p++) {
            const int c = 2 * p + (w >> 2);
            ldsm4t(wr[p], sm + (c < 5 ? O_WR0 : O_WR1 - 5 * 2048) + c * 2048 + sw);
        }
    } else {
        const uint64_t xl = (uint64_t)(x - 1024 + r * 16) - (tag >> 6), al = (uint64_t)(ea - 32 + (lane & 1) * 16) - (tag >> 4);
        const uint64_t ml = (uint64_t)gs->list + lane * 8;
        const uint32_t row = 0x76b821a3u >> 4 * r & 15, row0 = 0xc5bfe0cbu >> 4 * r & 15;
        const uint32_t c[13] = {(uint32_t)xl, (uint32_t)(xl >> 32), (uint32_t)al, (uint32_t)(al >> 32), (uint32_t)ml, (uint32_t)(ml >> 32),
            mat * 2048u + (r ^ 2 * mat) * 16, mat * 2048u + 1024 + (r ^ 2 * mat ^ 1) * 16,
            S_A + (lane & 2) * 128u + g * 32 + ((lane ^ lane >> 4) & 1) * 16, S_C + (mat & 1 ? row : row0) * 16, lane & 1 ? 16u : 9u, lane & 30u,
            lane == 4 ? 0xffff0000u : 0u};
#pragma unroll
        for (int i = 0; i < 20; i++) wr[i >> 2][i & 3] = i < 13 ? opaque(c[i % 13], lane) : 0;
    }
    };
    if (!WRP) ldwr();
    TS(21);
    mbar_wait(sm + O_WBC, 0);
    TS(22);
    if (act) {
        uint32_t s[8], y[12];
#pragma unroll
        for (int k = 0; k < 3; k++) *(uint4*)&y[4 * k] = lds128(sm + O_RH + t * 48 + k * 16);
#pragma unroll
        for (int k = 0; k < 2; k++) *(uint4*)&s[4 * k] = lds128(sm + O_SRC + t * 32 + k * 16);
#pragma unroll
        for (int i = 0; i < 8; i++) {
            const int k = 3 * i / 2;
            sts64(sm + O_OUT + ba[i] * 2, __byte_perm(y[k], s[i] + (tag >> 16) + 1, i & 1 ? 0x5432 : 0x5410),
                  i & 1 ? y[k + 1] : __byte_perm(y[k], y[k + 1], 0x5432));
        }
    }
    TS(12);
    __syncthreads();
    if (t == 352) { fence_async(); bulk_st(&gs->vals[b * CH], sm + O_OUT, ne * 8); pfx(PFA, PFB); }
    if (WRP) ldwr();

    const uint32_t am = lane < 31 ? 511 : 0, none = tag | (320 + 4 * lane);
    auto check = [&]() {
        old = 0;
#pragma unroll
        for (int j = 0; j < SEGW; j++) {
            ho[j] = __shfl_sync(0xffffffffu, kv[j], 31);
            kv[j] = ho[j] >= (lane < 31 ? tag + ((lane + 1) << 12) : 0u) ? kv[j] : none;
            old |= kv[j] ^ tag;
        }
        return __any_sync(0xffffffffu, old >> 30);
    };
#pragma unroll
    for (int j = 0; j < SEGW; j++) kv[j] = ld_rlx(kp + j * (G * 32));
    TS(1);
    if (t == 352) WLD(1);
    TV(19, 0); TV(23, 0);
    for (int it = 0; check(); it++) {
        spin_check(it);
        if (it == 0) TS(20);
        TV(19, (it + 1) * 100);
#pragma unroll
        for (int j = 0; j < SEGW; j++)
            if (__any_sync(0xffffffffu, (kv[j] ^ tag) >> 30)) kv[j] = ld_rlx(kp + j * (G * 32));
    }
    TS(3);
    if (t == 352) WLD(2);
    kv[SEGW] = none; ho[SEGW] = 0;
    bool slow = false;
    const bool more = __any_sync(0xffffffffu, lane == 31 && (old & 0xfe0000));
    if (more) {
        int c = lane;
#pragma unroll
        for (int j = 0; j < SEGW; j++) {
            const int n = max((int)(ho[j] >> 12 & 0xfff) - 31, 0);
            if ((unsigned)c < (unsigned)n) ho[SEGW] = j * CH + (ho[j] & 0xfff) + 31 + c - lane;
            c -= n;
        }
        slow = lane == 31 && c < 0;
        if (c < 0 && lane < 31)
            for (int it = 0; ((kv[SEGW] = ld_rlx(&gs->more[w * SEGW * CH + lane + ho[SEGW]])) ^ tag) >> 30; it++) spin_check(it);
        __syncwarp();
    }
#define EV 0
    uint32_t na_[SEGW + 1];
    uint64_t vp = (uint64_t)&gs->vals[w * SEGW * CH + lane], vv[SEGW + 1];
#pragma unroll
    for (int j = 0; j <= SEGW; j++) vv[j] = tag;
    auto ldv = [&](bool again) {
#pragma unroll
        for (int j = 0; j <= SEGW; j++)
            asm volatile("{.reg .pred p; setp.lt.u32 p, %2, 320; @p ld.relaxed.gpu.global.b64 %0, [%1];}" : "+l"(vv[j])
                         : "l"(madw(j < SEGW ? ho[j] & 0xfff : ho[j], 8, vp) + (j < SEGW ? j * CH * 8 : 0)),
                           "r"(again ? (((uint32_t)vv[j] ^ tag) >> 30 ? 0 : 320) : na_[j]) : "memory");
    };
#pragma unroll
    for (int j = 0; j <= SEGW; j++) na_[j] = (kv[j] & am) | (none & 511 & ~am);
    if (EV == 4) ldv(false);
#pragma unroll
    for (int j = 0; j <= SEGW; j++) nk[j] = atoms_add(sm + O_NCNT + na_[j], 512);
    if (EV == 3) ldv(false);
    auto visit = [&](auto f) {
#pragma unroll 1
        for (int j = 0; j < SEGW; j++) {
            const uint32_t* kl = &gs->keys[((w * SEGW + j) * G + b) * 32];
            const uint32_t h = ld_rlx(kl + ((31 + b) & 31));
#pragma unroll 1
            for (int i = lane; i < (h >> 12 & 0xfff); i += 32) {
                const int o = (w * SEGW + j) * CH + (h & 0xfff) + i;
                uint32_t k;
                int it = 0;
                do { k = ld_rlx(i < 31 ? kl + ((i + b) & 31) : &gs->more[o]); spin_check(it++); } while ((k ^ tag) >> 30);
                f(k, o, i);
            }
        }
    };
    slow = __syncthreads_or(slow);
    if (slow) {
        if (t < 80) sts32(sm + O_NCNT + 4 * t, t <= NLOC ? 4 * t : 0);
        __syncthreads();
        visit([&](uint32_t k, int, int) { atoms_add(sm + O_NCNT + (k & 511), 512); });
        __syncthreads();
    }
    TS(4);
    if (t == 352) { WLD(3); pfx(PFA + PFB, PFC); }
    if (EV == 2) ldv(false);
    if (w < 10) {
        const uint32_t key = lds32(sm + O_NCNT + 4 + (t & ~3));
        uint4 k[5];
#pragma unroll
        for (int i = 0; i < 5; i++) k[i] = lds128(sm + O_NCNT + q * 80 + i * 16);
        uint32_t c[4] = {0, 0, 0, 0};
#pragma unroll
        for (int i = 0; i < 5; i++) { c[0] += (key - k[i].x) >> 31; c[1] += (key - k[i].y) >> 31; c[2] += (key - k[i].z) >> 31; c[3] += (key - k[i].w) >> 31; }
        int rank = c[0] + c[1] + c[2] + c[3];
        rank += __shfl_xor_sync(0xffffffffu, rank, 1);
        rank += __shfl_xor_sync(0xffffffffu, rank, 2);
        if (ASC && rank < 2 * NPRIV) rank = (2 * NPRIV - 1 - rank) ^ 1;
        if (t < NLOC * 4) sts32(sm + O_SORT + 4 * rank, key);
    }
    if (EV == 5) ldv(false);
    __syncthreads();
    TS(2);
    const bool on = lane < NLOC / 4;
    const uint4 k4 = lds128(sm + O_SORT + 16 * (on ? lane : 0));
    if (EV == 1) ldv(false);
    const uint32_t ks[4] = {k4.x, k4.y, k4.z, k4.w};
    const int n0 = on ? max(1u, (ks[0] + 3584) >> 12) : 0, n1 = on ? max(1u, (ks[2] + 3584) >> 12) : 0;
    const int u2 = warp_incl(n0 + n1), u1 = u2 - n1, u0 = u1 - n0;
    const int total = __shfl_sync(0xffffffffu, u2, 31);
    slow |= total > CAPT;
    int gbase = b * CAPT + 1;
    if (on) {
#pragma unroll
        for (int i = 0; i < 4; i++) {
            const int a = ks[i] & 511, node = a * (G / 4) - G + b, o = (i >> 1 ? u1 : u0) * 256 + (i & 1) * 16;
            const uint32_t mk = (node < NN ? node + 1 : 0) + ((i >> 1 ? n1 : n0) << 16);
            sts64(sm + O_NOFF + 2 * a, o - (a >> 4), mk + a * 16);
            if (!slow && ks[i] < 512) sts32(sm + O_L + 4 + o, mk);
        }
    }
    __syncwarp();
    if (!slow) {
        uint32_t mk[SEGW + 1];
        TS(13);
        if (t == 352) { pfx(PFA + PFB + PFC, PFD); asm volatile("cp.async.bulk.wait_group.read 0;" ::: "memory"); }
        if (EV == 0) ldv(false);
        if (t == 352) WLD(4);
        TS(16);
#pragma unroll
        for (int j = 0; j <= SEGW; j++) {
            const uint2 o = lds64(sm + O_NOFF + 2 * na_[j]);
            mk[j] = o.y - nk[j] * 16; nk[j] = o.x + (nk[j] >> 4);
        }
        for (int it = 0;; it++) {
            old = 0;
#pragma unroll
            for (int j = 0; j <= SEGW; j++) old |= (uint32_t)vv[j] ^ tag;
            if (!__any_sync(0xffffffffu, old >> 30)) break;
            spin_check(it);
            vp = __shfl_sync(0xffffffffu, vp, lane);
            ldv(true);
            TV(23, (it + 1) * 100);
        }
        TS(17);
#pragma unroll
        for (int j = 0; j <= SEGW; j++)
            asm volatile("{.reg .pred p; setp.ne.u32 p, %3, %5; @p st.shared.v4.u32 [%0], {%1,%2,%3,%4};}"
                         ::"r"(sm + O_L + nk[j]), "r"(kv[j]), "r"(mk[j]), "r"((uint32_t)vv[j]), "r"((uint32_t)(vv[j] >> 32)), "r"(tag) : "memory");
        TS(18);
        if (na_[SEGW] < 320) gs->more[w * SEGW * CH + lane + ho[SEGW]] = 0;
    } else {
        int so = 0;
        if (t == 352) WLD(4);
#pragma unroll
        for (int j = 0; j < SEGW; j++) so += ho[j] & 0xfff;
        if (lane == 0) atoms_add(sm + O_SUM, so);
        if (t == 352) asm volatile("cp.async.bulk.wait_group.read 0;" ::: "memory");
        __syncthreads();
        gbase = TBIG + (lds32(sm + O_SUM) >> 3) + (NLOC + 5) * b;
        auto put = [&](uint32_t k, uint64_t e, uint32_t a, int rank) {
            const uint2 o = lds64(sm + O_NOFF + 2 * a);
            gs->list[gbase * 16 + ((o.x + (a >> 4)) >> 4) + rank * 2] = make_uint4(k, o.y - a * 16 - (rank << 13), e, e >> 32);
        };
        visit([&](uint32_t k, int o, int i) {
            uint64_t e;
            int it = 0;
            do {
                asm volatile("ld.relaxed.gpu.global.b64 %0, [%1];" : "=l"(e) : "l"(&gs->vals[o]) : "memory");
                spin_check(it++);
            } while (((uint32_t)e ^ tag) >> 30);
            if (i >= 31) gs->more[o] = 0;
            put(k, e, k & 511, atoms_add(sm + O_NCUR + (k & 511), 1));
        });
#pragma unroll 1
        for (int i = 0; i < 4; i++) {
            const uint32_t k = i == 0 ? ks[0] : i == 1 ? ks[1] : i == 2 ? ks[2] : ks[3];
#pragma unroll 1
            for (int p = (k >> 9) + w; p < (i >> 1 ? n1 : n0) * 8; p += NT / 32) put(0, 0, k & 511, p);
        }
        __threadfence();
    }
    const uint32_t iw0 = (gbase + u0) << 12 | n0, iw1 = (gbase + u1) << 12 | n1;
    __syncthreads();
    TS(5);

    if (w >= 8) {
        asm volatile("setmaxnreg.dec.sync.aligned.u32 " STR(PREG) ";");
        const int h = __reduce_max_sync(0xffffffffu, w & 3);
        gbase = __reduce_min_sync(0xffffffffu, iw0) >> 12;
        int pos = gbase + h, end = __reduce_max_sync(0xffffffffu, lane == NPRIV / 2 ? (NPRIV & 1 ? iw1 : iw0) : 0) >> 12;
        const int bytes = gbase < TBIG ? ((__reduce_max_sync(0xffffffffu, iw0) >> 12) - gbase) * 256 : 0;
        const uint32_t ring = sm + O_RING;
        const uint64_t xl = wr[0][0] | (uint64_t)wr[0][1] << 32, al = wr[0][2] | (uint64_t)wr[0][3] << 32, ml = wr[1][0] | (uint64_t)wr[1][1] << 32;
        const uint32_t xoff[2] = {wr[1][2], wr[1][3]}, aoff = wr[2][0], coff = wr[2][1], sh = wr[2][2], ial = wr[2][3], sel = wr[3][0];
        auto lde = [&](uint2& e, int p) {
            asm volatile("{.reg .pred p; setp.gt.s32 p, %3, 0; @p ld.relaxed.gpu.global.v2.u32 {%0,%1}, [%2];}" : "+r"(e.x), "+r"(e.y) : "l"(madw(p, 256, ml)), "r"(p) : "memory");
        };
        uint2 e0[3] = {};
#pragma unroll
        for (int k = 0; k < 3; k++) {
            e0[k] = lds64(sm + O_L - 2048 + k * 1024 + t * 8);
            lde(e0[k], bytes ? 0 : pos + 4 * k);
        }
        if (h == 3) fence_async();
        pos += 4;

        int ev = 0, state = -2, tk = 0, nr = 0;
        uint32_t inf = 0;
        int ii = 0;
        auto take = [&]() {
            int v = 0;
            asm volatile("{.reg .pred p; setp.eq.s32 p, %2, 0; @p atom.relaxed.gpu.global.add.u32 %0, [%1], 1;}" : "+r"(v) : "l"(&gs->ticket), "r"(lane) : "memory");
            return v;
        };
        auto resolve = [&]() {
            const int k = __reduce_max_sync(0xffffffffu, tk);
            inf = tag;
            if (k < G * NPOOL) { const int l = k / G; ii = (k - l * G) * NPOOL + l; inf = ld_rlx(&gs->info[ii]);
                tk = (STAG) && ((NPRIV + 1 + nr + (STAG)) & 7) == 0 && k >= G * NPOOL - THETA ? G * NPOOL : take(); }
        };
        uint32_t so = ring + h * SLOT, ph = 0x80000000u;
        uint32_t spins = 0;
        asm volatile(".reg .pred z<5>;");
        while (true) {
            const uint2 e = e0[0];
            const uint32_t o = e.x >> sh, id = __shfl_sync(0xffffffffu, o, ial);
            uint32_t s[4];
#pragma unroll
            for (int j = 0; j < 4; j++) s[j] = __shfl_sync(0xffffffffu, o, 2 * j + 1, 8);
            const uint32_t nx = so == ring + (NSLOT - 1) * SLOT ? ph : ph ^ 0x80000000u, ey = lop_sel(e.y, nx, sel);
            const uint64_t ga = madw(id, 32, al);
            uint64_t gx[4];
#pragma unroll
            for (int j = 0; j < 4; j++) gx[j] = madw(s[j], 1024, xl);
            const uint32_t da = so + aoff, dx[2] = {so + xoff[0], so + xoff[1]}, dc = so + coff;
            asm volatile("setp.eq.u32 z0, %0, 0;\nsetp.eq.u32 z1, %1, 0;\nsetp.eq.u32 z2, %2, 0;\nsetp.eq.u32 z3, %3, 0;\nsetp.eq.u32 z4, %4, 0;\n"
                         PFI
                         ::"r"(NULLP(s[0])), "r"(NULLP(s[1])), "r"(NULLP(s[2])), "r"(NULLP(s[3])), "r"(id), "l"(ga), "r"(da), "r"(dx[0]), "r"(dx[1]), "r"(dc));
            lde(e0[0], state < 0 ? 0 : pos);
            asm volatile("{\n.reg .pred p;\n.reg .b64 s;\nmov.b64 s, {0, %2};\n"
                         "LOOP:\nmbarrier.try_wait.shared::cta.b64 p, [%1], s;\n@p bra DONE;\n"
                         "add.u32 %0, %0, 1;\nsetp.gt.u32 p, %0, %3;\n@p trap;\nbra LOOP;\nDONE:\n}"
                         : "+r"(spins) : "r"(so + S_EMPTY), "r"(ph), "n"(SPIN_LIMIT) : "memory");
            asm volatile("cp.async.cg.shared.global [%0], [%1], 16, z4;" ::"r"(da), "l"(ga) : "memory");
#define ROW(j) _Pragma("unroll") for (int k = 0; k < 8; k++) \
                asm volatile("cp.async.cg.shared.global [%0], [%1], 16, z" #j ";" ::"r"(dx[j >> 1] + (j & 1) * 8192 + k * 128), "l"(gx[j] + k * 128) : "memory")
            X4(ROW);
            stsm2t(dc, e.x, ey);
            asm volatile("cp.async.mbarrier.arrive.noinc.shared::cta.b64 [%0];" ::"r"(so + S_FULL) : "memory");
            const bool wrap = NSLOT == 5 ? so != ring : so >= ring + (NSLOT - 4) * SLOT;
            ph ^= wrap ? 0x80000000u : 0u;
            so = wrap ? so - (NSLOT - 4) * SLOT : so + 4 * SLOT;
            pos += 4;
            if (pos >= ev) {
                if (state < 0) {
                    e0[0] = e0[1]; e0[1] = e0[2];
                    if (state == -2) {
                        if (h == 0) TSW(24);
                        if (h == 3) TSW(25);
                        if (h & 1) bar_sync(7, NT);
                        else asm volatile("bar.arrive 7, %0;" ::"n"(NT) : "memory");
                        if (h == 3) {
                            if (lane == 0) {
                                if (bytes) bulk_st(gs->list + gbase * 16, sm + O_L, bytes);
                                asm volatile("cp.async.bulk.wait_group.read 0;" ::: "memory");
                            }
                            __syncwarp();
                            if (lane == 0) {
                                for (int j = 0; j < 5; j++) tma3d(sm + O_W1 + j * 16384, &m_w1, 64 + 64 * j, 0, sm + O_WBB);
                            }
                            __syncwarp();
                        }
                        state = -1;
                    } else {
                        if (h == 3) {
                            if (lane == 0) asm volatile("cp.async.bulk.wait_group 0;\nfence.proxy.async;" ::: "memory");
                            __syncwarp();
                            const int i = opaque(2 * lane - NPRIV, lane);
                            if ((unsigned)i < NPOOL) st_rlx(&gs->info[b * NPOOL + i], tag | iw0);
                            if ((unsigned)(i + 1) < NPOOL) st_rlx(&gs->info[b * NPOOL + i + 1], tag | iw1);
                        }
                        bar_sync(6, 128);
                        ev = h ? end : end - 12; state = h ? 2 : 0;
                    }
                } else if (state == 0) { ev = end - 6; state = 1; tk = take(); }
                else if (state == 1) { resolve(); ev = end; state = 2; }
                else {
                    if (state == 3) break;
                    do {
                        const uint32_t mb = sm + O_MB + (nr & 15) * 8;
                        uint32_t rg;
                        nr++;
                        if (h == 0) {
                            for (int it = 0; (rg = __reduce_max_sync(0xffffffffu, inf ^ tag)) >> 30; it++) { spin_check(it); inf = ld_rlx(&gs->info[ii]); }
                            asm volatile("st.release.cta.shared.b64 [%0], %1;" ::"r"(mb), "l"(rg | (uint64_t)nr << 32) : "memory");
                            if (rg) resolve();
                        } else {
                            uint64_t m;
                            for (int it = 0;; it++) {
                                asm volatile("ld.acquire.cta.shared.b64 %0, [%1];" : "=l"(m) : "r"(mb) : "memory");
                                if (__all_sync(0xffffffffu, (int)(m >> 32) == nr)) break;
                                spin_check(it);
                            }
                            rg = __reduce_max_sync(0xffffffffu, (uint32_t)m);
                        }
                        pos = rg ? (int)(rg >> 12) + pos - end : 0;
                        end = rg ? (rg >> 12) + (rg & 0xfff) : 1;
                        state = rg ? 2 : 3;
                    } while (pos >= end);
                    ev = end;
                }
            }
        }
        mbar_wait31(so + S_EMPTY, ph);
        TSW(8 + (h & 1));
        if (lane == 0) sts32(so + S_N, 0);
        mbar_arrive(so + S_FULL);
        if (t == 256) {
            gs->epoch[b * 32] = (tag >> 30) % 3;
            if (atomicInc(&gs->done, G - 1) == G - 1) gs->ticket = 0;
        }
        asm volatile("cp.async.wait_all;" ::: "memory");
    } else {
        asm volatile("setmaxnreg.inc.sync.aligned.u32 " STR(CREG) ";");
        const uint32_t xa = opaque(((mat >> 1) * 8 + r) * 1024 + (w >> 2) * 128 + (((2 * (w & 3) + (mat & 1)) ^ r) * 16), lane);
        const uint32_t aa = opaque(S_A + ((mat >> 1) * 8 + r) * 32 + (((mat & 1) ^ (r >> 2)) * 16), lane);
        const uint32_t ya = opaque(S_C + (mat & 1) * 80 + (mat >> 1) * 16, lane);
        const uint32_t yc = opaque(S_C + (mat < 2 ? mat * 80 + 32 : (r >> 2) == (mat & 1) && q < 3 ? (mat & 1) * 80 + q * 16 : 64), lane);
        const uint32_t na = opaque(sm + O_NODE + mat * 4, lane);
        const uint32_t pw = sm + O_P + w * PW;
        const uint32_t fx = opaque(pw + (q < 3 ? P_1P0 + 2 * q * PSBO : P_1P1 + PSBO) + (mat & 1) * 128 + (r >> 2) * PSBO, lane);
        const uint32_t fyz = opaque(pw + (q < 3 ? (mat < 2 ? P_1P1 : P_1P2) + 2 * q * PSBO : mat < 2 ? P_0P0 : P_0P1) + (mat & 1) * 128 + (r >> 2) * PSBO, lane);
        uint32_t oh[4][2];
#pragma unroll
        for (int c = 0; c < 8; c++) oh[c & 3][c >> 2] = opaque(g == c ? 0x3F803F80u : 0u, lane);
        uint32_t eb[3];
#pragma unroll
        for (int k = 0; k < 3; k++) {
            const int i = (g & 3) * 9 + (q & 1) * 6 + k;
            const uint32_t lo = __shfl_sync(0xffffffffu, epl, i), hi = __shfl_sync(0xffffffffu, epl, i + 3);
            eb[k] = (g & 3) < 3 && (q >> 1) == (g >> 2) ? (q & 1 ? lo : lo | hi << 16) : 0u;
        }
        asm volatile(".reg .pred lane0;\nsetp.eq.u32 lane0, %0, 0;" ::"r"(lane));
        uint32_t w0[16][4], w1[4][4];
        mbar_wait(sm + O_WBD, 0);
#pragma unroll
        for (int k = 0; k < 16; k++) ldsm4t(w0[k], sm + O_W0S + (k >> 2) * 16384 + (w >> 2) * 8192 + (k & 3) * 2048 + sw);
#pragma unroll
        for (int k = 0; k < 4; k++) ldsm4t(w1[k], sm + O_W1S + (w >> 2) * 8192 + k * 2048 + sw);
        bar_sync(7, NT);
        TS(6);
        Acc A;
#pragma unroll
        for (int i = 0; i < 4; i++) { A.p00[i] = A.p110[i] = A.p10[0][i] = A.p10[1][i] = A.p10[2][i] = 0; A.t01[i] = A.m[0][i] = A.m[1][i] = A.m[2][i] = 0.f; }
        uint32_t room = 144 - (STAG) * 16;
        uint32_t so = sm + O_RING, ph, a[4], ok, go, mt = 0;
        mbar_wait(so + S_FULL, 0);
        ldsm4(a, so + aa);
        TS(7);
        while (true) {
            {
                constexpr int F = 1, XS = XS_F;
                uint32_t yb[8], f[4][4], R[5][4], u[4][4], sd[4];
                float y[4], z[4];
                const uint32_t sof = room & 112;
                SEQ_F
                room -= 16;
            }
            if (!(go && room)) {
                const uint32_t pu = __reduce_max_sync(0xffffffffu, ph);
                if (!room || !pu) {
                    asm volatile("fence.proxy.async.shared::cta;" ::: "memory");
                    mbar_wait(sm + O_WBB, 0);
                    bar_sync(1, 256);
                    float d0[8], d1[24];
                    const uint32_t wg = __reduce_max_sync(0xffffffffu, w >> 2);
                    const uint64_t db = (uint64_t)((sm + O_P) >> 4) | (8ull << 16) | ((uint64_t)(PSBO / 16) << 32);
                    const uint32_t da = ((sm + O_W1) >> 4 | 1 << 16) + wg * 512;
                    asm volatile("wgmma.fence.sync.aligned;" ::: "memory");
#pragma unroll
                    for (int k = 0; k < 16; k++) wg_rs16(d0, w0[k], db + (((k & 7) * PW + ((k >> 3) ? P_0P1 : P_0P0)) >> 4), k);
                    asm volatile("wgmma.commit_group.sync.aligned;" ::: "memory");
#pragma unroll
                    for (int k = 0; k < 4; k++) wg_rs48(d1, w1[k], db + ((k * PW + P_1P0) >> 4), k);
#pragma unroll
                    for (int k = 4; k < 24; k++)
                        wg_ss48(d1, (da + (k / 4 - 1) * 1024 + (k & 3) * 128) | (64ull << 32) | (1ull << 62), db + (((k & 7) * PW + ((k >> 3) == 0 ? P_1P0 : (k >> 3) == 1 ? P_1P1 : P_1P2)) >> 4), k);
                    asm volatile("wgmma.commit_group.sync.aligned;" ::: "memory");
                    const uint2 n0 = lds64(sm + O_NODE + mat * 16), n1 = lds64(sm + O_NODE + 64 + mat * 16);
                    const bool v0 = (mat * 16 - 16 & 112) >= room, v1 = mat * 16 + 48 >= room;
                    const uint32_t nd[4] = {v0 ? n0.x : 0, v1 ? n1.x : 0, v0 ? n0.y : 0, v1 ? n1.y : 0};
                    const uint64_t op = (uint64_t)(out - 1024 + (w & 3) * 256 + (w >> 2) * 128 + r * 16);
                    uint64_t oa[4];
#pragma unroll
                    for (int it = 0; it < 4; it++) oa[it] = madw(nd[it], 1024, op);
                    uint32_t sg = sm + O_P + (w & 4) * PW + ((mat >> 1) * 8 + r) * 128 + (((2 * (w & 3) + (mat & 1)) ^ r) * 16);
                    uint32_t sl = pw + mat * 128 + (r ^ mat) * 16, sl2 = pw + 512 + mat * 128 + (r ^ mat ^ 4) * 16;
                    asm volatile("wgmma.wait_group.sync.aligned 1;" ::: "memory");
#pragma unroll
                    for (int i = 0; i < 8; i++) asm volatile("" : "+f"(d0[i])::"memory");
                    uint32_t o[4][4], chk = sg & sl & sl2;
                    float gt[8];
#pragma unroll
                    for (int i = 0; i < 8; i++) {
                        asm("ex2.approx.ftz.f32 %0, %1;" : "=f"(gt[i]) : "f"(d0[i] * -1.4426950408889634f));
                        asm("rcp.approx.ftz.f32 %0, %1;" : "=f"(gt[i]) : "f"(gt[i] + 1.f));
                        chk &= __float_as_uint(gt[i]);
                    }
#pragma unroll
                    for (int i = 0; i < 4; i++) { o[0][i] = pack(d0[2 * i], d0[2 * i + 1]); chk &= o[0][i] & (uint32_t)(oa[i] >> 32); }
                    sts32(sm + O_TRASH, chk);
                    asm volatile("wgmma.wait_group.sync.aligned 0;" ::: "memory");
#pragma unroll
                    for (int i = 0; i < 24; i++) asm volatile("" : "+f"(d1[i])::"memory");
                    bar_sync(1, 256);
#pragma unroll
                    for (int i = 0; i < 4; i++)
#pragma unroll
                        for (int j = 0; j < 3; j++) o[1 + j][i] = pack(d1[8 * j + 2 * i] * gt[2 * i], d1[8 * j + 2 * i + 1] * gt[2 * i + 1]);
#pragma unroll
                    for (int j = 0; j < 4; j++) stsm4t(sg + j * PW, o[j][0], o[j][1], o[j][2], o[j][3]);
                    bar_sync(2 + wg, 128);
                    uint4 v[4];
#pragma unroll
                    for (int it = 0; it < 4; it++) v[it] = lds128((it & 1 ? sl2 : sl) + (it >> 1) * 1024);
#pragma unroll
                    for (int it = 0; it < 4; it++)
                        asm volatile("{.reg .pred p; setp.ne.u32 p, %5, 0; @p st.global.v4.u32 [%0], {%1,%2,%3,%4};}"
                                     ::"l"(oa[it]), "r"(v[it].x), "r"(v[it].y), "r"(v[it].z), "r"(v[it].w), "r"(nd[it]) : "memory");
                    __syncwarp();
                    room = 128;
                    if (!pu) break;
                }
                if (!ok) { mbar_wait31(so + S_FULL, pu); ldsm4(a, so + aa); }
                if (!(pu & 0xfffe)) continue;
            }
            while (true) {
                do {
                    constexpr int F = 0, XS = XS_R;
                    uint32_t yb[8], f[4][4], R[5][4], u[4][4], sd[4];
                    SEQ_R
                } while (go);
                if (ok) break;
                const uint32_t pu = __reduce_max_sync(0xffffffffu, ph);
                mbar_wait31(so + S_FULL, pu); ldsm4(a, so + aa);
                if (!(pu & 0xfffe)) break;
            }
        }
        TS(10);
    }
}

typedef CUresult (*EncFn)(CUtensorMap*, CUtensorMapDataType, cuuint32_t, void*, const cuuint64_t*, const cuuint64_t*,
                          const cuuint32_t*, const cuuint32_t*, CUtensorMapInterleave, CUtensorMapSwizzle,
                          CUtensorMapL2promotion, CUtensorMapFloatOOBfill);

void make_map(EncFn fn, CUtensorMap* m, void* p, int rows, int cols, int brows, int rank, int bblk, CUtensorMapSwizzle swz) {
    cuuint64_t dims[3] = {(cuuint64_t)(rank == 3 ? 64 : cols), (cuuint64_t)rows, (cuuint64_t)cols / 64}, strides[2] = {(cuuint64_t)cols * 2, 128};
    cuuint32_t box[3] = {64, (cuuint32_t)brows, (cuuint32_t)bblk}, es[3] = {1, 1, 1};
    fn(m, CU_TENSOR_MAP_DATA_TYPE_BFLOAT16, rank, p, dims, strides, box, es, CU_TENSOR_MAP_INTERLEAVE_NONE,
       swz, CU_TENSOR_MAP_L2_PROMOTION_NONE, CU_TENSOR_MAP_FLOAT_OOB_FILL_NONE);
}

}

extern "C" void kernel_launch(void* const* d_in, const int* in_sizes, int n_in, void* d_out, int out_size) {
    static EncFn enc = nullptr;
    static void* scratch = nullptr;
    if (!enc) {
        void* fn = nullptr;
        cudaDriverEntryPointQueryResult qr;
        cudaGetDriverEntryPoint("cuTensorMapEncodeTiled", &fn, cudaEnableDefault, &qr);
        enc = (EncFn)fn;
        cudaGetSymbolAddress(&scratch, g_scratch);
        cudaFuncSetAttribute(tp_kernel, cudaFuncAttributeMaxDynamicSharedMemorySize, SMEM_BYTES);
    }
    CUtensorMap m_wr, m_w0, m_w1;
    make_map(enc, &m_wr, d_in[5], 16, 640, 16, 3, 5, CU_TENSOR_MAP_SWIZZLE_128B);
    make_map(enc, &m_w0, d_in[6], 256, 128, 64, 3, 2, CU_TENSOR_MAP_SWIZZLE_128B);
    make_map(enc, &m_w1, d_in[7], 384, 128, 64, 3, 2, CU_TENSOR_MAP_SWIZZLE_128B);
    tp_kernel<<<G, NT, SMEM_BYTES>>>((const int4*)d_in[4], (const int4*)d_in[3], (const char*)d_in[1], (Scratch*)scratch,
                                     (const char*)d_in[0], (const char*)d_in[2], (const __nv_bfloat16*)d_in[8], (char*)d_out,
                                     m_wr, m_w0, m_w1);
}
```

```cpp
#include <cuda_runtime.h>
#include <cuda_bf16.h>
#include <cuda.h>
#include <stdint.h>
#include <stddef.h>

namespace {

constexpr int NN = 10000;
constexpr int NE = 320000;
constexpr int G = 132;
constexpr int NT = 384;
constexpr int CH = 2432;
constexpr int NLOC = (NN + G - 1) / G;
#define NPOOL 4
constexpr int NPAIR = NLOC / 2, NPRIV = NPAIR - NPOOL;
constexpr int SEGW = 11;

#define NSLOT 6
#define PP 0xffff
#define TP 0x9375
#define STAG (b & 7)
#define ASC (b & 1)
#define THETA G
#define WP 0x22255
#define WLD(p) { _Pragma("unroll") for (int j = 0; j < 5; j++) if ((WP >> 4 * j & 15) == p) \
    tma3d(sm + (j < 4 ? O_W0S + j * 16384 : O_W1S), j < 4 ? &m_w0 : &m_w1, (j & 3) * 64, 0, sm + O_WBD); \
    _Pragma("unroll") for (int j = 0; j < 4; j++) { const int r0 = (b * 4 + j) * (NLOC / 4); \
        if ((PP >> 4 * j & 15) == p) pf_l2(x + r0 * 1024, min(NLOC / 4, NN - r0) * 1024); \
        if ((TP >> 4 * j & 15) == p) tma3d(sm + O_WR1 + 10240, &m_x, r0 * 8, 0, sm + O_WBE); } }
#define INV 0
#define NULLP(v) v
#define CREG 224
#define PREG 56
#define STR2(x) #x
#define STR(x) STR2(x)

constexpr int S_A = 16384, S_C = S_A + 512, S_FULL = S_C + 144, S_EMPTY = S_FULL + 8, S_N = S_C + 160, SLOT = S_C + 256;

constexpr int PSBO = 272;
constexpr int PB1 = 5 * PSBO + 256, PB0 = PSBO + 256;
constexpr int P_1P0 = 0, P_1P1 = PB1, P_0P1 = 2 * PB1, P_0P0 = P_0P1 + PB0, P_1P2 = P_0P0 + PB0;
constexpr int PW = P_1P2 + PB1;

constexpr int up1k(int a) { return (a + 1023) / 1024 * 1024; }
constexpr int O_W1 = 0;
constexpr int O_P = 81920;
constexpr int O_RING = O_P + 8 * PW;
constexpr int O_WBA = O_RING + 6 * SLOT, O_WBB = O_WBA + 8, O_WBC = O_WBA + 16, O_WBD = O_WBA + 24, O_WBE = O_WBA + 32, O_TRASH = O_WBA + 40, O_NODE = O_WBA + 48;
constexpr int O_SUM = O_NODE + 128, O_MB = O_SUM + 16;
constexpr int SMEM_BYTES = O_MB + 128;
constexpr int CAPT = 192;
constexpr int O_L = 0, LZ = CAPT * 256 / (NT * 16), O_W0S = O_L + CAPT * 256, O_OUT = O_W0S + 65536, O_SRC = O_OUT + CH * 8;
constexpr int O_KT = O_RING + SLOT, O_RH = O_RING + 2 * SLOT;
constexpr int O_WR0 = up1k(O_RING + 3 * SLOT), O_WR1 = up1k(O_RING + 4 * SLOT), O_W1S = up1k(O_RING + 5 * SLOT);
constexpr int O_BCNT = O_WR0 + 10240, O_NCUR = O_BCNT + 640, O_NCNT = O_NCUR + 320;
constexpr int O_BOFF = O_NCNT + 512, O_SORT = O_BOFF + 640, O_NOFF = O_SORT + 320;
constexpr int TBIG = G * CAPT + 8, NTILE = TBIG + NE / 8 + G * (NLOC + 5);
static_assert(SMEM_BYTES <= 232448 && CAPT % 16 == 0 && NTILE < (1 << 18), "smem");
static_assert(LZ * NT * 16 == CAPT * 256 && O_W0S % 1024 == 0 && O_OUT <= O_RING && O_SRC + CH * 4 <= O_RING + S_C && G * 128 <= S_C, "staging");
static_assert(O_NOFF + 1024 <= O_RING + 3 * SLOT + S_C && O_W1S + 16384 <= O_RING + 5 * SLOT + S_C, "staging");
static_assert(O_RING % 128 == 0 && SLOT % 128 == 0 && O_W0S <= O_P && O_NOFF % 8 == 0, "layout");
static_assert(G * CH >= NE && NE % 8 == 0 && CH < 4096 && CH / 8 <= 320 && NE < (1 << 21), "chunks");
static_assert(SEGW * (NT / 32) == G && G <= 160 && G % 4 == 0, "segments");
static_assert(NLOC % 4 == 0 && NLOC < 80 && NLOC * 4 <= 320 && NN < 0x3fff && NE / 8 < 0xbfff && NPRIV >= 30, "scan width");

struct __align__(128) Scratch {
    uint32_t keys[G * G * 32];
    uint64_t vals[G * CH];
    uint32_t more[G * CH];
    uint32_t epoch[G * 32];
    uint32_t info[G * NPOOL];
    unsigned done, pad0[31], ticket, pad1[31 + 32 - G * NPOOL % 32];
    uint4 list[NTILE * 16];
};
static_assert(offsetof(Scratch, list) % 128 == 0, "list");
__device__ Scratch g_scratch;
#define TS(i)
#define TSW(i)
#define TV(i, v)

constexpr int SPIN_LIMIT = 1 << 24;

__device__ __forceinline__ void mbar_init(uint32_t a, int c) { asm volatile("mbarrier.init.shared::cta.b64 [%0], %1;" ::"r"(a), "r"(c) : "memory"); }
__device__ __forceinline__ void mbar_expect(uint32_t a, int b) { asm volatile("mbarrier.arrive.expect_tx.shared::cta.b64 _, [%0], %1;" ::"r"(a), "r"(b) : "memory"); }
__device__ __forceinline__ void mbar_arrive(uint32_t a) { asm volatile("mbarrier.arrive.shared::cta.b64 _, [%0];" ::"r"(a) : "memory"); }
__device__ __forceinline__ void mbar_wait(uint32_t a, uint32_t ph) {
    asm volatile("{\n.reg .pred p, q;\n.reg .u32 it;\n"
                 "mbarrier.try_wait.parity.shared::cta.b64 p, [%0], %1;\n"
                 "@p bra DONE;\n"
                 "mov.u32 it, 0;\n"
                 "LOOP:\n"
                 "mbarrier.try_wait.parity.shared::cta.b64 p, [%0], %1;\n"
                 "@p bra DONE;\n"
                 "add.u32 it, it, 1;\n"
                 "setp.gt.u32 q, it, %2;\n"
                 "@q trap;\n"
                 "bra LOOP;\n"
                 "DONE:\n}" ::"r"(a), "r"(ph), "n"(SPIN_LIMIT) : "memory");
}
__device__ __forceinline__ void mbar_wait31(uint32_t a, uint32_t ph) {
    asm volatile("{\n.reg .pred p, q;\n.reg .u32 it;\n.reg .b64 s;\n"
                 "mov.b64 s, {0, %1};\n"
                 "mbarrier.try_wait.shared::cta.b64 p, [%0], s;\n"
                 "@p bra DONE;\n"
                 "mov.u32 it, 0;\n"
                 "LOOP:\n"
                 "mbarrier.try_wait.shared::cta.b64 p, [%0], s;\n"
                 "@p bra DONE;\n"
                 "add.u32 it, it, 1;\n"
                 "setp.gt.u32 q, it, %2;\n"
                 "@q trap;\n"
                 "bra LOOP;\n"
                 "DONE:\n}" ::"r"(a), "r"(ph), "n"(SPIN_LIMIT) : "memory");
}
__device__ __forceinline__ void spin_check(int it) {
    asm volatile("{\n.reg .pred q;\nsetp.gt.s32 q, %0, %1;\n@q trap;\n}" ::"r"(it), "n"(SPIN_LIMIT));
}
__device__ __forceinline__ void ldsm4(uint32_t* r, uint32_t a) { asm volatile("ldmatrix.sync.aligned.m8n8.x4.shared.b16 {%0,%1,%2,%3}, [%4];" : "=r"(r[0]), "=r"(r[1]), "=r"(r[2]), "=r"(r[3]) : "r"(a) : "memory"); }
__device__ __forceinline__ void ldsm4t(uint32_t* r, uint32_t a) { asm volatile("ldmatrix.sync.aligned.m8n8.x4.trans.shared.b16 {%0,%1,%2,%3}, [%4];" : "=r"(r[0]), "=r"(r[1]), "=r"(r[2]), "=r"(r[3]) : "r"(a) : "memory"); }
__device__ __forceinline__ void stsm4t(uint32_t a, uint32_t r0, uint32_t r1, uint32_t r2, uint32_t r3) { asm volatile("stmatrix.sync.aligned.m8n8.x4.trans.shared.b16 [%0], {%1,%2,%3,%4};" ::"r"(a), "r"(r0), "r"(r1), "r"(r2), "r"(r3) : "memory"); }
__device__ __forceinline__ void stsm2t(uint32_t a, uint32_t r0, uint32_t r1) { asm volatile("stmatrix.sync.aligned.m8n8.x2.trans.shared.b16 [%0], {%1,%2};" ::"r"(a), "r"(r0), "r"(r1) : "memory"); }
__device__ __forceinline__ void mma16(float* d, const uint32_t* a, uint32_t b0, uint32_t b1) {
    asm("mma.sync.aligned.m16n8k16.row.col.f32.bf16.bf16.f32 {%0,%1,%2,%3}, {%4,%5,%6,%7}, {%8,%9}, {%0,%1,%2,%3};"
        : "+f"(d[0]), "+f"(d[1]), "+f"(d[2]), "+f"(d[3]) : "r"(a[0]), "r"(a[1]), "r"(a[2]), "r"(a[3]), "r"(b0), "r"(b1));
}
__device__ __forceinline__ void mma8(float* d, uint32_t a0, uint32_t a1, uint32_t b0) {
    asm("mma.sync.aligned.m16n8k8.row.col.f32.bf16.bf16.f32 {%0,%1,%2,%3}, {%4,%5}, {%6}, {%0,%1,%2,%3};"
        : "+f"(d[0]), "+f"(d[1]), "+f"(d[2]), "+f"(d[3]) : "r"(a0), "r"(a1), "r"(b0));
}
__device__ __forceinline__ void mma16z(float* d, const uint32_t* a, uint32_t b0, uint32_t b1) {
    asm("mma.sync.aligned.m16n8k16.row.col.f32.bf16.bf16.f32 {%0,%1,%2,%3}, {%4,%5,%6,%7}, {%8,%9}, {%10,%10,%10,%10};"
        : "=f"(d[0]), "=f"(d[1]), "=f"(d[2]), "=f"(d[3]) : "r"(a[0]), "r"(a[1]), "r"(a[2]), "r"(a[3]), "r"(b0), "r"(b1), "f"(0.f));
}
__device__ __forceinline__ uint32_t pack(float lo, float hi) { uint32_t r; asm("cvt.rn.bf16x2.f32 %0, %1, %2;" : "=r"(r) : "f"(hi), "f"(lo)); return r; }
__device__ __forceinline__ uint32_t hmul(uint32_t a, uint32_t b) { uint32_t r; asm("mul.rn.bf16x2 %0, %1, %2;" : "=r"(r) : "r"(a), "r"(b)); return r; }
__device__ __forceinline__ uint32_t hfma(uint32_t a, uint32_t b, uint32_t c) { uint32_t r; asm("fma.rn.bf16x2 %0, %1, %2, %3;" : "=r"(r) : "r"(a), "r"(b), "r"(c)); return r; }
__device__ __forceinline__ uint4 lds128(uint32_t a) { uint4 v; asm volatile("ld.shared.v4.u32 {%0,%1,%2,%3}, [%4];" : "=r"(v.x), "=r"(v.y), "=r"(v.z), "=r"(v.w) : "r"(a) : "memory"); return v; }
__device__ __forceinline__ void sts128(uint32_t a, uint4 v) { asm volatile("st.shared.v4.u32 [%0], {%1,%2,%3,%4};" ::"r"(a), "r"(v.x), "r"(v.y), "r"(v.z), "r"(v.w) : "memory"); }
__device__ __forceinline__ int lds32(uint32_t a) { int v; asm volatile("ld.shared.u32 %0, [%1];" : "=r"(v) : "r"(a) : "memory"); return v; }
__device__ __forceinline__ void sts32(uint32_t a, int v) { asm volatile("st.shared.u32 [%0], %1;" ::"r"(a), "r"(v) : "memory"); }
__device__ __forceinline__ int atoms_add(uint32_t a, int v) { int r; asm volatile("atom.shared.add.u32 %0, [%1], %2;" : "=r"(r) : "r"(a), "r"(v) : "memory"); return r; }
__device__ __forceinline__ uint32_t ld_rlx(const void* p) { uint32_t v; asm volatile("ld.relaxed.gpu.global.u32 %0, [%1];" : "=r"(v) : "l"(p) : "memory"); return v; }
__device__ __forceinline__ void st_rlx(void* p, uint32_t v) { asm volatile("st.relaxed.gpu.global.u32 [%0], %1;" ::"l"(p), "r"(v) : "memory"); }
__device__ __forceinline__ void bulk(uint32_t dst, const void* g, int n, uint32_t bar) {
    asm volatile("cp.async.bulk.shared::cluster.global.mbarrier::complete_tx::bytes [%0], [%1], %2, [%3];" ::"r"(dst), "l"(g), "r"(n), "r"(bar) : "memory");
}
__device__ __forceinline__ void bulk_st(void* g, uint32_t src, int n) {
    asm volatile("cp.async.bulk.global.shared::cta.bulk_group [%0], [%1], %2;\ncp.async.bulk.commit_group;" ::"l"(g), "r"(src), "r"(n) : "memory");
}
__device__ __forceinline__ uint2 lds64(uint32_t a) { uint2 v; asm volatile("ld.shared.v2.u32 {%0,%1}, [%2];" : "=r"(v.x), "=r"(v.y) : "r"(a) : "memory"); return v; }
__device__ __forceinline__ void sts64(uint32_t a, uint32_t x, uint32_t y) { asm volatile("st.shared.v2.u32 [%0], {%1,%2};" ::"r"(a), "r"(x), "r"(y) : "memory"); }
__device__ __forceinline__ void tma3d(uint32_t dst, const CUtensorMap* m, int c1, int c2, uint32_t bar) {
    asm volatile("cp.async.bulk.tensor.3d.shared::cluster.global.mbarrier::complete_tx::bytes [%0], [%1, {0, %3, %4}], [%2];"
                 ::"r"(dst), "l"(m), "r"(bar), "r"(c1), "r"(c2) : "memory");
}
__device__ __forceinline__ void pf_l2(const void* g, int n) {
    asm volatile("{.reg .pred p; setp.gt.s32 p, %1, 0; @p cp.async.bulk.prefetch.L2.global [%0], %1;}" ::"l"(g), "r"(n) : "memory");
}
__device__ __forceinline__ void fence_async() { asm volatile("fence.proxy.async.shared::cta;" ::: "memory"); }
__device__ __forceinline__ uint64_t madw(uint32_t a, uint32_t b, uint64_t c) { uint64_t r; asm("mad.wide.u32 %0, %1, %2, %3;" : "=l"(r) : "r"(a), "r"(b), "l"(c)); return r; }
__device__ __forceinline__ uint32_t lop_sel(uint32_t a, uint32_t b, uint32_t m) { uint32_t r; asm("lop3.b32 %0, %1, %2, %3, 0xd8;" : "=r"(r) : "r"(a), "r"(b), "r"(m)); return r; }
__device__ __forceinline__ uint32_t opaque(uint32_t v, int lane) { return __shfl_sync(0xffffffffu, v, lane); }
__device__ __forceinline__ void bar_sync(int id, int n) { asm volatile("bar.sync %0, %1;" ::"r"(id), "r"(n) : "memory"); }

__device__ __forceinline__ void wg_rs16(float* d, const uint32_t* a, uint64_t db, int sc) {
    asm volatile("{.reg .pred p; setp.ne.b32 p, %13, 0;\n"
                 "wgmma.mma_async.sync.aligned.m64n16k16.f32.bf16.bf16 {%0,%1,%2,%3,%4,%5,%6,%7}, {%8,%9,%10,%11}, %12, p, 1, 1, 0;}"
                 : "+f"(d[0]), "+f"(d[1]), "+f"(d[2]), "+f"(d[3]), "+f"(d[4]), "+f"(d[5]), "+f"(d[6]), "+f"(d[7])
                 : "r"(a[0]), "r"(a[1]), "r"(a[2]), "r"(a[3]), "l"(db), "r"(sc));
}
__device__ __forceinline__ void wg_rs48(float* d, const uint32_t* a, uint64_t db, int sc) {
    asm volatile("{.reg .pred p; setp.ne.b32 p, %29, 0;\n"
                 "wgmma.mma_async.sync.aligned.m64n48k16.f32.bf16.bf16 {%0,%1,%2,%3,%4,%5,%6,%7,%8,%9,%10,%11,%12,%13,%14,%15,%16,%17,%18,%19,%20,%21,%22,%23}, {%24,%25,%26,%27}, %28, p, 1, 1, 0;}"
                 : "+f"(d[0]), "+f"(d[1]), "+f"(d[2]), "+f"(d[3]), "+f"(d[4]), "+f"(d[5]), "+f"(d[6]), "+f"(d[7]),
                   "+f"(d[8]), "+f"(d[9]), "+f"(d[10]), "+f"(d[11]), "+f"(d[12]), "+f"(d[13]), "+f"(d[14]), "+f"(d[15]),
                   "+f"(d[16]), "+f"(d[17]), "+f"(d[18]), "+f"(d[19]), "+f"(d[20]), "+f"(d[21]), "+f"(d[22]), "+f"(d[23])
                 : "r"(a[0]), "r"(a[1]), "r"(a[2]), "r"(a[3]), "l"(db), "r"(sc));
}
__device__ __forceinline__ void wg_ss48(float* d, uint64_t da, uint64_t db, int sc) {
    asm volatile("{.reg .pred p; setp.ne.b32 p, %26, 0;\n"
                 "wgmma.mma_async.sync.aligned.m64n48k16.f32.bf16.bf16 {%0,%1,%2,%3,%4,%5,%6,%7,%8,%9,%10,%11,%12,%13,%14,%15,%16,%17,%18,%19,%20,%21,%22,%23}, %24, %25, p, 1, 1, 1, 0;}"
                 : "+f"(d[0]), "+f"(d[1]), "+f"(d[2]), "+f"(d[3]), "+f"(d[4]), "+f"(d[5]), "+f"(d[6]), "+f"(d[7]),
                   "+f"(d[8]), "+f"(d[9]), "+f"(d[10]), "+f"(d[11]), "+f"(d[12]), "+f"(d[13]), "+f"(d[14]), "+f"(d[15]),
                   "+f"(d[16]), "+f"(d[17]), "+f"(d[18]), "+f"(d[19]), "+f"(d[20]), "+f"(d[21]), "+f"(d[22]), "+f"(d[23])
                 : "l"(da), "l"(db), "r"(sc));
}

__device__ __forceinline__ int warp_incl(int v) {
#pragma unroll
    for (int o = 1; o < 32; o <<= 1)
        asm volatile("{.reg .pred p; .reg .b32 u; shfl.sync.up.b32 u|p, %0, %1, 0, 0xffffffff; @p add.s32 %0, %0, u;}" : "+r"(v) : "r"(o));
    return v;
}
__device__ __forceinline__ void ldg128(uint32_t* r, const void* p, bool on) {
    asm volatile("{.reg .pred p; setp.ne.u32 p, %5, 0; @p ld.global.nc.v4.u32 {%0,%1,%2,%3}, [%4];}"
                 : "=r"(r[0]), "=r"(r[1]), "=r"(r[2]), "=r"(r[3]) : "l"(p), "r"((uint32_t)on));
}

struct Acc {
    uint32_t p00[4], p110[4], p10[3][4];
    float t01[4], m[3][4];
};

#define LF(m) ldsm4t(f[m], so + xa + m * 256)
#define LY() ldsm4(yb, so + ya)
#define LC() ldsm4(yb + 4, so + yc)
#define LN() ph = lds32(so + S_N)
#define ADV() { asm volatile("@lane0 mbarrier.arrive.shared::cta.b64 _, [%0];" ::"r"(so + S_EMPTY) : "memory"); \
                so = so == sm + O_RING + (NSLOT - 1) * SLOT ? sm + O_RING : so + SLOT; }
#define LA() asm volatile("{\n.reg .pred p, q;\n.reg .b64 s;\n.reg .f32 n;\nmov.b64 s, {0, %7};\nmbarrier.test_wait.shared::cta.b64 p, [%6], s;\n" \
                          "abs.f32 n, %7;\nsetp.gt.and.f32 q, n, 0f00000001, p;\nselp.u32 %4, 1, 0, p;\nselp.u32 %5, 1, 0, q;\n" \
                          "@p ldmatrix.sync.aligned.m8n8.x4.shared.b16 {%0,%1,%2,%3}, [%8];\n}" \
                          : "+r"(a[0]), "+r"(a[1]), "+r"(a[2]), "+r"(a[3]), "=r"(ok), "=r"(go) : "r"(so + S_FULL), "r"(ph), "r"(so + aa) : "memory")
#define RAD(p, s) { float c[4]; mma16z(c, wr[p], a[2 * s], a[2 * s + 1]); R[p][2 * s] = pack(c[0], c[1]); R[p][2 * s + 1] = pack(c[2], c[3]); }
#define MUL(n, x, y) (XS >> n & 1 ? hmul(y, x) : hmul(x, y))
#define FMA(n, x, y, z) (XS >> n & 1 ? hfma(y, x, z) : hfma(x, y, z))
#define ACC(n, x, y, z) z = F ? MUL(n, x, y) : FMA(n, x, y, z)
#define P00(i) ACC(0, f[0][i], R[0][i], A.p00[i ^ XA])
#define P10(k, i) ACC(1, f[1 + k][i], R[3][i], A.p10[k][i ^ XA])
#define S0(k, i) sd[i] = MUL(2, f[1 + k][i], yb[2 * k + (i >> 1)])
#define SD(k, i) sd[i] = FMA(2, f[1 + k][i], yb[2 * k + (i >> 1)], sd[i])
#define P110(i) ACC(3, sd[i], R[1][i], A.p110[i ^ XA])
#define TU(i) u[3][i ^ XU] = MUL(4, f[0][i], R[2][i])
#define TM() if (F) mma16z(A.t01, u[3], yb[6], yb[7]); else mma16(A.t01, u[3], yb[6], yb[7])
#define MU(k, i) u[k][i ^ XU] = MUL(5, f[1 + k][i], R[4][i])
#define MM(k) if (F) mma16z(A.m[k], u[k], yb[6], yb[7]); else mma16(A.m[k], u[k], yb[6], yb[7])
#define PK(v, h) pack(v[2 * (h)], v[2 * (h) + 1])
#define LM() { sts32(na + sof, mt); asm volatile("ld.shared.u16 %0, [%1];" : "=r"(mt) : "r"(so + ya + 48) : "memory"); }
#define FY(k) if (k == 0) mma16z(y, A.p10[0], oh[0][0], oh[0][1]); else mma16(y, k < 3 ? A.p10[k % 3] : A.p00, oh[k][0], oh[k][1])
#define FZ(k) if (k == 0) mma16z(z, A.p110, oh[3][0], oh[3][1]); \
              else if (k == 1) { const uint32_t mp[4] = {PK(A.m[0], XA ^ XU), PK(A.m[0], 1 ^ XA ^ XU), PK(A.m[1], XA ^ XU), PK(A.m[1], 1 ^ XA ^ XU)}; mma16(z, mp, eb[0], eb[1]); } \
              else mma8(z, PK(A.m[2], XA ^ XU), PK(A.m[2], 1 ^ XA ^ XU), eb[2])
#define SX() stsm2t(fx + sof, PK(A.t01, XU), PK(A.t01, 1 ^ XU))
#define SY() stsm4t(fyz + sof, PK(y, XA), PK(y, 1 ^ XA), PK(z, XA), PK(z, 1 ^ XA))
#define X4(op) op(0); op(1); op(2); op(3)
#define Y4(op, k) op(k, 0); op(k, 1); op(k, 2); op(k, 3)
#define XA 0
#define XU 1
#define XS_R 63
#define SEQ_R LC(); LF(2); LF(1); LN(); RAD(2,0); LY(); RAD(2,1); LF(3); LF(0); ADV(); RAD(4,0); RAD(1,0); RAD(4,1); RAD(1,1); MU(1,0); MU(1,2); MU(1,1); \
    MU(1,3); MM(1); RAD(0,1); P00(2); P00(3); RAD(0,0); P00(0); P00(1); TU(0); TU(2); TU(1); TU(3); S0(0,0); SD(2,0); SD(1,0); TM(); S0(0,2); \
    SD(2,2); SD(1,2); S0(0,3); SD(2,3); SD(1,3); S0(0,1); SD(2,1); SD(1,1); MU(0,0); MU(0,2); MU(0,3); MU(0,1); MM(0); P110(0); P110(2); \
    P110(1); P110(3); RAD(3,1); P10(0,2); P10(0,3); RAD(3,0); LA(); P10(0,0); P10(0,1); P10(2,2); P10(2,3); P10(2,0); P10(2,1); P10(1,1); \
    P10(1,0); MU(2,1); MU(2,0); MU(2,3); MU(2,2); MM(2); P10(1,3); P10(1,2);
#define XS_F 0
#define SEQ_F LN(); LM(); LF(0); LC(); LF(1); LF(2); LF(3); LY(); ADV(); FY(0); FZ(0); FY(1); FZ(1); FY(2); FZ(2); FY(3); SX(); SY(); \
    RAD(0, 0); RAD(0, 1); RAD(1, 0); RAD(1, 1); RAD(2, 0); RAD(2, 1); RAD(3, 0); RAD(3, 1); RAD(4, 0); RAD(4, 1); LA(); \
    X4(P00); X4(TU); TM(); Y4(P10, 0); Y4(MU, 0); MM(0); Y4(P10, 1); Y4(MU, 1); MM(1); Y4(P10, 2); Y4(MU, 2); MM(2); \
    Y4(S0, 0); Y4(SD, 1); Y4(SD, 2); X4(P110);

__global__ void __launch_bounds__(NT, 1)
tp_kernel(const int4* __restrict__ dst, const int4* __restrict__ src, const char* __restrict__ rhat, Scratch* __restrict__ gs,
          const char* __restrict__ x, const char* __restrict__ ea, const __nv_bfloat16* __restrict__ eps, char* __restrict__ out,
          const __grid_constant__ CUtensorMap m_wr, const __grid_constant__ CUtensorMap m_w0, const __grid_constant__ CUtensorMap m_w1,
          const __grid_constant__ CUtensorMap m_x) {
    extern __shared__ __align__(1024) char smem_raw[];
    constexpr uint32_t sm = 1024;
    spin_check((uint32_t)__cvta_generic_to_shared(smem_raw) == sm ? 0 : 2 * SPIN_LIMIT);
    int t;
    asm volatile("mov.u32 %0, %%tid.x;" : "=r"(t));
    const int w = t >> 5, lane = t & 31, b = blockIdx.x;

    const int g = lane >> 2, q = lane & 3, mat = lane >> 3, r = lane & 7;
    const int e0 = b * CH + t * 8, ne = min(CH, NE - b * CH);
    const bool act = t * 8 < ne;
    uint32_t d[8];
#pragma unroll
    for (int k = 0; k < 2; k++) ldg128(d + 4 * k, dst + e0 / 4 + k, act);
    uint32_t tag = ld_rlx(&gs->epoch[b * 32]), epl;
    asm volatile("ld.global.nc.u16 %0, [%1];" : "=r"(epl) : "l"(eps + min(lane, 26)));
    if (t < 60) sts128(sm + O_BCNT + 16 * t, make_uint4(0, 0, 0, 0));
    if (t == NT - 1) {
#pragma unroll
        for (int i = 0; i < 5; i++) mbar_init(sm + O_WBA + 8 * i, 1);
        fence_async();
        mbar_expect(sm + O_WBC, ne * 10); mbar_expect(sm + O_WBA, 20480); mbar_expect(sm + O_WBB, 81920); mbar_expect(sm + O_WBD, 81920);
        mbar_expect(sm + O_WBE, (((TP & 15) != 15) + ((TP >> 4 & 15) != 15) + ((TP >> 8 & 15) != 15) + ((TP >> 12) != 15)) * (NLOC / 4 * 128));
        WLD(6);
        spin_check(tag);
        bulk(sm + O_RH, rhat + b * (CH * 6), ne * 6, sm + O_WBC);
        bulk(sm + O_SRC, src + b * (CH / 4), ne * 4, sm + O_WBC);
        tma3d(sm + O_WR0, &m_wr, 0, 0, sm + O_WBA);
        tma3d(sm + O_WR1, &m_wr, 0, 5, sm + O_WBA);
        WLD(0);
    }
    if (t == 320) {
#pragma unroll
        for (int i = 0; i < NSLOT; i++) {
            sts128(sm + O_RING + i * SLOT + S_C + 64, make_uint4(0, 0, 0, 0));
            mbar_init(sm + O_RING + i * SLOT + S_FULL, 32); mbar_init(sm + O_RING + i * SLOT + S_EMPTY, 8);
        }
    }
#pragma unroll
    for (int k = 0; k < LZ; k++) sts128(sm + O_L + 16 * (t + k * NT), make_uint4(0, 0, 0, 0));
    if (t < 80) sts32(sm + O_NCNT + 4 * t, t <= NLOC ? 4 * t : 0);
    if (t < 68) sts32(sm + O_NODE + 4 * t, 0);
    uint32_t ba[8], rk[8];
    if (w < 10) bar_sync(1, 320);
    tag = (tag + 1) << 30;
    if (act) {
#pragma unroll
        for (int i = 0; i < 8; i++) {
            const uint32_t l = __umulhi(d[i], (uint32_t)((1ull << 32) / G + 1));
            ba[i] = d[i] * 4 - l * (4 * G);
            d[i] = l * 4 + (tag + ((e0 + i + 1) << 9) + 4);
            rk[i] = atoms_add(sm + O_BCNT + ba[i], 4);
        }
#pragma unroll
        for (int i = 0; i < 8; i++)
            asm volatile("{.reg .pred p; setp.lt.u32 p, %2, 124; @p st.shared.u32 [%0], %1;}"
                         ::"r"(sm + O_KT + ba[i] * 32 + ((ba[i] + rk[i]) & 127)), "r"(d[i]), "r"(rk[i]) : "memory");
    }
    TS(0);
    __syncthreads();
    {
        int v[5], sum = 0;
#pragma unroll
        for (int i = 0; i < 5; i++) { v[i] = lds32(sm + O_BCNT + 4 * (lane * 5 + i)); sum += v[i]; }
        int e = warp_incl(sum) - sum;
        if (w == 10) {
#pragma unroll
            for (int i = 0; i < 5; i++) {
                const int k = lane * 5 + i;
                if (k < G) sts32(sm + O_KT + k * 128 + ((k * 4 + 124) & 127), tag | v[i] << 10 | e >> 2);
                e += v[i];
            }
            __syncwarp();
            if (lane == 0) {
                fence_async();
                bulk_st(&gs->keys[b * (G * 32)], sm + O_KT, G * 128);
                WLD(5);
            }
        } else {
#pragma unroll
            for (int i = 0; i < 5; i++) { sts32(sm + O_BOFF + 4 * (lane * 5 + i), e); e += v[i]; }
        }
        __syncwarp();
    }
    TS(11);
    const uint32_t sw = (uint32_t)(((2 * (w & 3) + (mat & 1)) ^ r) * 16 + ((mat >> 1) * 8 + r) * 128);
    uint32_t wr[5][4];
    const uint32_t* kp = &gs->keys[(w * SEGW * G + b) * 32 + ((lane + b) & 31)];
    uint32_t kv[SEGW + 1], ho[SEGW + 1], nk[SEGW + 1], old;
    if (act) {
        uint32_t mx = 0;
#pragma unroll
        for (int i = 0; i < 8; i++) { mx = max(mx, rk[i]); ba[i] = rk[i] + lds32(sm + O_BOFF + ba[i]); }
        if (mx >= 124) {
#pragma unroll
            for (int i = 0; i < 8; i++)
                if (rk[i] >= 124) st_rlx(&gs->more[b * CH + (ba[i] >> 2)], d[i]);
        }
    }
#define WRP 0
    auto ldwr = [&]() {
    if (w < 8) {
        mbar_wait(sm + O_WBA, 0);
#pragma unroll
        for (int p = 0; p < 5; p++) {
            const int c = 2 * p + (w >> 2);
            ldsm4t(wr[p], sm + (c < 5 ? O_WR0 : O_WR1 - 5 * 2048) + c * 2048 + sw);
        }
    } else {
        const uint64_t xl = (uint64_t)(x - 1024 + r * 16) - (tag >> 6), al = (uint64_t)(ea - 32 + (lane & 1) * 16) - (tag >> 4);
        const uint64_t ml = (uint64_t)gs->list + lane * 8;
        const uint32_t row = 0x76b821a3u >> 4 * r & 15, row0 = 0xc5bfe0cbu >> 4 * r & 15;
        const uint32_t c[13] = {(uint32_t)xl, (uint32_t)(xl >> 32), (uint32_t)al, (uint32_t)(al >> 32), (uint32_t)ml, (uint32_t)(ml >> 32),
            mat * 2048u + (r ^ 2 * mat) * 16, mat * 2048u + 1024 + (r ^ 2 * mat ^ 1) * 16,
            S_A + (lane & 2) * 128u + g * 32 + ((lane ^ lane >> 4) & 1) * 16, S_C + (mat & 1 ? row : row0) * 16, lane & 1 ? 16u : 9u, lane & 30u,
            lane == 4 ? 0xffff0000u : 0u};
#pragma unroll
        for (int i = 0; i < 20; i++) wr[i >> 2][i & 3] = i < 13 ? opaque(c[i % 13], lane) : 0;
    }
    };
    if (!WRP) ldwr();
    TS(21);
    mbar_wait(sm + O_WBC, 0);
    TS(22);
    if (act) {
        uint32_t s[8], y[12];
#pragma unroll
        for (int k = 0; k < 3; k++) *(uint4*)&y[4 * k] = lds128(sm + O_RH + t * 48 + k * 16);
#pragma unroll
        for (int k = 0; k < 2; k++) *(uint4*)&s[4 * k] = lds128(sm + O_SRC + t * 32 + k * 16);
#pragma unroll
        for (int i = 0; i < 8; i++) {
            const int k = 3 * i / 2;
            sts64(sm + O_OUT + ba[i] * 2, __byte_perm(y[k], s[i] + (tag >> 16) + 1, i & 1 ? 0x5432 : 0x5410),
                  i & 1 ? y[k + 1] : __byte_perm(y[k], y[k + 1], 0x5432));
        }
    }
    TS(12);
    __syncthreads();
    if (t == 352) { fence_async(); bulk_st(&gs->vals[b * CH], sm + O_OUT, ne * 8); WLD(7); }
    if (WRP) ldwr();

    const uint32_t am = lane < 31 ? 511 : 0, none = tag | (320 + 4 * lane);
    auto check = [&]() {
        old = 0;
#pragma unroll
        for (int j = 0; j < SEGW; j++) {
            ho[j] = __shfl_sync(0xffffffffu, kv[j], 31);
            kv[j] = ho[j] >= (lane < 31 ? tag + ((lane + 1) << 12) : 0u) ? kv[j] : none;
            old |= kv[j] ^ tag;
        }
        return __any_sync(0xffffffffu, old >> 30);
    };
#pragma unroll
    for (int j = 0; j < SEGW; j++) kv[j] = ld_rlx(kp + j * (G * 32));
    TS(1);
    if (t == 352) WLD(1);
    TV(19, 0); TV(23, 0);
    for (int it = 0; check(); it++) {
        spin_check(it);
        if (it == 0) TS(20);
        TV(19, (it + 1) * 100);
#pragma unroll
        for (int j = 0; j < SEGW; j++)
            if (__any_sync(0xffffffffu, (kv[j] ^ tag) >> 30)) kv[j] = ld_rlx(kp + j * (G * 32));
    }
    TS(3);
    if (t == 352) WLD(2);
    kv[SEGW] = none; ho[SEGW] = 0;
    bool slow = false;
    const bool more = __any_sync(0xffffffffu, lane == 31 && (old & 0xfe0000));
    if (more) {
        int c = lane;
#pragma unroll
        for (int j = 0; j < SEGW; j++) {
            const int n = max((int)(ho[j] >> 12 & 0xfff) - 31, 0);
            if ((unsigned)c < (unsigned)n) ho[SEGW] = j * CH + (ho[j] & 0xfff) + 31 + c - lane;
            c -= n;
        }
        slow = lane == 31 && c < 0;
        if (c < 0 && lane < 31)
            for (int it = 0; ((kv[SEGW] = ld_rlx(&gs->more[w * SEGW * CH + lane + ho[SEGW]])) ^ tag) >> 30; it++) spin_check(it);
        __syncwarp();
    }
#define EV 0
    uint32_t na_[SEGW + 1];
    uint64_t vp = (uint64_t)&gs->vals[w * SEGW * CH + lane], vv[SEGW + 1];
#pragma unroll
    for (int j = 0; j <= SEGW; j++) vv[j] = tag;
    auto ldv = [&](bool again) {
#pragma unroll
        for (int j = 0; j <= SEGW; j++)
            asm volatile("{.reg .pred p; setp.lt.u32 p, %2, 320; @p ld.relaxed.gpu.global.b64 %0, [%1];}" : "+l"(vv[j])
                         : "l"(madw(j < SEGW ? ho[j] & 0xfff : ho[j], 8, vp) + (j < SEGW ? j * CH * 8 : 0)),
                           "r"(again ? (((uint32_t)vv[j] ^ tag) >> 30 ? 0 : 320) : na_[j]) : "memory");
    };
#pragma unroll
    for (int j = 0; j <= SEGW; j++) na_[j] = (kv[j] & am) | (none & 511 & ~am);
    if (EV == 4) ldv(false);
#pragma unroll
    for (int j = 0; j <= SEGW; j++) nk[j] = atoms_add(sm + O_NCNT + na_[j], 512);
    if (EV == 3) ldv(false);
    auto visit = [&](auto f) {
#pragma unroll 1
        for (int j = 0; j < SEGW; j++) {
            const uint32_t* kl = &gs->keys[((w * SEGW + j) * G + b) * 32];
            const uint32_t h = ld_rlx(kl + ((31 + b) & 31));
#pragma unroll 1
            for (int i = lane; i < (h >> 12 & 0xfff); i += 32) {
                const int o = (w * SEGW + j) * CH + (h & 0xfff) + i;
                uint32_t k;
                int it = 0;
                do { k = ld_rlx(i < 31 ? kl + ((i + b) & 31) : &gs->more[o]); spin_check(it++); } while ((k ^ tag) >> 30);
                f(k, o, i);
            }
        }
    };
    slow = __syncthreads_or(slow);
    if (slow) {
        if (t < 80) sts32(sm + O_NCNT + 4 * t, t <= NLOC ? 4 * t : 0);
        __syncthreads();
        visit([&](uint32_t k, int, int) { atoms_add(sm + O_NCNT + (k & 511), 512); });
        __syncthreads();
    }
    TS(4);
    if (t == 352) WLD(3);
    if (EV == 2) ldv(false);
    if (w < 10) {
        const uint32_t key = lds32(sm + O_NCNT + 4 + (t & ~3));
        uint4 k[5];
#pragma unroll
        for (int i = 0; i < 5; i++) k[i] = lds128(sm + O_NCNT + q * 80 + i * 16);
        uint32_t c[4] = {0, 0, 0, 0};
#pragma unroll
        for (int i = 0; i < 5; i++) { c[0] += (key - k[i].x) >> 31; c[1] += (key - k[i].y) >> 31; c[2] += (key - k[i].z) >> 31; c[3] += (key - k[i].w) >> 31; }
        int rank = c[0] + c[1] + c[2] + c[3];
        rank += __shfl_xor_sync(0xffffffffu, rank, 1);
        rank += __shfl_xor_sync(0xffffffffu, rank, 2);
        if (ASC && rank < 2 * NPRIV) rank = (2 * NPRIV - 1 - rank) ^ 1;
        if (t < NLOC * 4) sts32(sm + O_SORT + 4 * rank, key);
    }
    if (EV == 5) ldv(false);
    __syncthreads();
    TS(2);
    const bool on = lane < NLOC / 4;
    const uint4 k4 = lds128(sm + O_SORT + 16 * (on ? lane : 0));
    if (EV == 1) ldv(false);
    const uint32_t ks[4] = {k4.x, k4.y, k4.z, k4.w};
    const int n0 = on ? max(1u, (ks[0] + 3584) >> 12) : 0, n1 = on ? max(1u, (ks[2] + 3584) >> 12) : 0;
    const int u2 = warp_incl(n0 + n1), u1 = u2 - n1, u0 = u1 - n0;
    const int total = __shfl_sync(0xffffffffu, u2, 31);
    slow |= total > CAPT;
    int gbase = b * CAPT + 1;
    if (on) {
#pragma unroll
        for (int i = 0; i < 4; i++) {
            const int a = ks[i] & 511, node = a * (G / 4) - G + b, o = (i >> 1 ? u1 : u0) * 256 + (i & 1) * 16;
            const uint32_t mk = (node < NN ? node + 1 : 0) + ((i >> 1 ? n1 : n0) << 16);
            sts64(sm + O_NOFF + 2 * a, o - (a >> 4), mk + a * 16);
            if (!slow && ks[i] < 512) sts32(sm + O_L + 4 + o, mk);
        }
    }
    __syncwarp();
    if (t == 352) WLD(8);
    if (!slow) {
        uint32_t mk[SEGW + 1];
        TS(13);
        if (t == 352) { asm volatile("cp.async.bulk.wait_group.read 0;" ::: "memory"); }
        if (EV == 0) ldv(false);
        if (t == 352) WLD(4);
        TS(16);
#pragma unroll
        for (int j = 0; j <= SEGW; j++) {
            const uint2 o = lds64(sm + O_NOFF + 2 * na_[j]);
            mk[j] = o.y - nk[j] * 16; nk[j] = o.x + (nk[j] >> 4);
        }
        for (int it = 0;; it++) {
            old = 0;
#pragma unroll
            for (int j = 0; j <= SEGW; j++) old |= (uint32_t)vv[j] ^ tag;
            if (!__any_sync(0xffffffffu, old >> 30)) break;
            spin_check(it);
            vp = __shfl_sync(0xffffffffu, vp, lane);
            ldv(true);
            TV(23, (it + 1) * 100);
        }
        TS(17);
#pragma unroll
        for (int j = 0; j <= SEGW; j++)
            asm volatile("{.reg .pred p; setp.ne.u32 p, %3, %5; @p st.shared.v4.u32 [%0], {%1,%2,%3,%4};}"
                         ::"r"(sm + O_L + nk[j]), "r"(kv[j]), "r"(mk[j]), "r"((uint32_t)vv[j]), "r"((uint32_t)(vv[j] >> 32)), "r"(tag) : "memory");
        TS(18);
        if (na_[SEGW] < 320) gs->more[w * SEGW * CH + lane + ho[SEGW]] = 0;
    } else {
        int so = 0;
        if (t == 352) WLD(4);
#pragma unroll
        for (int j = 0; j < SEGW; j++) so += ho[j] & 0xfff;
        if (lane == 0) atoms_add(sm + O_SUM, so);
        if (t == 352) asm volatile("cp.async.bulk.wait_group.read 0;" ::: "memory");
        __syncthreads();
        gbase = TBIG + (lds32(sm + O_SUM) >> 3) + (NLOC + 5) * b;
        auto put = [&](uint32_t k, uint64_t e, uint32_t a, int rank) {
            const uint2 o = lds64(sm + O_NOFF + 2 * a);
            gs->list[gbase * 16 + ((o.x + (a >> 4)) >> 4) + rank * 2] = make_uint4(k, o.y - a * 16 - (rank << 13), e, e >> 32);
        };
        visit([&](uint32_t k, int o, int i) {
            uint64_t e;
            int it = 0;
            do {
                asm volatile("ld.relaxed.gpu.global.b64 %0, [%1];" : "=l"(e) : "l"(&gs->vals[o]) : "memory");
                spin_check(it++);
            } while (((uint32_t)e ^ tag) >> 30);
            if (i >= 31) gs->more[o] = 0;
            put(k, e, k & 511, atoms_add(sm + O_NCUR + (k & 511), 1));
        });
#pragma unroll 1
        for (int i = 0; i < 4; i++) {
            const uint32_t k = i == 0 ? ks[0] : i == 1 ? ks[1] : i == 2 ? ks[2] : ks[3];
#pragma unroll 1
            for (int p = (k >> 9) + w; p < (i >> 1 ? n1 : n0) * 8; p += NT / 32) put(0, 0, k & 511, p);
        }
        __threadfence();
    }
    if (t == 352) WLD(9);
    const uint32_t iw0 = (gbase + u0) << 12 | n0, iw1 = (gbase + u1) << 12 | n1;
    __syncthreads();
    TS(5);

    if (w >= 8) {
        asm volatile("setmaxnreg.dec.sync.aligned.u32 " STR(PREG) ";");
        const int h = __reduce_max_sync(0xffffffffu, w & 3);
        gbase = __reduce_min_sync(0xffffffffu, iw0) >> 12;
        int pos = gbase + h, end = __reduce_max_sync(0xffffffffu, lane == NPRIV / 2 ? (NPRIV & 1 ? iw1 : iw0) : 0) >> 12;
        const int bytes = gbase < TBIG ? ((__reduce_max_sync(0xffffffffu, iw0) >> 12) - gbase) * 256 : 0;
        const uint32_t ring = sm + O_RING;
        const uint64_t xl = wr[0][0] | (uint64_t)wr[0][1] << 32, al = wr[0][2] | (uint64_t)wr[0][3] << 32, ml = wr[1][0] | (uint64_t)wr[1][1] << 32;
        const uint32_t xoff[2] = {wr[1][2], wr[1][3]}, aoff = wr[2][0], coff = wr[2][1], sh = wr[2][2], ial = wr[2][3], sel = wr[3][0];
        auto lde = [&](uint2& e, int p) {
            asm volatile("{.reg .pred p; setp.gt.s32 p, %3, 0; @p ld.relaxed.gpu.global.v2.u32 {%0,%1}, [%2];}" : "+r"(e.x), "+r"(e.y) : "l"(madw(p, 256, ml)), "r"(p) : "memory");
        };
        uint2 e0[3] = {};
#pragma unroll
        for (int k = 0; k < 3; k++) {
            e0[k] = lds64(sm + O_L - 2048 + k * 1024 + t * 8);
            lde(e0[k], bytes ? 0 : pos + 4 * k);
        }
        if (h == 3) fence_async();
        pos += 4;

        int ev = 0, state = -2, tk = 0, nr = 0;
        uint32_t inf = 0;
        int ii = 0;
        auto take = [&]() {
            int v = 0;
            asm volatile("{.reg .pred p; setp.eq.s32 p, %2, 0; @p atom.relaxed.gpu.global.add.u32 %0, [%1], 1;}" : "+r"(v) : "l"(&gs->ticket), "r"(lane) : "memory");
            return v;
        };
        auto resolve = [&]() {
            const int k = __reduce_max_sync(0xffffffffu, tk);
            inf = tag;
            if (k < G * NPOOL) { const int l = k / G; ii = (k - l * G) * NPOOL + l; inf = ld_rlx(&gs->info[ii]);
                tk = (STAG) && ((NPRIV + 1 + nr + (STAG)) & 7) == 0 && k >= G * NPOOL - THETA ? G * NPOOL : take(); }
        };
        uint32_t so = ring + h * SLOT, ph = 0x80000000u;
        uint32_t spins = 0;
        asm volatile(".reg .pred z<5>;");
        while (true) {
            const uint2 e = e0[0];
            const uint32_t o = e.x >> sh, id = __shfl_sync(0xffffffffu, o, ial);
            uint32_t s[4];
#pragma unroll
            for (int j = 0; j < 4; j++) s[j] = __shfl_sync(0xffffffffu, o, 2 * j + 1, 8);
            const uint32_t nx = so == ring + (NSLOT - 1) * SLOT ? ph : ph ^ 0x80000000u, ey = lop_sel(e.y, nx, sel);
            const uint64_t ga = madw(id, 32, al);
            uint64_t gx[4];
#pragma unroll
            for (int j = 0; j < 4; j++) gx[j] = madw(s[j], 1024, xl);
            const uint32_t da = so + aoff, dx[2] = {so + xoff[0], so + xoff[1]}, dc = so + coff;
            asm volatile("setp.eq.u32 z0, %0, 0;\nsetp.eq.u32 z1, %1, 0;\nsetp.eq.u32 z2, %2, 0;\nsetp.eq.u32 z3, %3, 0;\nsetp.eq.u32 z4, %4, 0;\n"
                         ::"r"(NULLP(s[0])), "r"(NULLP(s[1])), "r"(NULLP(s[2])), "r"(NULLP(s[3])), "r"(id), "l"(ga), "r"(da), "r"(dx[0]), "r"(dx[1]), "r"(dc));
            lde(e0[0], state < 0 ? 0 : pos);
            asm volatile("{\n.reg .pred p;\n.reg .b64 s;\nmov.b64 s, {0, %2};\n"
                         "LOOP:\nmbarrier.try_wait.shared::cta.b64 p, [%1], s;\n@p bra DONE;\n"
                         "add.u32 %0, %0, 1;\nsetp.gt.u32 p, %0, %3;\n@p trap;\nbra LOOP;\nDONE:\n}"
                         : "+r"(spins) : "r"(so + S_EMPTY), "r"(ph), "n"(SPIN_LIMIT) : "memory");
            asm volatile("cp.async.cg.shared.global [%0], [%1], 16, z4;" ::"r"(da), "l"(ga) : "memory");
#define ROW(j) _Pragma("unroll") for (int k = 0; k < 8; k++) \
                asm volatile("cp.async.cg.shared.global [%0], [%1], 16, z" #j ";" ::"r"(dx[j >> 1] + (j & 1) * 8192 + k * 128), "l"(gx[j] + k * 128) : "memory")
            X4(ROW);
            stsm2t(dc, e.x, ey);
            asm volatile("cp.async.mbarrier.arrive.noinc.shared::cta.b64 [%0];" ::"r"(so + S_FULL) : "memory");
            const bool wrap = NSLOT == 5 ? so != ring : so >= ring + (NSLOT - 4) * SLOT;
            ph ^= wrap ? 0x80000000u : 0u;
            so = wrap ? so - (NSLOT - 4) * SLOT : so + 4 * SLOT;
            pos += 4;
            if (pos >= ev) {
                if (state < 0) {
                    e0[0] = e0[1]; e0[1] = e0[2];
                    if (state == -2) {
                        if (h == 0) TSW(24);
                        if (h == 3) TSW(25);
                        if (h & 1) bar_sync(7, NT);
                        else asm volatile("bar.arrive 7, %0;" ::"n"(NT) : "memory");
                        if (h == 0) mbar_wait(sm + O_WBE, 0);
                        if (h == 3) {
                            if (lane == 0) {
                                if (bytes) bulk_st(gs->list + gbase * 16, sm + O_L, bytes);
                                asm volatile("cp.async.bulk.wait_group.read 0;" ::: "memory");
                            }
                            __syncwarp();
                            if (lane == 0) {
                                for (int j = 0; j < 5; j++) tma3d(sm + O_W1 + j * 16384, &m_w1, 64 + 64 * j, 0, sm + O_WBB);
                            }
                            __syncwarp();
                        }
                        state = -1;
                    } else {
                        if (h == 3) {
                            if (lane == 0) asm volatile("cp.async.bulk.wait_group 0;\nfence.proxy.async;" ::: "memory");
                            __syncwarp();
                            const int i = opaque(2 * lane - NPRIV, lane);
                            if ((unsigned)i < NPOOL) st_rlx(&gs->info[b * NPOOL + i], tag | iw0);
                            if ((unsigned)(i + 1) < NPOOL) st_rlx(&gs->info[b * NPOOL + i + 1], tag | iw1);
                        }
                        bar_sync(6, 128);
                        ev = h ? end : end - 12; state = h ? 2 : 0;
                    }
                } else if (state == 0) { ev = end - 6; state = 1; tk = take(); }
                else if (state == 1) { resolve(); ev = end; state = 2; }
                else {
                    if (state == 3) break;
                    do {
                        const uint32_t mb = sm + O_MB + (nr & 15) * 8;
                        uint32_t rg;
                        nr++;
                        if (h == 0) {
                            for (int it = 0; (rg = __reduce_max_sync(0xffffffffu, inf ^ tag)) >> 30; it++) { spin_check(it); inf = ld_rlx(&gs->info[ii]); }
                            asm volatile("st.release.cta.shared.b64 [%0], %1;" ::"r"(mb), "l"(rg | (uint64_t)nr << 32) : "memory");
                            if (rg) resolve();
                        } else {
                            uint64_t m;
                            for (int it = 0;; it++) {
                                asm volatile("ld.acquire.cta.shared.b64 %0, [%1];" : "=l"(m) : "r"(mb) : "memory");
                                if (__all_sync(0xffffffffu, (int)(m >> 32) == nr)) break;
                                spin_check(it);
                            }
                            rg = __reduce_max_sync(0xffffffffu, (uint32_t)m);
                        }
                        pos = rg ? (int)(rg >> 12) + pos - end : 0;
                        end = rg ? (rg >> 12) + (rg & 0xfff) : 1;
                        state = rg ? 2 : 3;
                    } while (pos >= end);
                    ev = end;
                }
            }
        }
        mbar_wait31(so + S_EMPTY, ph);
        TSW(8 + (h & 1));
        if (lane == 0) sts32(so + S_N, 0);
        mbar_arrive(so + S_FULL);
        if (t == 256) {
            gs->epoch[b * 32] = (tag >> 30) % 3;
            if (atomicInc(&gs->done, G - 1) == G - 1) gs->ticket = 0;
        }
        asm volatile("cp.async.wait_all;" ::: "memory");
    } else {
        asm volatile("setmaxnreg.inc.sync.aligned.u32 " STR(CREG) ";");
        const uint32_t xa = opaque(((mat >> 1) * 8 + r) * 1024 + (w >> 2) * 128 + (((2 * (w & 3) + (mat & 1)) ^ r) * 16), lane);
        const uint32_t aa = opaque(S_A + ((mat >> 1) * 8 + r) * 32 + (((mat & 1) ^ (r >> 2)) * 16), lane);
        const uint32_t ya = opaque(S_C + (mat & 1) * 80 + (mat >> 1) * 16, lane);
        const uint32_t yc = opaque(S_C + (mat < 2 ? mat * 80 + 32 : (r >> 2) == (mat & 1) && q < 3 ? (mat & 1) * 80 + q * 16 : 64), lane);
        const uint32_t na = opaque(sm + O_NODE + mat * 4, lane);
        const uint32_t pw = sm + O_P + w * PW;
        const uint32_t fx = opaque(pw + (q < 3 ? P_1P0 + 2 * q * PSBO : P_1P1 + PSBO) + (mat & 1) * 128 + (r >> 2) * PSBO, lane);
        const uint32_t fyz = opaque(pw + (q < 3 ? (mat < 2 ? P_1P1 : P_1P2) + 2 * q * PSBO : mat < 2 ? P_0P0 : P_0P1) + (mat & 1) * 128 + (r >> 2) * PSBO, lane);
        uint32_t oh[4][2];
#pragma unroll
        for (int c = 0; c < 8; c++) oh[c & 3][c >> 2] = opaque(g == c ? 0x3F803F80u : 0u, lane);
        uint32_t eb[3];
#pragma unroll
        for (int k = 0; k < 3; k++) {
            const int i = (g & 3) * 9 + (q & 1) * 6 + k;
            const uint32_t lo = __shfl_sync(0xffffffffu, epl, i), hi = __shfl_sync(0xffffffffu, epl, i + 3);
            eb[k] = (g & 3) < 3 && (q >> 1) == (g >> 2) ? (q & 1 ? lo : lo | hi << 16) : 0u;
        }
        asm volatile(".reg .pred lane0;\nsetp.eq.u32 lane0, %0, 0;" ::"r"(lane));
        uint32_t w0[16][4], w1[4][4];
        mbar_wait(sm + O_WBD, 0);
#pragma unroll
        for (int k = 0; k < 16; k++) ldsm4t(w0[k], sm + O_W0S + (k >> 2) * 16384 + (w >> 2) * 8192 + (k & 3) * 2048 + sw);
#pragma unroll
        for (int k = 0; k < 4; k++) ldsm4t(w1[k], sm + O_W1S + (w >> 2) * 8192 + k * 2048 + sw);
        bar_sync(7, NT);
        TS(6);
        Acc A;
#pragma unroll
        for (int i = 0; i < 4; i++) { A.p00[i] = A.p110[i] = A.p10[0][i] = A.p10[1][i] = A.p10[2][i] = 0; A.t01[i] = A.m[0][i] = A.m[1][i] = A.m[2][i] = 0.f; }
        uint32_t room = 144 - (STAG) * 16;
        uint32_t so = sm + O_RING, ph, a[4], ok, go, mt = 0;
        mbar_wait(so + S_FULL, 0);
        ldsm4(a, so + aa);
        TS(7);
        while (true) {
            {
                constexpr int F = 1, XS = XS_F;
                uint32_t yb[8], f[4][4], R[5][4], u[4][4], sd[4];
                float y[4], z[4];
                const uint32_t sof = room & 112;
                SEQ_F
                room -= 16;
            }
            if (!(go && room)) {
                const uint32_t pu = __reduce_max_sync(0xffffffffu, ph);
                if (!room || !pu) {
                    asm volatile("fence.proxy.async.shared::cta;" ::: "memory");
                    mbar_wait(sm + O_WBB, 0);
                    bar_sync(1, 256);
                    float d0[8], d1[24];
                    const uint32_t wg = __reduce_max_sync(0xffffffffu, w >> 2);
                    const uint64_t db = (uint64_t)((sm + O_P) >> 4) | (8ull << 16) | ((uint64_t)(PSBO / 16) << 32);
                    const uint32_t da = ((sm + O_W1) >> 4 | 1 << 16) + wg * 512;
                    asm volatile("wgmma.fence.sync.aligned;" ::: "memory");
#pragma unroll
                    for (int k = 0; k < 16; k++) wg_rs16(d0, w0[k], db + (((k & 7) * PW + ((k >> 3) ? P_0P1 : P_0P0)) >> 4), k);
                    asm volatile("wgmma.commit_group.sync.aligned;" ::: "memory");
#pragma unroll
                    for (int k = 0; k < 4; k++) wg_rs48(d1, w1[k], db + ((k * PW + P_1P0) >> 4), k);
#pragma unroll
                    for (int k = 4; k < 24; k++)
                        wg_ss48(d1, (da + (k / 4 - 1) * 1024 + (k & 3) * 128) | (64ull << 32) | (1ull << 62), db + (((k & 7) * PW + ((k >> 3) == 0 ? P_1P0 : (k >> 3) == 1 ? P_1P1 : P_1P2)) >> 4), k);
                    asm volatile("wgmma.commit_group.sync.aligned;" ::: "memory");
                    const uint2 n0 = lds64(sm + O_NODE + mat * 16), n1 = lds64(sm + O_NODE + 64 + mat * 16);
                    const bool v0 = (mat * 16 - 16 & 112) >= room, v1 = mat * 16 + 48 >= room;
                    const uint32_t nd[4] = {v0 ? n0.x : 0, v1 ? n1.x : 0, v0 ? n0.y : 0, v1 ? n1.y : 0};
                    const uint64_t op = (uint64_t)(out - 1024 + (w & 3) * 256 + (w >> 2) * 128 + r * 16);
                    uint64_t oa[4];
#pragma unroll
                    for (int it = 0; it < 4; it++) oa[it] = madw(nd[it], 1024, op);
                    uint32_t sg = sm + O_P + (w & 4) * PW + ((mat >> 1) * 8 + r) * 128 + (((2 * (w & 3) + (mat & 1)) ^ r) * 16);
                    uint32_t sl = pw + mat * 128 + (r ^ mat) * 16, sl2 = pw + 512 + mat * 128 + (r ^ mat ^ 4) * 16;
                    asm volatile("wgmma.wait_group.sync.aligned 1;" ::: "memory");
#pragma unroll
                    for (int i = 0; i < 8; i++) asm volatile("" : "+f"(d0[i])::"memory");
                    uint32_t o[4][4], chk = sg & sl & sl2;
                    float gt[8];
#pragma unroll
                    for (int i = 0; i < 8; i++) {
                        asm("ex2.approx.ftz.f32 %0, %1;" : "=f"(gt[i]) : "f"(d0[i] * -1.4426950408889634f));
                        asm("rcp.approx.ftz.f32 %0, %1;" : "=f"(gt[i]) : "f"(gt[i] + 1.f));
                        chk &= __float_as_uint(gt[i]);
                    }
#pragma unroll
                    for (int i = 0; i < 4; i++) { o[0][i] = pack(d0[2 * i], d0[2 * i + 1]); chk &= o[0][i] & (uint32_t)(oa[i] >> 32); }
                    sts32(sm + O_TRASH, chk);
                    asm volatile("wgmma.wait_group.sync.aligned 0;" ::: "memory");
#pragma unroll
                    for (int i = 0; i < 24; i++) asm volatile("" : "+f"(d1[i])::"memory");
                    bar_sync(1, 256);
#pragma unroll
                    for (int i = 0; i < 4; i++)
#pragma unroll
                        for (int j = 0; j < 3; j++) o[1 + j][i] = pack(d1[8 * j + 2 * i] * gt[2 * i], d1[8 * j + 2 * i + 1] * gt[2 * i + 1]);
#pragma unroll
                    for (int j = 0; j < 4; j++) stsm4t(sg + j * PW, o[j][0], o[j][1], o[j][2], o[j][3]);
                    bar_sync(2 + wg, 128);
                    uint4 v[4];
#pragma unroll
                    for (int it = 0; it < 4; it++) v[it] = lds128((it & 1 ? sl2 : sl) + (it >> 1) * 1024);
#pragma unroll
                    for (int it = 0; it < 4; it++)
                        asm volatile("{.reg .pred p; setp.ne.u32 p, %5, 0; @p st.global.v4.u32 [%0], {%1,%2,%3,%4};}"
                                     ::"l"(oa[it]), "r"(v[it].x), "r"(v[it].y), "r"(v[it].z), "r"(v[it].w), "r"(nd[it]) : "memory");
                    __syncwarp();
                    room = 128;
                    if (!pu) break;
                }
                if (!ok) { mbar_wait31(so + S_FULL, pu); ldsm4(a, so + aa); }
                if (!(pu & 0xfffe)) continue;
            }
            while (true) {
                do {
                    constexpr int F = 0, XS = XS_R;
                    uint32_t yb[8], f[4][4], R[5][4], u[4][4], sd[4];
                    SEQ_R
                } while (go);
                if (ok) break;
                const uint32_t pu = __reduce_max_sync(0xffffffffu, ph);
                mbar_wait31(so + S_FULL, pu); ldsm4(a, so + aa);
                if (!(pu & 0xfffe)) break;
            }
        }
        TS(10);
    }
}

typedef CUresult (*EncFn)(CUtensorMap*, CUtensorMapDataType, cuuint32_t, void*, const cuuint64_t*, const cuuint64_t*,
                          const cuuint32_t*, const cuuint32_t*, CUtensorMapInterleave, CUtensorMapSwizzle,
                          CUtensorMapL2promotion, CUtensorMapFloatOOBfill);

void make_map(EncFn fn, CUtensorMap* m, void* p, int rows, int cols, int brows, int bcols, int bblk) {
    cuuint64_t dims[3] = {64, (cuuint64_t)rows, (cuuint64_t)cols / 64}, strides[2] = {(cuuint64_t)cols * 2, 128};
    cuuint32_t box[3] = {(cuuint32_t)bcols, (cuuint32_t)brows, (cuuint32_t)bblk}, es[3] = {1, 1, 1};
    fn(m, CU_TENSOR_MAP_DATA_TYPE_BFLOAT16, 3, p, dims, strides, box, es, CU_TENSOR_MAP_INTERLEAVE_NONE,
       bcols == 64 ? CU_TENSOR_MAP_SWIZZLE_128B : CU_TENSOR_MAP_SWIZZLE_NONE, CU_TENSOR_MAP_L2_PROMOTION_L2_128B, CU_TENSOR_MAP_FLOAT_OOB_FILL_NONE);
}

}

extern "C" void kernel_launch(void* const* d_in, const int* in_sizes, int n_in, void* d_out, int out_size) {
    static EncFn enc = nullptr;
    static void* scratch = nullptr;
    if (!enc) {
        void* fn = nullptr;
        cudaDriverEntryPointQueryResult qr;
        cudaGetDriverEntryPoint("cuTensorMapEncodeTiled", &fn, cudaEnableDefault, &qr);
        enc = (EncFn)fn;
        cudaGetSymbolAddress(&scratch, g_scratch);
        cudaFuncSetAttribute(tp_kernel, cudaFuncAttributeMaxDynamicSharedMemorySize, SMEM_BYTES);
    }
    CUtensorMap m_wr, m_w0, m_w1, m_x;
    make_map(enc, &m_wr, d_in[5], 16, 640, 16, 64, 5);
    make_map(enc, &m_w0, d_in[6], 256, 128, 64, 64, 2);
    make_map(enc, &m_w1, d_in[7], 384, 128, 64, 64, 2);
    make_map(enc, &m_x, d_in[0], NN * 8, 64, NLOC * 2, 8, 1);
    tp_kernel<<<G, NT, SMEM_BYTES>>>((const int4*)d_in[4], (const int4*)d_in[3], (const char*)d_in[1], (Scratch*)scratch,
                                     (const char*)d_in[0], (const char*)d_in[2], (const __nv_bfloat16*)d_in[8], (char*)d_out,
                                     m_wr, m_w0, m_w1, m_x);
}
```

```cpp
#include <cuda_runtime.h>
#include <cuda_bf16.h>
#include <cuda.h>
#include <stdint.h>
#include <stddef.h>

namespace {

constexpr int NN = 10000;
constexpr int NE = 320000;
constexpr int G = 132;
constexpr int NT = 384;
constexpr int CH = 2432;
constexpr int NLOC = (NN + G - 1) / G;
#define NPOOL 3
constexpr int NPAIR = NLOC / 2, NPRIV = NPAIR - NPOOL;
constexpr int SEGW = 11;

#define NSLOT 6
#define PP 0xffff
#define TP 0x9375
#define STAG (b & 7)
#define ASC (b & 1)
#define THETA (3 * G / 2)
#define THETB (3 * G / 4)
#define QOK (STAG)
#define QJ 3
#define WP 0x2222255
#define KR 6
#define WLD(p) { _Pragma("unroll") for (int j = 0; j < 4 + KR / 2; j++) if ((WP >> 4 * j & 15) == p) \
    tma3d(sm + (j < 4 ? O_W0S + j * 16384 : j < 6 ? O_W1S + (j - 4) * 8192 : O_WR1), j < 4 ? &m_w0 : &m_w1, j < 4 ? j * 64 : (j - 4) * 32, 0, sm + O_WBD); \
    _Pragma("unroll") for (int j = 0; j < 4; j++) { const int r0 = (b * 4 + j) * (NLOC / 4); \
        if ((PP >> 4 * j & 15) == p) pf_l2(x + r0 * 1024, min(NLOC / 4, NN - r0) * 1024); \
        if ((TP >> 4 * j & 15) == p) tma3d(sm + O_WR1 + 10240, &m_x, r0 * 8, 0, sm + O_WBE); } }
#define ALT 1
#define AWG 0
#define IL 1
#define RSL 1
#define FEN 1
#define GP 24
#define GS 2
#define ASP 20
#define INV 0
#define NULLP(v) v
#define CREG 224
#define PREG 56
#define STR2(x) #x
#define STR(x) STR2(x)

constexpr int S_A = 16384, S_C = S_A + 512, S_FULL = S_C + 144, S_EMPTY = S_FULL + 8, S_N = S_C + 160, SLOT = S_C + 256;

constexpr int PSBO = 272;
constexpr int PB1 = 5 * PSBO + 256, PB0 = PSBO + 256;
constexpr int P_1P0 = 0, P_1P1 = PB1, P_0P1 = 2 * PB1, P_0P0 = P_0P1 + PB0, P_1P2 = P_0P0 + PB0;
constexpr int PW = P_1P2 + PB1;

constexpr int up1k(int a) { return (a + 1023) / 1024 * 1024; }
constexpr int O_W1 = 0;
constexpr int O_P = 81920;
constexpr int O_RING = O_P + 8 * PW;
constexpr int O_WBA = O_RING + 6 * SLOT, O_WBB = O_WBA + 8, O_WBC = O_WBA + 16, O_WBD = O_WBA + 24, O_WBE = O_WBA + 32, O_TRASH = O_WBA + 40, O_NODE = O_WBA + 48;
constexpr int O_SUM = O_NODE + 128, O_MB = O_SUM + 16;
constexpr int SMEM_BYTES = O_MB + 128;
constexpr int CAPT = 192;
constexpr int O_L = 0, LZ = CAPT * 256 / (NT * 16), O_W0S = O_L + CAPT * 256, O_OUT = O_W0S + 65536, O_SRC = O_OUT + CH * 8;
constexpr int O_KT = O_RING + SLOT, O_RH = O_RING + 2 * SLOT;
constexpr int O_WR0 = up1k(O_RING + 3 * SLOT), O_WR1 = up1k(O_RING + 4 * SLOT), O_W1S = up1k(O_RING + 5 * SLOT);
constexpr int O_BCNT = O_WR0 + 10240, O_NCUR = O_BCNT + 640, O_NCNT = O_NCUR + 320;
constexpr int O_BOFF = O_NCNT + 512, O_SORT = O_BOFF + 640, O_NOFF = O_SORT + 320;
constexpr int TBIG = G * CAPT + 8, NTILE = TBIG + NE / 8 + G * (NLOC + 5);
static_assert(SMEM_BYTES <= 232448 && CAPT % 16 == 0 && NTILE < (1 << 18), "smem");
static_assert(LZ * NT * 16 == CAPT * 256 && O_W0S % 1024 == 0 && O_OUT <= O_RING && O_SRC + CH * 4 <= O_RING + S_C && G * 128 <= S_C, "staging");
static_assert(O_NOFF + 1024 <= O_RING + 3 * SLOT + S_C && O_W1S + 16384 <= O_RING + 5 * SLOT + S_C, "staging");
static_assert(O_RING % 128 == 0 && SLOT % 128 == 0 && O_W0S <= O_P && O_NOFF % 8 == 0, "layout");
static_assert(G * CH >= NE && NE % 8 == 0 && CH < 4096 && CH / 8 <= 320 && NE < (1 << 21), "chunks");
static_assert(SEGW * (NT / 32) == G && G <= 160 && G % 4 == 0, "segments");
static_assert(NLOC % 4 == 0 && NLOC < 80 && NLOC * 4 <= 320 && NN < 0x3fff && NE / 8 < 0xbfff && NPRIV >= 30, "scan width");

struct __align__(128) Scratch {
    uint32_t keys[G * G * 32];
    uint64_t vals[G * CH];
    uint32_t more[G * CH];
    uint32_t epoch[G * 32];
    uint32_t info[G * NPOOL];
    unsigned done, pad0[31], ticket, pad1[31 + 32 - G * NPOOL % 32];
    uint4 list[NTILE * 16];
};
static_assert(offsetof(Scratch, list) % 128 == 0, "list");
__device__ Scratch g_scratch;
#define GT(i)
#define TS(i)
#define TSW(i)
#define TV(i, v)

constexpr int SPIN_LIMIT = 1 << 24;

__device__ __forceinline__ void mbar_init(uint32_t a, int c) { asm volatile("mbarrier.init.shared::cta.b64 [%0], %1;" ::"r"(a), "r"(c) : "memory"); }
__device__ __forceinline__ void mbar_expect(uint32_t a, int b) { asm volatile("mbarrier.arrive.expect_tx.shared::cta.b64 _, [%0], %1;" ::"r"(a), "r"(b) : "memory"); }
__device__ __forceinline__ void mbar_arrive(uint32_t a) { asm volatile("mbarrier.arrive.shared::cta.b64 _, [%0];" ::"r"(a) : "memory"); }
__device__ __forceinline__ void mbar_wait(uint32_t a, uint32_t ph) {
    asm volatile("{\n.reg .pred p, q;\n.reg .u32 it;\n"
                 "mbarrier.try_wait.parity.shared::cta.b64 p, [%0], %1;\n"
                 "@p bra DONE;\n"
                 "mov.u32 it, 0;\n"
                 "LOOP:\n"
                 "mbarrier.try_wait.parity.shared::cta.b64 p, [%0], %1;\n"
                 "@p bra DONE;\n"
                 "add.u32 it, it, 1;\n"
                 "setp.gt.u32 q, it, %2;\n"
                 "@q trap;\n"
                 "bra LOOP;\n"
                 "DONE:\n}" ::"r"(a), "r"(ph), "n"(SPIN_LIMIT) : "memory");
}
__device__ __forceinline__ void mbar_wait31(uint32_t a, uint32_t ph) {
    asm volatile("{\n.reg .pred p, q;\n.reg .u32 it;\n.reg .b64 s;\n"
                 "mov.b64 s, {0, %1};\n"
                 "mbarrier.try_wait.shared::cta.b64 p, [%0], s;\n"
                 "@p bra DONE;\n"
                 "mov.u32 it, 0;\n"
                 "LOOP:\n"
                 "mbarrier.try_wait.shared::cta.b64 p, [%0], s;\n"
                 "@p bra DONE;\n"
                 "add.u32 it, it, 1;\n"
                 "setp.gt.u32 q, it, %2;\n"
                 "@q trap;\n"
                 "bra LOOP;\n"
                 "DONE:\n}" ::"r"(a), "r"(ph), "n"(SPIN_LIMIT) : "memory");
}
__device__ __forceinline__ void spin_check(int it) {
    asm volatile("{\n.reg .pred q;\nsetp.gt.s32 q, %0, %1;\n@q trap;\n}" ::"r"(it), "n"(SPIN_LIMIT));
}
__device__ __forceinline__ void ldsm4(uint32_t* r, uint32_t a) { asm volatile("ldmatrix.sync.aligned.m8n8.x4.shared.b16 {%0,%1,%2,%3}, [%4];" : "=r"(r[0]), "=r"(r[1]), "=r"(r[2]), "=r"(r[3]) : "r"(a) : "memory"); }
__device__ __forceinline__ void ldsm4t(uint32_t* r, uint32_t a) { asm volatile("ldmatrix.sync.aligned.m8n8.x4.trans.shared.b16 {%0,%1,%2,%3}, [%4];" : "=r"(r[0]), "=r"(r[1]), "=r"(r[2]), "=r"(r[3]) : "r"(a) : "memory"); }
__device__ __forceinline__ void stsm4t(uint32_t a, uint32_t r0, uint32_t r1, uint32_t r2, uint32_t r3) { asm volatile("stmatrix.sync.aligned.m8n8.x4.trans.shared.b16 [%0], {%1,%2,%3,%4};" ::"r"(a), "r"(r0), "r"(r1), "r"(r2), "r"(r3) : "memory"); }
__device__ __forceinline__ void stsm2t(uint32_t a, uint32_t r0, uint32_t r1) { asm volatile("stmatrix.sync.aligned.m8n8.x2.trans.shared.b16 [%0], {%1,%2};" ::"r"(a), "r"(r0), "r"(r1) : "memory"); }
__device__ __forceinline__ void mma16(float* d, const uint32_t* a, uint32_t b0, uint32_t b1) {
    asm("mma.sync.aligned.m16n8k16.row.col.f32.bf16.bf16.f32 {%0,%1,%2,%3}, {%4,%5,%6,%7}, {%8,%9}, {%0,%1,%2,%3};"
        : "+f"(d[0]), "+f"(d[1]), "+f"(d[2]), "+f"(d[3]) : "r"(a[0]), "r"(a[1]), "r"(a[2]), "r"(a[3]), "r"(b0), "r"(b1));
}
__device__ __forceinline__ void mma8(float* d, uint32_t a0, uint32_t a1, uint32_t b0) {
    asm("mma.sync.aligned.m16n8k8.row.col.f32.bf16.bf16.f32 {%0,%1,%2,%3}, {%4,%5}, {%6}, {%0,%1,%2,%3};"
        : "+f"(d[0]), "+f"(d[1]), "+f"(d[2]), "+f"(d[3]) : "r"(a0), "r"(a1), "r"(b0));
}
__device__ __forceinline__ void mma16z(float* d, const uint32_t* a, uint32_t b0, uint32_t b1) {
    asm("mma.sync.aligned.m16n8k16.row.col.f32.bf16.bf16.f32 {%0,%1,%2,%3}, {%4,%5,%6,%7}, {%8,%9}, {%10,%10,%10,%10};"
        : "=f"(d[0]), "=f"(d[1]), "=f"(d[2]), "=f"(d[3]) : "r"(a[0]), "r"(a[1]), "r"(a[2]), "r"(a[3]), "r"(b0), "r"(b1), "f"(0.f));
}
__device__ __forceinline__ uint32_t pack(float lo, float hi) { uint32_t r; asm("cvt.rn.bf16x2.f32 %0, %1, %2;" : "=r"(r) : "f"(hi), "f"(lo)); return r; }
__device__ __forceinline__ uint32_t hmul(uint32_t a, uint32_t b) { uint32_t r; asm("mul.rn.bf16x2 %0, %1, %2;" : "=r"(r) : "r"(a), "r"(b)); return r; }
__device__ __forceinline__ uint32_t hfma(uint32_t a, uint32_t b, uint32_t c) { uint32_t r; asm("fma.rn.bf16x2 %0, %1, %2, %3;" : "=r"(r) : "r"(a), "r"(b), "r"(c)); return r; }
__device__ __forceinline__ uint4 lds128(uint32_t a) { uint4 v; asm volatile("ld.shared.v4.u32 {%0,%1,%2,%3}, [%4];" : "=r"(v.x), "=r"(v.y), "=r"(v.z), "=r"(v.w) : "r"(a) : "memory"); return v; }
__device__ __forceinline__ void sts128(uint32_t a, uint4 v) { asm volatile("st.shared.v4.u32 [%0], {%1,%2,%3,%4};" ::"r"(a), "r"(v.x), "r"(v.y), "r"(v.z), "r"(v.w) : "memory"); }
__device__ __forceinline__ int lds32(uint32_t a) { int v; asm volatile("ld.shared.u32 %0, [%1];" : "=r"(v) : "r"(a) : "memory"); return v; }
__device__ __forceinline__ void sts32(uint32_t a, int v) { asm volatile("st.shared.u32 [%0], %1;" ::"r"(a), "r"(v) : "memory"); }
__device__ __forceinline__ int atoms_add(uint32_t a, int v) { int r; asm volatile("atom.shared.add.u32 %0, [%1], %2;" : "=r"(r) : "r"(a), "r"(v) : "memory"); return r; }
__device__ __forceinline__ uint32_t ld_rlx(const void* p) { uint32_t v; asm volatile("ld.relaxed.gpu.global.u32 %0, [%1];" : "=r"(v) : "l"(p) : "memory"); return v; }
__device__ __forceinline__ void st_rlx(void* p, uint32_t v) { asm volatile("st.relaxed.gpu.global.u32 [%0], %1;" ::"l"(p), "r"(v) : "memory"); }
__device__ __forceinline__ void bulk(uint32_t dst, const void* g, int n, uint32_t bar) {
    asm volatile("cp.async.bulk.shared::cluster.global.mbarrier::complete_tx::bytes [%0], [%1], %2, [%3];" ::"r"(dst), "l"(g), "r"(n), "r"(bar) : "memory");
}
__device__ __forceinline__ void bulk_st(void* g, uint32_t src, int n) {
    asm volatile("cp.async.bulk.global.shared::cta.bulk_group [%0], [%1], %2;\ncp.async.bulk.commit_group;" ::"l"(g), "r"(src), "r"(n) : "memory");
}
__device__ __forceinline__ uint2 lds64(uint32_t a) { uint2 v; asm volatile("ld.shared.v2.u32 {%0,%1}, [%2];" : "=r"(v.x), "=r"(v.y) : "r"(a) : "memory"); return v; }
__device__ __forceinline__ void sts64(uint32_t a, uint32_t x, uint32_t y) { asm volatile("st.shared.v2.u32 [%0], {%1,%2};" ::"r"(a), "r"(x), "r"(y) : "memory"); }
__device__ __forceinline__ void tma3d(uint32_t dst, const CUtensorMap* m, int c1, int c2, uint32_t bar) {
    asm volatile("cp.async.bulk.tensor.3d.shared::cluster.global.mbarrier::complete_tx::bytes [%0], [%1, {0, %3, %4}], [%2];"
                 ::"r"(dst), "l"(m), "r"(bar), "r"(c1), "r"(c2) : "memory");
}
__device__ __forceinline__ void pf_l2(const void* g, int n) {
    asm volatile("{.reg .pred p; setp.gt.s32 p, %1, 0; @p cp.async.bulk.prefetch.L2.global [%0], %1;}" ::"l"(g), "r"(n) : "memory");
}
__device__ __forceinline__ void fence_async() { asm volatile("fence.proxy.async.shared::cta;" ::: "memory"); }
__device__ __forceinline__ uint64_t madw(uint32_t a, uint32_t b, uint64_t c) { uint64_t r; asm("mad.wide.u32 %0, %1, %2, %3;" : "=l"(r) : "r"(a), "r"(b), "l"(c)); return r; }
__device__ __forceinline__ uint32_t lop_sel(uint32_t a, uint32_t b, uint32_t m) { uint32_t r; asm("lop3.b32 %0, %1, %2, %3, 0xd8;" : "=r"(r) : "r"(a), "r"(b), "r"(m)); return r; }
__device__ __forceinline__ uint32_t opaque(uint32_t v, int lane) { return __shfl_sync(0xffffffffu, v, lane); }
__device__ __forceinline__ void bar_sync(int id, int n) { asm volatile("bar.sync %0, %1;" ::"r"(id), "r"(n) : "memory"); }

__device__ __forceinline__ void wg_rs16(float* d, const uint32_t* a, uint64_t db, int sc) {
    asm volatile("{.reg .pred p; setp.ne.b32 p, %13, 0;\n"
                 "wgmma.mma_async.sync.aligned.m64n16k16.f32.bf16.bf16 {%0,%1,%2,%3,%4,%5,%6,%7}, {%8,%9,%10,%11}, %12, p, 1, 1, 0;}"
                 : "+f"(d[0]), "+f"(d[1]), "+f"(d[2]), "+f"(d[3]), "+f"(d[4]), "+f"(d[5]), "+f"(d[6]), "+f"(d[7])
                 : "r"(a[0]), "r"(a[1]), "r"(a[2]), "r"(a[3]), "l"(db), "r"(sc));
}
__device__ __forceinline__ void wg_rs48(float* d, const uint32_t* a, uint64_t db, int sc) {
    asm volatile("{.reg .pred p; setp.ne.b32 p, %29, 0;\n"
                 "wgmma.mma_async.sync.aligned.m64n48k16.f32.bf16.bf16 {%0,%1,%2,%3,%4,%5,%6,%7,%8,%9,%10,%11,%12,%13,%14,%15,%16,%17,%18,%19,%20,%21,%22,%23}, {%24,%25,%26,%27}, %28, p, 1, 1, 0;}"
                 : "+f"(d[0]), "+f"(d[1]), "+f"(d[2]), "+f"(d[3]), "+f"(d[4]), "+f"(d[5]), "+f"(d[6]), "+f"(d[7]),
                   "+f"(d[8]), "+f"(d[9]), "+f"(d[10]), "+f"(d[11]), "+f"(d[12]), "+f"(d[13]), "+f"(d[14]), "+f"(d[15]),
                   "+f"(d[16]), "+f"(d[17]), "+f"(d[18]), "+f"(d[19]), "+f"(d[20]), "+f"(d[21]), "+f"(d[22]), "+f"(d[23])
                 : "r"(a[0]), "r"(a[1]), "r"(a[2]), "r"(a[3]), "l"(db), "r"(sc));
}
__device__ __forceinline__ void wg_ss48(float* d, uint64_t da, uint64_t db, int sc) {
    asm volatile("{.reg .pred p; setp.ne.b32 p, %26, 0;\n"
                 "wgmma.mma_async.sync.aligned.m64n48k16.f32.bf16.bf16 {%0,%1,%2,%3,%4,%5,%6,%7,%8,%9,%10,%11,%12,%13,%14,%15,%16,%17,%18,%19,%20,%21,%22,%23}, %24, %25, p, 1, 1, 1, 0;}"
                 : "+f"(d[0]), "+f"(d[1]), "+f"(d[2]), "+f"(d[3]), "+f"(d[4]), "+f"(d[5]), "+f"(d[6]), "+f"(d[7]),
                   "+f"(d[8]), "+f"(d[9]), "+f"(d[10]), "+f"(d[11]), "+f"(d[12]), "+f"(d[13]), "+f"(d[14]), "+f"(d[15]),
                   "+f"(d[16]), "+f"(d[17]), "+f"(d[18]), "+f"(d[19]), "+f"(d[20]), "+f"(d[21]), "+f"(d[22]), "+f"(d[23])
                 : "l"(da), "l"(db), "r"(sc));
}

__device__ __forceinline__ int warp_incl(int v) {
#pragma unroll
    for (int o = 1; o < 32; o <<= 1)
        asm volatile("{.reg .pred p; .reg .b32 u; shfl.sync.up.b32 u|p, %0, %1, 0, 0xffffffff; @p add.s32 %0, %0, u;}" : "+r"(v) : "r"(o));
    return v;
}
__device__ __forceinline__ void ldg128(uint32_t* r, const void* p, bool on) {
    asm volatile("{.reg .pred p; setp.ne.u32 p, %5, 0; @p ld.global.nc.v4.u32 {%0,%1,%2,%3}, [%4];}"
                 : "=r"(r[0]), "=r"(r[1]), "=r"(r[2]), "=r"(r[3]) : "l"(p), "r"((uint32_t)on));
}

template <int V> struct IC { static constexpr int value = V; };
template <int N, int I = 0, class Fn> __device__ __forceinline__ void static_for(Fn f) { if constexpr (I < N) { f(IC<I>{}); static_for<N, I + 1>(f); } }

struct Acc {
    uint32_t p00[4], p110[4], p10[3][4];
    float t01[4], m[3][4];
};

#define LF(m) ldsm4t(f[m], so + xa + m * 256)
#define LY() ldsm4(yb, so + ya)
#define LC() ldsm4(yb + 4, so + yc)
#define LN() ph = lds32(so + S_N)
#define ADV() { if (F && ALT) asm volatile("{.reg .pred p; setp.ne.and.u32 p, %1, 0, lane0; @p mbarrier.arrive.shared::cta.b64 _, [%0];}" ::"r"(so + S_EMPTY), "r"(room) : "memory"); \
                else asm volatile("@lane0 mbarrier.arrive.shared::cta.b64 _, [%0];" ::"r"(so + S_EMPTY) : "memory"); \
                so = so == sm + O_RING + (NSLOT - 1) * SLOT ? sm + O_RING : so + SLOT; }
#define LA() asm volatile("{\n.reg .pred p, q;\n.reg .b64 s;\n.reg .f32 n;\nmov.b64 s, {0, %7};\nmbarrier.test_wait.shared::cta.b64 p, [%6], s;\n" \
                          "abs.f32 n, %7;\nsetp.gt.and.f32 q, n, 0f00000001, p;\nselp.u32 %4, 1, 0, p;\nselp.u32 %5, 1, 0, q;\n" \
                          "@p ldmatrix.sync.aligned.m8n8.x4.shared.b16 {%0,%1,%2,%3}, [%8];\n}" \
                          : "+r"(a[0]), "+r"(a[1]), "+r"(a[2]), "+r"(a[3]), "=r"(ok), "=r"(go) : "r"(so + S_FULL), "r"(ph), "r"(so + aa) : "memory")
#define RAD(p, s) { float c[4]; mma16z(c, wr[p], a[2 * s], a[2 * s + 1]); R[p][2 * s] = pack(c[0], c[1]); R[p][2 * s + 1] = pack(c[2], c[3]); }
#define MUL(n, x, y) (XS >> n & 1 ? hmul(y, x) : hmul(x, y))
#define FMA(n, x, y, z) (XS >> n & 1 ? hfma(y, x, z) : hfma(x, y, z))
#define ACC(n, x, y, z) z = F ? MUL(n, x, y) : FMA(n, x, y, z)
#define P00(i) ACC(0, f[0][i], R[0][i], A.p00[i ^ XA])
#define P10(k, i) ACC(1, f[1 + k][i], R[3][i], A.p10[k][i ^ XA])
#define S0(k, i) sd[i] = MUL(2, f[1 + k][i], yb[2 * k + (i >> 1)])
#define SD(k, i) sd[i] = FMA(2, f[1 + k][i], yb[2 * k + (i >> 1)], sd[i])
#define P110(i) ACC(3, sd[i], R[1][i], A.p110[i ^ XA])
#define TU(i) u[3][i ^ XU] = MUL(4, f[0][i], R[2][i])
#define TM() if (F) mma16z(A.t01, u[3], yb[6], yb[7]); else mma16(A.t01, u[3], yb[6], yb[7])
#define MU(k, i) u[k][i ^ XU] = MUL(5, f[1 + k][i], R[4][i])
#define MM(k) if (F) mma16z(A.m[k], u[k], yb[6], yb[7]); else mma16(A.m[k], u[k], yb[6], yb[7])
#define PK(v, h) pack(v[2 * (h)], v[2 * (h) + 1])
#define LM() { sts32(na + sof, mt); asm volatile("ld.shared.u16 %0, [%1];" : "=r"(mt) : "r"(so + ya + 48) : "memory"); }
#define FY(k) if (k == 0) mma16z(y, A.p10[0], oh[0][0], oh[0][1]); else mma16(y, k < 3 ? A.p10[k % 3] : A.p00, oh[k][0], oh[k][1])
#define FZ(k) if (k == 0) mma16z(z, A.p110, oh[3][0], oh[3][1]); \
              else if (k == 1) { const uint32_t mp[4] = {PK(A.m[0], XA ^ XU), PK(A.m[0], 1 ^ XA ^ XU), PK(A.m[1], XA ^ XU), PK(A.m[1], 1 ^ XA ^ XU)}; mma16(z, mp, eb[0], eb[1]); } \
              else mma8(z, PK(A.m[2], XA ^ XU), PK(A.m[2], 1 ^ XA ^ XU), eb[2])
#define SX() stsm2t(fx + sof, PK(A.t01, XU), PK(A.t01, 1 ^ XU))
#define SY() stsm4t(fyz + sof, PK(y, XA), PK(y, 1 ^ XA), PK(z, XA), PK(z, 1 ^ XA))
#define G0(k) wg_rs16(d0, w0[k], db + ((((k) & 7) * PW + (((k) >> 3) ? P_0P1 : P_0P0)) >> 4), k)
#define G1(i) { constexpr int k_ = RSL ? ((i) + KR) % 24 : (i); const uint64_t bk = db + (((k_ & 7) * PW + ((k_ >> 3) == 0 ? P_1P0 : (k_ >> 3) == 1 ? P_1P1 : P_1P2)) >> 4); \
                if (k_ < KR) wg_rs48(d1, w1[k_ % KR], bk, i); else wg_ss48(d1, (da + (k_ - KR) / 2 * 512 + (k_ & 1) * 128) | (64ull << 32) | (1ull << 62), bk, i); }
#define X4(op) op(0); op(1); op(2); op(3)
#define Y4(op, k) op(k, 0); op(k, 1); op(k, 2); op(k, 3)
#define XA 1
#define XU 0
#define XS_R 63
#define SEQ_R LF(2); LN(); RAD(1,0); RAD(1,1); LC(); LY(); RAD(2,0); RAD(2,1); RAD(4,0); RAD(4,1); RAD(3,0); RAD(3,1); LF(3); LF(0); P10(1,1); \
    P10(1,0); P10(1,3); P10(1,2); S0(2,3); S0(2,2); S0(2,1); S0(2,0); RAD(0,1); RAD(0,0); P00(2); MU(2,0); MU(2,2); MU(2,1); MU(2,3); MM(2); MU(1,3); \
    P00(3); MU(1,2); LF(1); ADV(); LA(); P10(0,0); P10(0,1); P10(0,2); P10(0,3); SD(0,0); SD(0,2); SD(0,1); SD(0,3); SD(1,0); P110(0); SD(1,2); \
    P110(2); SD(1,1); P110(1); SD(1,3); P110(3); P00(0); MU(0,0); TU(0); TU(2); MU(1,1); TU(3); TU(1); TM(); P00(1); MU(0,2); MU(1,0); MM(1); MU(0,1); \
    MU(0,3); MM(0); P10(2,0); P10(2,2); P10(2,3); P10(2,1);
#define XS_F 0
#define SEQ_F LN(); LF(2); LY(); LF(1); LM(); RAD(2,0); RAD(2,1); LF(3); RAD(0,1); RAD(3,0); RAD(0,0); LC(); RAD(3,1); RAD(1,0); FZ(0); LF(0); \
    RAD(4,0); FY(0); FY(1); FZ(1); RAD(4,1); TU(0); MU(1,1); MU(1,0); MU(1,3); MU(1,2); TU(2); SX(); TU(1); TU(3); TM(); RAD(1,1); MM(1); ADV(); LA(); \
    FZ(2); P10(1,1); FY(3); P10(1,0); P10(1,3); S0(2,0); SD(0,0); SD(1,0); P10(1,2); P110(0); S0(2,2); SD(0,2); SD(1,2); P110(2); MU(2,1); MU(2,0); \
    MU(2,3); MU(2,2); MM(2); S0(2,3); SD(0,3); SD(1,3); P110(3); P00(0); MU(0,0); FY(2); SY(); P10(2,2); P10(2,3); P10(2,0); P10(2,1); S0(2,1); \
    SD(0,1); SD(1,1); P110(1); P00(1); MU(0,1); P00(2); MU(0,2); P10(0,3); P10(0,2); P10(0,1); P10(0,0); P00(3); MU(0,3); MM(0);

__global__ void __launch_bounds__(NT, 1)
tp_kernel(const int4* __restrict__ dst, const int4* __restrict__ src, const char* __restrict__ rhat, Scratch* __restrict__ gs,
          const char* __restrict__ x, const char* __restrict__ ea, const __nv_bfloat16* __restrict__ eps, char* __restrict__ out,
          const __grid_constant__ CUtensorMap m_wr, const __grid_constant__ CUtensorMap m_w0, const __grid_constant__ CUtensorMap m_w1,
          const __grid_constant__ CUtensorMap m_x) {
    extern __shared__ __align__(1024) char smem_raw[];
    constexpr uint32_t sm = 1024;
    spin_check((uint32_t)__cvta_generic_to_shared(smem_raw) == sm ? 0 : 2 * SPIN_LIMIT);
    int t;
    asm volatile("mov.u32 %0, %%tid.x;" : "=r"(t));
    const int w = t >> 5, lane = t & 31, b = blockIdx.x;

    const int g = lane >> 2, q = lane & 3, mat = lane >> 3, r = lane & 7;
    const int e0 = b * CH + t * 8, ne = min(CH, NE - b * CH);
    const bool act = t * 8 < ne;
    uint32_t d[8];
#pragma unroll
    for (int k = 0; k < 2; k++) ldg128(d + 4 * k, dst + e0 / 4 + k, act);
    uint32_t tag = ld_rlx(&gs->epoch[b * 32]), epl;
    asm volatile("ld.global.nc.u16 %0, [%1];" : "=r"(epl) : "l"(eps + min(lane, 26)));
    if (t < 60) sts128(sm + O_BCNT + 16 * t, make_uint4(0, 0, 0, 0));
    if (t == NT - 1) {
#pragma unroll
        for (int i = 0; i < 5; i++) mbar_init(sm + O_WBA + 8 * i, 1);
        fence_async();
        mbar_expect(sm + O_WBC, ne * 10); mbar_expect(sm + O_WBA, 20480); mbar_expect(sm + O_WBB, (24 - KR) * 4096); mbar_expect(sm + O_WBD, 65536 + KR * 4096);
        mbar_expect(sm + O_WBE, (((TP & 15) != 15) + ((TP >> 4 & 15) != 15) + ((TP >> 8 & 15) != 15) + ((TP >> 12) != 15)) * (NLOC / 4 * 128));
        WLD(6);
        spin_check(tag);
        bulk(sm + O_RH, rhat + b * (CH * 6), ne * 6, sm + O_WBC);
        bulk(sm + O_SRC, src + b * (CH / 4), ne * 4, sm + O_WBC);
        tma3d(sm + O_WR0, &m_wr, 0, 0, sm + O_WBA);
        tma3d(sm + O_WR1, &m_wr, 0, 5, sm + O_WBA);
        WLD(0);
    }
    if (t == 320) {
#pragma unroll
        for (int i = 0; i < NSLOT; i++) {
            sts128(sm + O_RING + i * SLOT + S_C + 64, make_uint4(0, 0, 0, 0));
            mbar_init(sm + O_RING + i * SLOT + S_FULL, 32); mbar_init(sm + O_RING + i * SLOT + S_EMPTY, 8);
        }
    }
#pragma unroll
    for (int k = 0; k < LZ; k++) sts128(sm + O_L + 16 * (t + k * NT), make_uint4(0, 0, 0, 0));
    if (t < 80) sts32(sm + O_NCNT + 4 * t, t <= NLOC ? 4 * t : 0);
    if (t < 68) sts32(sm + O_NODE + 4 * t, 0);
    uint32_t ba[8], rk[8];
    if (w < 10) bar_sync(1, 320);
    tag = (tag + 1) << 30;
    if (act) {
#pragma unroll
        for (int i = 0; i < 8; i++) {
            const uint32_t l = __umulhi(d[i], (uint32_t)((1ull << 32) / G + 1));
            ba[i] = d[i] * 4 - l * (4 * G);
            d[i] = l * 4 + (tag + ((e0 + i + 1) << 9) + 4);
            rk[i] = atoms_add(sm + O_BCNT + ba[i], 4);
        }
#pragma unroll
        for (int i = 0; i < 8; i++)
            asm volatile("{.reg .pred p; setp.lt.u32 p, %2, 124; @p st.shared.u32 [%0], %1;}"
                         ::"r"(sm + O_KT + ba[i] * 32 + ((ba[i] + rk[i]) & 127)), "r"(d[i]), "r"(rk[i]) : "memory");
    }
    TS(0);
    __syncthreads();
    {
        int v[5], sum = 0;
#pragma unroll
        for (int i = 0; i < 5; i++) { v[i] = lds32(sm + O_BCNT + 4 * (lane * 5 + i)); sum += v[i]; }
        int e = warp_incl(sum) - sum;
        if (w == 10) {
#pragma unroll
            for (int i = 0; i < 5; i++) {
                const int k = lane * 5 + i;
                if (k < G) sts32(sm + O_KT + k * 128 + ((k * 4 + 124) & 127), tag | v[i] << 10 | e >> 2);
                e += v[i];
            }
            __syncwarp();
            if (lane == 0) {
                fence_async();
                bulk_st(&gs->keys[b * (G * 32)], sm + O_KT, G * 128);
                WLD(5);
            }
        } else {
#pragma unroll
            for (int i = 0; i < 5; i++) { sts32(sm + O_BOFF + 4 * (lane * 5 + i), e); e += v[i]; }
        }
        __syncwarp();
    }
    TS(11);
    const uint32_t sw = (uint32_t)(((2 * (w & 3) + (mat & 1)) ^ r) * 16 + ((mat >> 1) * 8 + r) * 128);
    uint32_t wr[5][4];
    const uint32_t* kp = &gs->keys[(w * SEGW * G + b) * 32 + ((lane + b) & 31)];
    uint32_t kv[SEGW + 1], ho[SEGW + 1], nk[SEGW + 1], old;
    if (act) {
        uint32_t mx = 0;
#pragma unroll
        for (int i = 0; i < 8; i++) { mx = max(mx, rk[i]); ba[i] = rk[i] + lds32(sm + O_BOFF + ba[i]); }
        if (mx >= 124) {
#pragma unroll
            for (int i = 0; i < 8; i++)
                if (rk[i] >= 124) st_rlx(&gs->more[b * CH + (ba[i] >> 2)], d[i]);
        }
    }
#define WRP 0
    auto ldwr = [&]() {
    if (w < 8) {
        mbar_wait(sm + O_WBA, 0);
#pragma unroll
        for (int p = 0; p < 5; p++) {
            const int c = 2 * p + (w >> 2);
            ldsm4t(wr[p], sm + (c < 5 ? O_WR0 : O_WR1 - 5 * 2048) + c * 2048 + sw);
        }
    } else {
        const uint64_t xl = (uint64_t)(x - 1024 + r * 16) - (tag >> 6), al = (uint64_t)(ea - 32 + (lane & 1) * 16) - (tag >> 4);
        const uint64_t ml = (uint64_t)gs->list + lane * 8;
        const uint32_t row = 0x76b821a3u >> 4 * r & 15, row0 = 0xc5bfe0cbu >> 4 * r & 15;
        const uint32_t c[13] = {(uint32_t)xl, (uint32_t)(xl >> 32), (uint32_t)al, (uint32_t)(al >> 32), (uint32_t)ml, (uint32_t)(ml >> 32),
            mat * 2048u + (r ^ 2 * mat) * 16, mat * 2048u + 1024 + (r ^ 2 * mat ^ 1) * 16,
            S_A + (lane & 2) * 128u + g * 32 + ((lane ^ lane >> 4) & 1) * 16, S_C + (mat & 1 ? row : row0) * 16, lane & 1 ? 16u : 9u, lane & 30u,
            lane == 4 ? 0xffff0000u : 0u};
#pragma unroll
        for (int i = 0; i < 20; i++) wr[i >> 2][i & 3] = i < 13 ? opaque(c[i % 13], lane) : 0;
    }
    };
    if (!WRP) ldwr();
    TS(21);
    mbar_wait(sm + O_WBC, 0);
    TS(22);
    if (act) {
        uint32_t s[8], y[12];
#pragma unroll
        for (int k = 0; k < 3; k++) *(uint4*)&y[4 * k] = lds128(sm + O_RH + t * 48 + k * 16);
#pragma unroll
        for (int k = 0; k < 2; k++) *(uint4*)&s[4 * k] = lds128(sm + O_SRC + t * 32 + k * 16);
#pragma unroll
        for (int i = 0; i < 8; i++) {
            const int k = 3 * i / 2;
            sts64(sm + O_OUT + ba[i] * 2, __byte_perm(y[k], s[i] + (tag >> 16) + 1, i & 1 ? 0x5432 : 0x5410),
                  i & 1 ? y[k + 1] : __byte_perm(y[k], y[k + 1], 0x5432));
        }
    }
    TS(12);
    __syncthreads();
    if (t == 352) { fence_async(); bulk_st(&gs->vals[b * CH], sm + O_OUT, ne * 8); WLD(7); }
    if (WRP) ldwr();

    const uint32_t am = lane < 31 ? 511 : 0, none = tag | (320 + 4 * lane);
    auto check = [&]() {
        old = 0;
#pragma unroll
        for (int j = 0; j < SEGW; j++) {
            ho[j] = __shfl_sync(0xffffffffu, kv[j], 31);
            kv[j] = ho[j] >= (lane < 31 ? tag + ((lane + 1) << 12) : 0u) ? kv[j] : none;
            old |= kv[j] ^ tag;
        }
        return __any_sync(0xffffffffu, old >> 30);
    };
#pragma unroll
    for (int j = 0; j < SEGW; j++) kv[j] = ld_rlx(kp + j * (G * 32));
    TS(1);
    if (t == 352) WLD(1);
    TV(19, 0); TV(23, 0);
    for (int it = 0; check(); it++) {
        spin_check(it);
        if (it == 0) TS(20);
        TV(19, (it + 1) * 100);
#pragma unroll
        for (int j = 0; j < SEGW; j++)
            if (__any_sync(0xffffffffu, (kv[j] ^ tag) >> 30)) kv[j] = ld_rlx(kp + j * (G * 32));
    }
    TS(3);
    if (t == 352) WLD(2);
    kv[SEGW] = none; ho[SEGW] = 0;
    bool slow = false;
    const bool more = __any_sync(0xffffffffu, lane == 31 && (old & 0xfe0000));
    if (more) {
        int c = lane;
#pragma unroll
        for (int j = 0; j < SEGW; j++) {
            const int n = max((int)(ho[j] >> 12 & 0xfff) - 31, 0);
            if ((unsigned)c < (unsigned)n) ho[SEGW] = j * CH + (ho[j] & 0xfff) + 31 + c - lane;
            c -= n;
        }
        slow = lane == 31 && c < 0;
        if (c < 0 && lane < 31)
            for (int it = 0; ((kv[SEGW] = ld_rlx(&gs->more[w * SEGW * CH + lane + ho[SEGW]])) ^ tag) >> 30; it++) spin_check(it);
        __syncwarp();
    }
#define EV 0
    uint32_t na_[SEGW + 1];
    uint64_t vp = (uint64_t)&gs->vals[w * SEGW * CH + lane], vv[SEGW + 1];
#pragma unroll
    for (int j = 0; j <= SEGW; j++) vv[j] = tag;
    auto ldv = [&](bool again) {
#pragma unroll
        for (int j = 0; j <= SEGW; j++)
            asm volatile("{.reg .pred p; setp.lt.u32 p, %2, 320; @p ld.relaxed.gpu.global.b64 %0, [%1];}" : "+l"(vv[j])
                         : "l"(madw(j < SEGW ? ho[j] & 0xfff : ho[j], 8, vp) + (j < SEGW ? j * CH * 8 : 0)),
                           "r"(again ? (((uint32_t)vv[j] ^ tag) >> 30 ? 0 : 320) : na_[j]) : "memory");
    };
#pragma unroll
    for (int j = 0; j <= SEGW; j++) na_[j] = (kv[j] & am) | (none & 511 & ~am);
    if (EV == 4) ldv(false);
#pragma unroll
    for (int j = 0; j <= SEGW; j++) nk[j] = atoms_add(sm + O_NCNT + na_[j], 512);
    if (EV == 3) ldv(false);
    auto visit = [&](auto f) {
#pragma unroll 1
        for (int j = 0; j < SEGW; j++) {
            const uint32_t* kl = &gs->keys[((w * SEGW + j) * G + b) * 32];
            const uint32_t h = ld_rlx(kl + ((31 + b) & 31));
#pragma unroll 1
            for (int i = lane; i < (h >> 12 & 0xfff); i += 32) {
                const int o = (w * SEGW + j) * CH + (h & 0xfff) + i;
                uint32_t k;
                int it = 0;
                do { k = ld_rlx(i < 31 ? kl + ((i + b) & 31) : &gs->more[o]); spin_check(it++); } while ((k ^ tag) >> 30);
                f(k, o, i);
            }
        }
    };
    slow = __syncthreads_or(slow);
    if (slow) {
        if (t < 80) sts32(sm + O_NCNT + 4 * t, t <= NLOC ? 4 * t : 0);
        __syncthreads();
        visit([&](uint32_t k, int, int) { atoms_add(sm + O_NCNT + (k & 511), 512); });
        __syncthreads();
    }
    TS(4);
    if (t == 352) WLD(3);
    if (EV == 2) ldv(false);
    if (w < 10) {
        const uint32_t key = lds32(sm + O_NCNT + 4 + (t & ~3));
        uint4 k[5];
#pragma unroll
        for (int i = 0; i < 5; i++) k[i] = lds128(sm + O_NCNT + q * 80 + i * 16);
        uint32_t c[4] = {0, 0, 0, 0};
#pragma unroll
        for (int i = 0; i < 5; i++) { c[0] += (key - k[i].x) >> 31; c[1] += (key - k[i].y) >> 31; c[2] += (key - k[i].z) >> 31; c[3] += (key - k[i].w) >> 31; }
        int rank = c[0] + c[1] + c[2] + c[3];
        rank += __shfl_xor_sync(0xffffffffu, rank, 1);
        rank += __shfl_xor_sync(0xffffffffu, rank, 2);
        if (ASC && rank < 2 * NPRIV) rank = (2 * NPRIV - 1 - rank) ^ 1;
        if (t < NLOC * 4) sts32(sm + O_SORT + 4 * rank, key);
    }
    if (EV == 5) ldv(false);
    __syncthreads();
    TS(2);
    const bool on = lane < NLOC / 4;
    const uint4 k4 = lds128(sm + O_SORT + 16 * (on ? lane : 0));
    if (EV == 1) ldv(false);
    const uint32_t ks[4] = {k4.x, k4.y, k4.z, k4.w};
    const int n0 = on ? max(1u, (ks[0] + 3584) >> 12) : 0, n1 = on ? max(1u, (ks[2] + 3584) >> 12) : 0;
    const int u2 = warp_incl(n0 + n1), u1 = u2 - n1, u0 = u1 - n0;
    const int total = __shfl_sync(0xffffffffu, u2, 31);
    slow |= total > CAPT;
    int gbase = b * CAPT + 1;
    if (on) {
#pragma unroll
        for (int i = 0; i < 4; i++) {
            const int a = ks[i] & 511, node = a * (G / 4) - G + b, o = (i >> 1 ? u1 : u0) * 256 + (i & 1) * 16;
            const uint32_t mk = (node < NN ? node + 1 : 0) + ((i >> 1 ? n1 : n0) << 16);
            sts64(sm + O_NOFF + 2 * a, o - (a >> 4), mk + a * 16);
            if (!slow && ks[i] < 512) sts32(sm + O_L + 4 + o, mk);
        }
    }
    __syncwarp();
    if (t == 352) WLD(8);
    if (!slow) {
        uint32_t mk[SEGW + 1];
        TS(13);
        if (t == 352) { asm volatile("cp.async.bulk.wait_group.read 0;" ::: "memory"); }
        if (EV == 0) ldv(false);
        if (t == 352) WLD(4);
        TS(16);
#pragma unroll
        for (int j = 0; j <= SEGW; j++) {
            const uint2 o = lds64(sm + O_NOFF + 2 * na_[j]);
            mk[j] = o.y - nk[j] * 16; nk[j] = o.x + (nk[j] >> 4);
        }
        for (int it = 0;; it++) {
            old = 0;
#pragma unroll
            for (int j = 0; j <= SEGW; j++) old |= (uint32_t)vv[j] ^ tag;
            if (!__any_sync(0xffffffffu, old >> 30)) break;
            spin_check(it);
            vp = __shfl_sync(0xffffffffu, vp, lane);
            ldv(true);
            TV(23, (it + 1) * 100);
        }
        TS(17);
#pragma unroll
        for (int j = 0; j <= SEGW; j++)
            asm volatile("{.reg .pred p; setp.ne.u32 p, %3, %5; @p st.shared.v4.u32 [%0], {%1,%2,%3,%4};}"
                         ::"r"(sm + O_L + nk[j]), "r"(kv[j]), "r"(mk[j]), "r"((uint32_t)vv[j]), "r"((uint32_t)(vv[j] >> 32)), "r"(tag) : "memory");
        TS(18);
        if (na_[SEGW] < 320) gs->more[w * SEGW * CH + lane + ho[SEGW]] = 0;
    } else {
        int so = 0;
        if (t == 352) WLD(4);
#pragma unroll
        for (int j = 0; j < SEGW; j++) so += ho[j] & 0xfff;
        if (lane == 0) atoms_add(sm + O_SUM, so);
        if (t == 352) asm volatile("cp.async.bulk.wait_group.read 0;" ::: "memory");
        __syncthreads();
        gbase = TBIG + (lds32(sm + O_SUM) >> 3) + (NLOC + 5) * b;
        auto put = [&](uint32_t k, uint64_t e, uint32_t a, int rank) {
            const uint2 o = lds64(sm + O_NOFF + 2 * a);
            gs->list[gbase * 16 + ((o.x + (a >> 4)) >> 4) + rank * 2] = make_uint4(k, o.y - a * 16 - (rank << 13), e, e >> 32);
        };
        visit([&](uint32_t k, int o, int i) {
            uint64_t e;
            int it = 0;
            do {
                asm volatile("ld.relaxed.gpu.global.b64 %0, [%1];" : "=l"(e) : "l"(&gs->vals[o]) : "memory");
                spin_check(it++);
            } while (((uint32_t)e ^ tag) >> 30);
            if (i >= 31) gs->more[o] = 0;
            put(k, e, k & 511, atoms_add(sm + O_NCUR + (k & 511), 1));
        });
#pragma unroll 1
        for (int i = 0; i < 4; i++) {
            const uint32_t k = i == 0 ? ks[0] : i == 1 ? ks[1] : i == 2 ? ks[2] : ks[3];
#pragma unroll 1
            for (int p = (k >> 9) + w; p < (i >> 1 ? n1 : n0) * 8; p += NT / 32) put(0, 0, k & 511, p);
        }
        __threadfence();
    }
    if (t == 352) WLD(9);
    const uint32_t iw0 = (gbase + u0) << 12 | n0, iw1 = (gbase + u1) << 12 | n1;
    __syncthreads();
    TS(5);

    if (w >= 8) {
        asm volatile("setmaxnreg.dec.sync.aligned.u32 " STR(PREG) ";");
        const int h = __reduce_max_sync(0xffffffffu, w & 3);
        if (h == 0) TSW(28);
        gbase = __reduce_min_sync(0xffffffffu, iw0) >> 12;
        int pos = gbase + h, end = __reduce_max_sync(0xffffffffu, lane == NPRIV / 2 ? (NPRIV & 1 ? iw1 : iw0) : 0) >> 12;
        const int bytes = gbase < TBIG ? ((__reduce_max_sync(0xffffffffu, iw0) >> 12) - gbase) * 256 : 0;
        const uint32_t ring = sm + O_RING;
        const uint64_t xl = wr[0][0] | (uint64_t)wr[0][1] << 32, al = wr[0][2] | (uint64_t)wr[0][3] << 32, ml = wr[1][0] | (uint64_t)wr[1][1] << 32;
        const uint32_t xoff[2] = {wr[1][2], wr[1][3]}, aoff = wr[2][0], coff = wr[2][1], sh = wr[2][2], ial = wr[2][3], sel = wr[3][0];
        auto lde = [&](uint2& e, int p) {
            asm volatile("{.reg .pred p; setp.gt.s32 p, %3, 0; @p ld.relaxed.gpu.global.v2.u32 {%0,%1}, [%2];}" : "+r"(e.x), "+r"(e.y) : "l"(madw(p, 256, ml)), "r"(p) : "memory");
        };
        uint2 e0[3] = {};
#pragma unroll
        for (int k = 0; k < 3; k++) {
            e0[k] = lds64(sm + O_L - 2048 + k * 1024 + t * 8);
            lde(e0[k], bytes ? 0 : pos + 4 * k);
        }
        if (h == 3) fence_async();
        pos += 4;

        int ev = 0, state = -2, tk = 0, nr = 0;
        uint32_t inf = 0;
        int ii = 0;
        auto take = [&]() {
            int v = 0;
            asm volatile("{.reg .pred p; setp.eq.s32 p, %2, 0; @p atom.relaxed.gpu.global.add.u32 %0, [%1], 1;}" : "+r"(v) : "l"(&gs->ticket), "r"(lane) : "memory");
            return v;
        };
        auto resolve = [&]() {
            const int k = __reduce_max_sync(0xffffffffu, tk);
            inf = tag;
            if (k < G * NPOOL) { const int l = k / G; ii = (k - l * G) * NPOOL + l; inf = ld_rlx(&gs->info[ii]);
                const int j = (NPRIV + 1 + nr + (STAG)) & 7;
                tk = (QOK) && j <= QJ && k >= G * NPOOL - (j ? THETB : THETA) ? G * NPOOL : take(); }
        };
        uint32_t so = ring + h * SLOT, ph = 0x80000000u;
        uint32_t spins = 0;
        asm volatile(".reg .pred z<5>;");
        while (true) {
            const uint2 e = e0[0];
            const uint32_t o = e.x >> sh, id = __shfl_sync(0xffffffffu, o, ial);
            uint32_t s[4];
#pragma unroll
            for (int j = 0; j < 4; j++) s[j] = __shfl_sync(0xffffffffu, o, 2 * j + 1, 8);
            const uint32_t nx = so == ring + (NSLOT - 1) * SLOT ? ph : ph ^ 0x80000000u, ey = lop_sel(e.y, nx, sel);
            const uint64_t ga = madw(id, 32, al);
            uint64_t gx[4];
#pragma unroll
            for (int j = 0; j < 4; j++) gx[j] = madw(s[j], 1024, xl);
            const uint32_t da = so + aoff, dx[2] = {so + xoff[0], so + xoff[1]}, dc = so + coff;
            asm volatile("setp.eq.u32 z0, %0, 0;\nsetp.eq.u32 z1, %1, 0;\nsetp.eq.u32 z2, %2, 0;\nsetp.eq.u32 z3, %3, 0;\nsetp.eq.u32 z4, %4, 0;\n"
                         ::"r"(NULLP(s[0])), "r"(NULLP(s[1])), "r"(NULLP(s[2])), "r"(NULLP(s[3])), "r"(id), "l"(ga), "r"(da), "r"(dx[0]), "r"(dx[1]), "r"(dc));
            lde(e0[0], state < 0 ? 0 : pos);
            if (h == 0 && state == -2) TSW(29);
            if (h == 0 && state == -1) TSW(30);
            asm volatile("{\n.reg .pred p;\n.reg .b64 s;\nmov.b64 s, {0, %2};\n"
                         "LOOP:\nmbarrier.try_wait.shared::cta.b64 p, [%1], s;\n@p bra DONE;\n"
                         "add.u32 %0, %0, 1;\nsetp.gt.u32 p, %0, %3;\n@p trap;\nbra LOOP;\nDONE:\n}"
                         : "+r"(spins) : "r"(so + S_EMPTY), "r"(ph), "n"(SPIN_LIMIT) : "memory");
            asm volatile("cp.async.cg.shared.global [%0], [%1], 16, z4;" ::"r"(da), "l"(ga) : "memory");
#define ROW(j) _Pragma("unroll") for (int k = 0; k < 8; k++) \
                asm volatile("cp.async.cg.shared.global [%0], [%1], 16, z" #j ";" ::"r"(dx[j >> 1] + (j & 1) * 8192 + k * 128), "l"(gx[j] + k * 128) : "memory")
            X4(ROW);
            stsm2t(dc, e.x, ey);
            asm volatile("cp.async.mbarrier.arrive.noinc.shared::cta.b64 [%0];" ::"r"(so + S_FULL) : "memory");
            const bool wrap = NSLOT == 5 ? so != ring : so >= ring + (NSLOT - 4) * SLOT;
            ph ^= wrap ? 0x80000000u : 0u;
            so = wrap ? so - (NSLOT - 4) * SLOT : so + 4 * SLOT;
            pos += 4;
            if (pos >= ev) {
                if (state < 0) {
                    e0[0] = e0[1]; e0[1] = e0[2];
                    if (state == -2) {
                        if (h == 0) TSW(24);
                        if (h == 3) TSW(25);
                        if (h & 1) bar_sync(7, NT);
                        else asm volatile("bar.arrive 7, %0;" ::"n"(NT) : "memory");
                        if (h == 0) mbar_wait(sm + O_WBE, 0);
                        if (h == 3) {
                            if (lane == 0) {
                                if (bytes) bulk_st(gs->list + gbase * 16, sm + O_L, bytes);
                                asm volatile("cp.async.bulk.wait_group.read 0;" ::: "memory");
                            }
                            __syncwarp();
                            if (lane == 0) {
                                for (int j = 0; j < 12 - KR / 2; j++) tma3d(sm + O_W1 + j * 8192, &m_w1, KR * 16 + 32 * j, 0, sm + O_WBB);
                            }
                            __syncwarp();
                        }
                        state = -1;
                    } else {
                        if (h == 3) {
                            if (lane == 0) asm volatile("cp.async.bulk.wait_group 0;\nfence.proxy.async;" ::: "memory");
                            __syncwarp();
                            const int i = opaque(2 * lane - NPRIV, lane);
                            if ((unsigned)i < NPOOL) st_rlx(&gs->info[b * NPOOL + i], tag | iw0);
                            if ((unsigned)(i + 1) < NPOOL) st_rlx(&gs->info[b * NPOOL + i + 1], tag | iw1);
                        }
                        bar_sync(6, 128);
                        ev = h ? end : end - 12; state = h ? 2 : 0;
                    }
                } else if (state == 0) { ev = end - 6; state = 1; tk = take(); }
                else if (state == 1) { resolve(); ev = end; state = 2; }
                else {
                    if (state == 3) break;
                    do {
                        const uint32_t mb = sm + O_MB + (nr & 15) * 8;
                        uint32_t rg;
                        nr++;
                        if (h == 0) {
                            for (int it = 0; (rg = __reduce_max_sync(0xffffffffu, inf ^ tag)) >> 30; it++) { spin_check(it); inf = ld_rlx(&gs->info[ii]); }
                            asm volatile("st.release.cta.shared.b64 [%0], %1;" ::"r"(mb), "l"(rg | (uint64_t)nr << 32) : "memory");
                            if (rg) resolve();
                        } else {
                            uint64_t m;
                            for (int it = 0;; it++) {
                                asm volatile("ld.acquire.cta.shared.b64 %0, [%1];" : "=l"(m) : "r"(mb) : "memory");
                                if (__all_sync(0xffffffffu, (int)(m >> 32) == nr)) break;
                                spin_check(it);
                            }
                            rg = __reduce_max_sync(0xffffffffu, (uint32_t)m);
                        }
                        pos = rg ? (int)(rg >> 12) + pos - end : 0;
                        end = rg ? (rg >> 12) + (rg & 0xfff) : 1;
                        state = rg ? 2 : 3;
                    } while (pos >= end);
                    ev = end;
                }
            }
        }
        mbar_wait31(so + S_EMPTY, ph);
        TSW(8 + (h & 1));
        if (lane == 0) sts32(so + S_N, 0);
        mbar_arrive(so + S_FULL);
        if (t == 256) {
            gs->epoch[b * 32] = (tag >> 30) % 3;
            if (atomicInc(&gs->done, G - 1) == G - 1) gs->ticket = 0;
        }
        asm volatile("cp.async.wait_all;" ::: "memory");
    } else {
        asm volatile("setmaxnreg.inc.sync.aligned.u32 " STR(CREG) ";");
        const uint32_t xa = opaque(((mat >> 1) * 8 + r) * 1024 + (w >> 2) * 128 + (((2 * (w & 3) + (mat & 1)) ^ r) * 16), lane);
        const uint32_t aa = opaque(S_A + ((mat >> 1) * 8 + r) * 32 + (((mat & 1) ^ (r >> 2)) * 16), lane);
        const uint32_t ya = opaque(S_C + (mat & 1) * 80 + (mat >> 1) * 16, lane);
        const uint32_t yc = opaque(S_C + (mat < 2 ? mat * 80 + 32 : (r >> 2) == (mat & 1) && q < 3 ? (mat & 1) * 80 + q * 16 : 64), lane);
        const uint32_t na = opaque(sm + O_NODE + mat * 4, lane);
        const uint32_t pw = sm + O_P + w * PW;
        const uint32_t fx = opaque(pw + (q < 3 ? P_1P0 + 2 * q * PSBO : P_1P1 + PSBO) + (mat & 1) * 128 + (r >> 2) * PSBO, lane);
        const uint32_t fyz = opaque(pw + (q < 3 ? (mat < 2 ? P_1P1 : P_1P2) + 2 * q * PSBO : mat < 2 ? P_0P0 : P_0P1) + (mat & 1) * 128 + (r >> 2) * PSBO, lane);
        uint32_t oh[4][2];
#pragma unroll
        for (int c = 0; c < 8; c++) oh[c & 3][c >> 2] = opaque(g == c ? 0x3F803F80u : 0u, lane);
        uint32_t eb[3];
#pragma unroll
        for (int k = 0; k < 3; k++) {
            const int i = (g & 3) * 9 + (q & 1) * 6 + k;
            const uint32_t lo = __shfl_sync(0xffffffffu, epl, i), hi = __shfl_sync(0xffffffffu, epl, i + 3);
            eb[k] = (g & 3) < 3 && (q >> 1) == (g >> 2) ? (q & 1 ? lo : lo | hi << 16) : 0u;
        }
        asm volatile(".reg .pred lane0;\nsetp.eq.u32 lane0, %0, 0;" ::"r"(lane));
        uint32_t w0[16][4], w1[KR][4];
        mbar_wait(sm + O_WBD, 0);
#pragma unroll
        for (int k = 0; k < 16; k++) ldsm4t(w0[k], sm + O_W0S + (k >> 2) * 16384 + (w >> 2) * 8192 + (k & 3) * 2048 + sw);
#pragma unroll
        for (int k = 0; k < KR; k++) ldsm4t(w1[k], sm + (k < 4 ? O_W1S + (k >> 1) * 8192 : O_WR1) + (w >> 2) * 4096 + (k & 1) * 2048 + sw);
        bar_sync(7, NT);
        TS(6);
        Acc A;
#pragma unroll
        for (int i = 0; i < 4; i++) { A.p00[i] = A.p110[i] = A.p10[0][i] = A.p10[1][i] = A.p10[2][i] = 0; A.t01[i] = A.m[0][i] = A.m[1][i] = A.m[2][i] = 0.f; }
        uint32_t room = 144 - (STAG) * 16;
        uint32_t so = sm + O_RING, ph, a[4], ok, go, mt = 0;
        mbar_wait(so + S_FULL, 0);
        ldsm4(a, so + aa);
        TS(7);
        while (true) {
            {
                constexpr int F = 1, XS = XS_F;
                uint32_t yb[8], f[4][4], R[5][4], u[4][4], sd[4];
                float y[4], z[4];
                const uint32_t sof = room & 112;
                room -= 16;
                SEQ_F
            }
            if (!(go && room)) {
                const uint32_t pu = __reduce_max_sync(0xffffffffu, ph);
                if (!room || !pu) {
                    GT(0);
                    const uint32_t wg = __reduce_max_sync(0xffffffffu, w >> 2);
                    if (!FEN) asm volatile("fence.proxy.async.shared::cta;" ::: "memory");
                    mbar_wait(sm + O_WBB, 0);
                    GT(1);
                    if (ALT == 1) asm volatile("{.reg .pred p; setp.ne.u32 p, %0, 0;\n@p bar.arrive 1, 256;\n@p bar.sync 2, 256;\n@!p bar.sync 1, 256;}" ::"r"(wg ^ AWG) : "memory");
                    else bar_sync(1, 256);
                    if (FEN) asm volatile("fence.proxy.async::generic.acquire.sync_restrict::shared::cluster.cluster;" ::: "memory");
                    GT(2);
                    float d0[8], d1[24];
                    const uint64_t db = (uint64_t)((sm + O_P) >> 4) | (8ull << 16) | ((uint64_t)(PSBO / 16) << 32);
                    const uint32_t da = ((sm + O_W1) >> 4 | 1 << 16) + wg * 256;
                    asm volatile("wgmma.fence.sync.aligned;" ::: "memory");
                    if (!IL) {
#pragma unroll
                        for (int k = 0; k < 16; k++) G0(k);
                        asm volatile("wgmma.commit_group.sync.aligned;" ::: "memory");
                    }
                    const uint32_t sp = so == sm + O_RING ? sm + O_RING + (NSLOT - 1) * SLOT : so - SLOT, sr = (r & 6) + (mat & 1);
                    const uint32_t nd = (sr * 16 - 16 & 112) >= room ? lds32(sm + O_NODE + sr * 16 + (mat >> 1) * 4) : 0;
                    const uint64_t oa = madw(nd, 1024, (uint64_t)(out - 1024 + w * 32 + (r & 1) * 16));
                    const uint32_t sl = sp + ((mat >> 1) * 8 + sr) * 1024 + (w >> 2) * 128 + (((2 * (w & 3) + (r & 1)) ^ sr) * 16);
                    auto put = [&](int j) {
                        const uint4 v = lds128(sl + j * 256);
                        asm volatile("{.reg .pred p; setp.ne.u32 p, %5, 0; @p st.global.v4.u32 [%0], {%1,%2,%3,%4};}"
                                     ::"l"(oa + j * 256), "r"(v.x), "r"(v.y), "r"(v.z), "r"(v.w), "r"(nd) : "memory");
                    };
                    float gt[8];
#pragma unroll
                    static_for<25>([&](auto kc) {
                        constexpr int k = kc.value;
                        if (IL && k == 16 / (IL + !IL)) asm volatile("wgmma.commit_group.sync.aligned;" ::: "memory");
                        if (ALT == 1 && k == ASP) asm volatile("{.reg .pred p; setp.eq.u32 p, %0, 0;\n@p bar.arrive 2, 256;}" ::"r"(wg ^ AWG) : "memory");
                        if (k == GP || k == 24) asm volatile("wgmma.commit_group.sync.aligned;" ::: "memory");
                        if (k == GP) {
                            asm volatile("wgmma.wait_group.sync.aligned 1;" ::: "memory");
#pragma unroll
                            for (int i = 0; i < 8; i++) asm volatile("" : "+f"(d0[i])::"memory");
                            stsm4t(sp + xa, pack(d0[0], d0[1]), pack(d0[2], d0[3]), pack(d0[4], d0[5]), pack(d0[6], d0[7]));
                            __syncwarp();
                        }
                        if (k == min(GP + GS, 24)) put(0);
#pragma unroll
                        for (int i = 0; i < 8; i++) {
                            if (k == min(GP + i / 2 * GS, 24)) asm volatile("ex2.approx.ftz.f32 %0, %1;" : "=f"(gt[i]) : "f"(d0[i] * -1.4426950408889634f) : "memory");
                            if (k == min(GP + (i / 2 + 1) * GS, 24)) asm volatile("rcp.approx.ftz.f32 %0, %1;" : "=f"(gt[i]) : "f"(gt[i] + 1.f) : "memory");
                        }
                        if (k == min(GP + 5 * GS, 24)) {
                            uint32_t chk = -1;
#pragma unroll
                            for (int i = 0; i < 8; i++) chk &= __float_as_uint(gt[i]);
                            sts32(sm + O_TRASH, chk);
                        }
                        if (k < 24) G1(k % 24);
#pragma unroll
                        for (int i = 0; i < IL; i++) if (k * IL + i < 16) G0((k * IL + i) % 16);
                    });
                    GT(3);
                    asm volatile("wgmma.wait_group.sync.aligned 0;" ::: "memory");
                    GT(4);
#pragma unroll
                    for (int i = 0; i < 24; i++) asm volatile("" : "+f"(d1[i])::"memory");
                    if (ALT == 1) asm volatile("{.reg .pred p; setp.ne.u32 p, %0, 0;\n@p bar.sync 3, 256;}" ::"r"(wg ^ AWG) : "memory");
#pragma unroll
                    for (int j = 0; j < 3; j++) {
                        uint32_t o[4];
#pragma unroll
                        for (int i = 0; i < 4; i++) o[i] = pack(d1[8 * j + 2 * i] * gt[2 * i], d1[8 * j + 2 * i + 1] * gt[2 * i + 1]);
                        stsm4t(sp + xa + 256 + j * 256, o[0], o[1], o[2], o[3]);
                    }
                    __syncwarp();
#pragma unroll
                    for (int j = 1; j < 4; j++) put(j);
                    __syncwarp();
                    asm volatile("@lane0 mbarrier.arrive.shared::cta.b64 _, [%0];" ::"r"(sp + S_EMPTY) : "memory");
                    GT(5);
                    if (ALT == 1) asm volatile("{.reg .pred p; setp.eq.u32 p, %0, 0;\n@p bar.sync 3, 256;}" ::"r"(wg ^ AWG) : "memory");
                    else bar_sync(3, 256);
                    GT(6);
                    room = 128;
                    if (!pu) break;
                }
                if (!ok) { mbar_wait31(so + S_FULL, pu); ldsm4(a, so + aa); }
                if (!(pu & 0xfffe)) continue;
            }
            while (true) {
                do {
                    constexpr int F = 0, XS = XS_R;
                    uint32_t yb[8], f[4][4], R[5][4], u[4][4], sd[4];
                    SEQ_R
                } while (go);
                if (ok) break;
                const uint32_t pu = __reduce_max_sync(0xffffffffu, ph);
                mbar_wait31(so + S_FULL, pu); ldsm4(a, so + aa);
                if (!(pu & 0xfffe)) break;
            }
        }
        TS(10);
    }
}

typedef CUresult (*EncFn)(CUtensorMap*, CUtensorMapDataType, cuuint32_t, void*, const cuuint64_t*, const cuuint64_t*,
                          const cuuint32_t*, const cuuint32_t*, CUtensorMapInterleave, CUtensorMapSwizzle,
                          CUtensorMapL2promotion, CUtensorMapFloatOOBfill);

void make_map(EncFn fn, CUtensorMap* m, void* p, int rows, int cols, int brows, int bcols, int bblk) {
    cuuint64_t dims[3] = {64, (cuuint64_t)rows, (cuuint64_t)cols / 64}, strides[2] = {(cuuint64_t)cols * 2, 128};
    cuuint32_t box[3] = {(cuuint32_t)bcols, (cuuint32_t)brows, (cuuint32_t)bblk}, es[3] = {1, 1, 1};
    fn(m, CU_TENSOR_MAP_DATA_TYPE_BFLOAT16, 3, p, dims, strides, box, es, CU_TENSOR_MAP_INTERLEAVE_NONE,
       bcols == 64 ? CU_TENSOR_MAP_SWIZZLE_128B : CU_TENSOR_MAP_SWIZZLE_NONE, CU_TENSOR_MAP_L2_PROMOTION_L2_128B, CU_TENSOR_MAP_FLOAT_OOB_FILL_NONE);
}

}

extern "C" void kernel_launch(void* const* d_in, const int* in_sizes, int n_in, void* d_out, int out_size) {
    static EncFn enc = nullptr;
    static void* scratch = nullptr;
    if (!enc) {
        void* fn = nullptr;
        cudaDriverEntryPointQueryResult qr;
        cudaGetDriverEntryPoint("cuTensorMapEncodeTiled", &fn, cudaEnableDefault, &qr);
        enc = (EncFn)fn;
        cudaGetSymbolAddress(&scratch, g_scratch);
        cudaFuncSetAttribute(tp_kernel, cudaFuncAttributeMaxDynamicSharedMemorySize, SMEM_BYTES);
    }
    CUtensorMap m_wr, m_w0, m_w1, m_x;
    make_map(enc, &m_wr, d_in[5], 16, 640, 16, 64, 5);
    make_map(enc, &m_w0, d_in[6], 256, 128, 64, 64, 2);
    make_map(enc, &m_w1, d_in[7], 384, 128, 32, 64, 2);
    make_map(enc, &m_x, d_in[0], NN * 8, 64, NLOC * 2, 8, 1);
    tp_kernel<<<G, NT, SMEM_BYTES>>>((const int4*)d_in[4], (const int4*)d_in[3], (const char*)d_in[1], (Scratch*)scratch,
                                     (const char*)d_in[0], (const char*)d_in[2], (const __nv_bfloat16*)d_in[8], (char*)d_out,
                                     m_wr, m_w0, m_w1, m_x);
}
```

```cpp
#include <cuda_runtime.h>
#include <cuda_bf16.h>
#include <cuda.h>
#include <stdint.h>
#include <stddef.h>

namespace {

constexpr int NN = 10000;
constexpr int NE = 320000;
constexpr int G = 132;
constexpr int NT = 384;
constexpr int CH = 2432;
constexpr int NLOC = (NN + G - 1) / G;
#define NPOOL 3
constexpr int NPAIR = NLOC / 2, NPRIV = NPAIR - NPOOL;
constexpr int SEGW = 11;

#define NSLOT 6
#define PP 0xffff
#define TP 0x9375
#define STAG (b & 7)
#define ASC (b & 1)
#define THETA (5 * G / 3)
#define THETB G
#define QOK (STAG)
#define QJ 3
#define WP 0x2222255
#define KR 6
#define WLD(p) { _Pragma("unroll") for (int j = 0; j < 4 + KR / 2; j++) if ((WP >> 4 * j & 15) == p) \
    tma3d(sm + (j < 4 ? O_W0S + j * 16384 : j < 6 ? O_W1S + (j - 4) * 8192 : O_WR1), j < 4 ? &m_w0 : &m_w1, j < 4 ? j * 64 : (j - 4) * 32, 0, sm + O_WBD); \
    _Pragma("unroll") for (int j = 0; j < 4; j++) { const int r0 = (b * 4 + j) * (NLOC / 4); \
        if ((PP >> 4 * j & 15) == p) pf_l2(x + r0 * 1024, min(NLOC / 4, NN - r0) * 1024); \
        if ((TP >> 4 * j & 15) == p) tma3d(sm + O_WR1 + 10240, &m_x, r0 * 8, 0, sm + O_WBE); } }
#define ALT 1
#define AWG 0
#define IL 1
#define RSL 1
#define FEN 1
#define HS 4
#define HL 0
#define B4 1
#define NB1 (12 - KR / 2)
#define GD 1
#define GM 0
#define GP 24
#define GS 2
#define ASP 20
#define INV 0
#define NULLP(v) v
#define CREG 224
#define PREG 56
#define STR2(x) #x
#define STR(x) STR2(x)

constexpr int S_A = 16384, S_C = S_A + 512, S_FULL = S_C + 144, S_EMPTY = S_FULL + 8, S_N = S_C + 160, SLOT = S_C + 256;

constexpr int PSBO = 272;
constexpr int PB1 = 5 * PSBO + 256, PB0 = PSBO + 256;
constexpr int P_1P0 = 0, P_1P1 = PB1, P_0P1 = 2 * PB1, P_0P0 = P_0P1 + PB0, P_1P2 = P_0P0 + PB0;
constexpr int PW = P_1P2 + PB1;

constexpr int up1k(int a) { return (a + 1023) / 1024 * 1024; }
constexpr int O_W1 = 0;
constexpr int O_P = 81920;
constexpr int O_RING = O_P + 8 * PW;
constexpr int O_WBA = O_RING + 6 * SLOT, O_WBB = O_WBA + 8, O_WBC = O_WBA + 16, O_WBD = O_WBA + 24, O_WBE = O_WBA + 32, O_TRASH = O_WBA + 40, O_NODE = O_WBA + 48;
constexpr int O_SUM = O_NODE + 128, O_MB = O_SUM + 16;
constexpr int SMEM_BYTES = O_MB + 128;
constexpr int CAPT = 192;
constexpr int O_L = 0, LZ = CAPT * 256 / (NT * 16), O_W0S = O_L + CAPT * 256, O_OUT = O_W0S + 65536, O_SRC = O_OUT + CH * 8;
constexpr int O_KT = O_RING + SLOT, O_RH = O_RING + 2 * SLOT;
constexpr int O_WR0 = up1k(O_RING + 3 * SLOT), O_WR1 = up1k(O_RING + 4 * SLOT), O_W1S = up1k(O_RING + 5 * SLOT);
constexpr int O_BCNT = O_WR0 + 10240, O_NCUR = O_BCNT + 640, O_NCNT = O_NCUR + 320;
constexpr int O_BOFF = O_NCNT + 512, O_SORT = O_BOFF + 640, O_NOFF = O_SORT + 320;
constexpr int TBIG = G * CAPT + 8, NTILE = TBIG + NE / 8 + G * (NLOC + 5);
static_assert(SMEM_BYTES <= 232448 && CAPT % 16 == 0 && NTILE < (1 << 18), "smem");
static_assert(LZ * NT * 16 == CAPT * 256 && O_W0S % 1024 == 0 && O_OUT <= O_RING && O_SRC + CH * 4 <= O_RING + S_C && G * 128 <= S_C, "staging");
static_assert(O_NOFF + 1024 <= O_RING + 3 * SLOT + S_C && O_W1S + 16384 <= O_RING + 5 * SLOT + S_C, "staging");
static_assert(O_RING % 128 == 0 && SLOT % 128 == 0 && O_W0S <= O_P && O_NOFF % 8 == 0, "layout");
static_assert(G * CH >= NE && NE % 8 == 0 && CH < 4096 && CH / 8 <= 320 && NE < (1 << 21), "chunks");
static_assert(SEGW * (NT / 32) == G && G <= 160 && G % 4 == 0, "segments");
static_assert(NLOC % 4 == 0 && NLOC < 80 && NLOC * 4 <= 320 && NN < 0x3fff && NE / 8 < 0xbfff && NPRIV >= 30, "scan width");

struct __align__(128) Scratch {
    uint32_t keys[G * G * 32];
    uint64_t vals[G * CH];
    uint32_t more[G * CH];
    uint32_t epoch[G * 32];
    uint32_t info[(G * NPOOL + 127) / 128 * 128];
    unsigned done, pad0[31], ticket, pad1[31];
    uint4 list[NTILE * 16];
};
static_assert(offsetof(Scratch, list) % 128 == 0, "list");
__device__ Scratch g_scratch;
#define GT(i)
#define TS(i)
#define TSW(i)
#define TV(i, v)

constexpr int SPIN_LIMIT = 1 << 24;

__device__ __forceinline__ void mbar_init(uint32_t a, int c) { asm volatile("mbarrier.init.shared::cta.b64 [%0], %1;" ::"r"(a), "r"(c) : "memory"); }
__device__ __forceinline__ void mbar_expect(uint32_t a, int b) { asm volatile("mbarrier.arrive.expect_tx.shared::cta.b64 _, [%0], %1;" ::"r"(a), "r"(b) : "memory"); }
__device__ __forceinline__ void mbar_arrive(uint32_t a) { asm volatile("mbarrier.arrive.shared::cta.b64 _, [%0];" ::"r"(a) : "memory"); }
__device__ __forceinline__ void mbar_wait(uint32_t a, uint32_t ph) {
    asm volatile("{\n.reg .pred p, q;\n.reg .u32 it;\n"
                 "mbarrier.try_wait.parity.shared::cta.b64 p, [%0], %1;\n"
                 "@p bra DONE;\n"
                 "mov.u32 it, 0;\n"
                 "LOOP:\n"
                 "mbarrier.try_wait.parity.shared::cta.b64 p, [%0], %1;\n"
                 "@p bra DONE;\n"
                 "add.u32 it, it, 1;\n"
                 "setp.gt.u32 q, it, %2;\n"
                 "@q trap;\n"
                 "bra LOOP;\n"
                 "DONE:\n}" ::"r"(a), "r"(ph), "n"(SPIN_LIMIT) : "memory");
}
__device__ __forceinline__ void mbar_wait31(uint32_t a, uint32_t ph) {
    asm volatile("{\n.reg .pred p, q;\n.reg .u32 it;\n.reg .b64 s;\n"
                 "mov.b64 s, {0, %1};\n"
                 "mbarrier.try_wait.shared::cta.b64 p, [%0], s;\n"
                 "@p bra DONE;\n"
                 "mov.u32 it, 0;\n"
                 "LOOP:\n"
                 "mbarrier.try_wait.shared::cta.b64 p, [%0], s;\n"
                 "@p bra DONE;\n"
                 "add.u32 it, it, 1;\n"
                 "setp.gt.u32 q, it, %2;\n"
                 "@q trap;\n"
                 "bra LOOP;\n"
                 "DONE:\n}" ::"r"(a), "r"(ph), "n"(SPIN_LIMIT) : "memory");
}
__device__ __forceinline__ void spin_check(int it) {
    asm volatile("{\n.reg .pred q;\nsetp.gt.s32 q, %0, %1;\n@q trap;\n}" ::"r"(it), "n"(SPIN_LIMIT));
}
__device__ __forceinline__ void ldsm4(uint32_t* r, uint32_t a) { asm volatile("ldmatrix.sync.aligned.m8n8.x4.shared.b16 {%0,%1,%2,%3}, [%4];" : "=r"(r[0]), "=r"(r[1]), "=r"(r[2]), "=r"(r[3]) : "r"(a) : "memory"); }
__device__ __forceinline__ void ldsm4t(uint32_t* r, uint32_t a) { asm volatile("ldmatrix.sync.aligned.m8n8.x4.trans.shared.b16 {%0,%1,%2,%3}, [%4];" : "=r"(r[0]), "=r"(r[1]), "=r"(r[2]), "=r"(r[3]) : "r"(a) : "memory"); }
__device__ __forceinline__ void stsm4t(uint32_t a, uint32_t r0, uint32_t r1, uint32_t r2, uint32_t r3) { asm volatile("stmatrix.sync.aligned.m8n8.x4.trans.shared.b16 [%0], {%1,%2,%3,%4};" ::"r"(a), "r"(r0), "r"(r1), "r"(r2), "r"(r3) : "memory"); }
__device__ __forceinline__ void stsm2t(uint32_t a, uint32_t r0, uint32_t r1) { asm volatile("stmatrix.sync.aligned.m8n8.x2.trans.shared.b16 [%0], {%1,%2};" ::"r"(a), "r"(r0), "r"(r1) : "memory"); }
__device__ __forceinline__ void mma16(float* d, const uint32_t* a, uint32_t b0, uint32_t b1) {
    asm("mma.sync.aligned.m16n8k16.row.col.f32.bf16.bf16.f32 {%0,%1,%2,%3}, {%4,%5,%6,%7}, {%8,%9}, {%0,%1,%2,%3};"
        : "+f"(d[0]), "+f"(d[1]), "+f"(d[2]), "+f"(d[3]) : "r"(a[0]), "r"(a[1]), "r"(a[2]), "r"(a[3]), "r"(b0), "r"(b1));
}
__device__ __forceinline__ void mma8(float* d, uint32_t a0, uint32_t a1, uint32_t b0) {
    asm("mma.sync.aligned.m16n8k8.row.col.f32.bf16.bf16.f32 {%0,%1,%2,%3}, {%4,%5}, {%6}, {%0,%1,%2,%3};"
        : "+f"(d[0]), "+f"(d[1]), "+f"(d[2]), "+f"(d[3]) : "r"(a0), "r"(a1), "r"(b0));
}
__device__ __forceinline__ void mma16z(float* d, const uint32_t* a, uint32_t b0, uint32_t b1) {
    asm("mma.sync.aligned.m16n8k16.row.col.f32.bf16.bf16.f32 {%0,%1,%2,%3}, {%4,%5,%6,%7}, {%8,%9}, {%10,%10,%10,%10};"
        : "=f"(d[0]), "=f"(d[1]), "=f"(d[2]), "=f"(d[3]) : "r"(a[0]), "r"(a[1]), "r"(a[2]), "r"(a[3]), "r"(b0), "r"(b1), "f"(0.f));
}
__device__ __forceinline__ uint32_t pack(float lo, float hi) { uint32_t r; asm("cvt.rn.bf16x2.f32 %0, %1, %2;" : "=r"(r) : "f"(hi), "f"(lo)); return r; }
__device__ __forceinline__ uint32_t hmul(uint32_t a, uint32_t b) { uint32_t r; asm("mul.rn.bf16x2 %0, %1, %2;" : "=r"(r) : "r"(a), "r"(b)); return r; }
__device__ __forceinline__ uint32_t hfma(uint32_t a, uint32_t b, uint32_t c) { uint32_t r; asm("fma.rn.bf16x2 %0, %1, %2, %3;" : "=r"(r) : "r"(a), "r"(b), "r"(c)); return r; }
__device__ __forceinline__ uint4 lds128(uint32_t a) { uint4 v; asm volatile("ld.shared.v4.u32 {%0,%1,%2,%3}, [%4];" : "=r"(v.x), "=r"(v.y), "=r"(v.z), "=r"(v.w) : "r"(a) : "memory"); return v; }
__device__ __forceinline__ void sts128(uint32_t a, uint4 v) { asm volatile("st.shared.v4.u32 [%0], {%1,%2,%3,%4};" ::"r"(a), "r"(v.x), "r"(v.y), "r"(v.z), "r"(v.w) : "memory"); }
__device__ __forceinline__ int lds32(uint32_t a) { int v; asm volatile("ld.shared.u32 %0, [%1];" : "=r"(v) : "r"(a) : "memory"); return v; }
__device__ __forceinline__ void sts32(uint32_t a, int v) { asm volatile("st.shared.u32 [%0], %1;" ::"r"(a), "r"(v) : "memory"); }
__device__ __forceinline__ int atoms_add(uint32_t a, int v) { int r; asm volatile("atom.shared.add.u32 %0, [%1], %2;" : "=r"(r) : "r"(a), "r"(v) : "memory"); return r; }
__device__ __forceinline__ uint32_t ld_rlx(const void* p) { uint32_t v; asm volatile("ld.relaxed.gpu.global.u32 %0, [%1];" : "=r"(v) : "l"(p) : "memory"); return v; }
__device__ __forceinline__ void st_rlx(void* p, uint32_t v) { asm volatile("st.relaxed.gpu.global.u32 [%0], %1;" ::"l"(p), "r"(v) : "memory"); }
__device__ __forceinline__ void bulk(uint32_t dst, const void* g, int n, uint32_t bar) {
    asm volatile("cp.async.bulk.shared::cluster.global.mbarrier::complete_tx::bytes [%0], [%1], %2, [%3];" ::"r"(dst), "l"(g), "r"(n), "r"(bar) : "memory");
}
__device__ __forceinline__ void bulk_st(void* g, uint32_t src, int n) {
    asm volatile("cp.async.bulk.global.shared::cta.bulk_group [%0], [%1], %2;\ncp.async.bulk.commit_group;" ::"l"(g), "r"(src), "r"(n) : "memory");
}
__device__ __forceinline__ uint2 lds64(uint32_t a) { uint2 v; asm volatile("ld.shared.v2.u32 {%0,%1}, [%2];" : "=r"(v.x), "=r"(v.y) : "r"(a) : "memory"); return v; }
__device__ __forceinline__ void sts64(uint32_t a, uint32_t x, uint32_t y) { asm volatile("st.shared.v2.u32 [%0], {%1,%2};" ::"r"(a), "r"(x), "r"(y) : "memory"); }
__device__ __forceinline__ void tma3d(uint32_t dst, const CUtensorMap* m, int c1, int c2, uint32_t bar) {
    asm volatile("cp.async.bulk.tensor.3d.shared::cluster.global.mbarrier::complete_tx::bytes [%0], [%1, {0, %3, %4}], [%2];"
                 ::"r"(dst), "l"(m), "r"(bar), "r"(c1), "r"(c2) : "memory");
}
__device__ __forceinline__ void pf_l2(const void* g, int n) {
    asm volatile("{.reg .pred p; setp.gt.s32 p, %1, 0; @p cp.async.bulk.prefetch.L2.global [%0], %1;}" ::"l"(g), "r"(n) : "memory");
}
__device__ __forceinline__ void fence_async() { asm volatile("fence.proxy.async.shared::cta;" ::: "memory"); }
__device__ __forceinline__ uint64_t madw(uint32_t a, uint32_t b, uint64_t c) { uint64_t r; asm("mad.wide.u32 %0, %1, %2, %3;" : "=l"(r) : "r"(a), "r"(b), "l"(c)); return r; }
__device__ __forceinline__ uint32_t lop_sel(uint32_t a, uint32_t b, uint32_t m) { uint32_t r; asm("lop3.b32 %0, %1, %2, %3, 0xd8;" : "=r"(r) : "r"(a), "r"(b), "r"(m)); return r; }
__device__ __forceinline__ uint32_t opaque(uint32_t v, int lane) { return __shfl_sync(0xffffffffu, v, lane); }
__device__ __forceinline__ void bar_sync(int id, int n) { asm volatile("bar.sync %0, %1;" ::"r"(id), "r"(n) : "memory"); }

__device__ __forceinline__ void wg_rs16(float* d, const uint32_t* a, uint64_t db, int sc) {
    asm volatile("{.reg .pred p; setp.ne.b32 p, %13, 0;\n"
                 "wgmma.mma_async.sync.aligned.m64n16k16.f32.bf16.bf16 {%0,%1,%2,%3,%4,%5,%6,%7}, {%8,%9,%10,%11}, %12, p, 1, 1, 0;}"
                 : "+f"(d[0]), "+f"(d[1]), "+f"(d[2]), "+f"(d[3]), "+f"(d[4]), "+f"(d[5]), "+f"(d[6]), "+f"(d[7])
                 : "r"(a[0]), "r"(a[1]), "r"(a[2]), "r"(a[3]), "l"(db), "r"(sc));
}
__device__ __forceinline__ void wg_rs48(float* d, const uint32_t* a, uint64_t db, int sc) {
    asm volatile("{.reg .pred p; setp.ne.b32 p, %29, 0;\n"
                 "wgmma.mma_async.sync.aligned.m64n48k16.f32.bf16.bf16 {%0,%1,%2,%3,%4,%5,%6,%7,%8,%9,%10,%11,%12,%13,%14,%15,%16,%17,%18,%19,%20,%21,%22,%23}, {%24,%25,%26,%27}, %28, p, 1, 1, 0;}"
                 : "+f"(d[0]), "+f"(d[1]), "+f"(d[2]), "+f"(d[3]), "+f"(d[4]), "+f"(d[5]), "+f"(d[6]), "+f"(d[7]),
                   "+f"(d[8]), "+f"(d[9]), "+f"(d[10]), "+f"(d[11]), "+f"(d[12]), "+f"(d[13]), "+f"(d[14]), "+f"(d[15]),
                   "+f"(d[16]), "+f"(d[17]), "+f"(d[18]), "+f"(d[19]), "+f"(d[20]), "+f"(d[21]), "+f"(d[22]), "+f"(d[23])
                 : "r"(a[0]), "r"(a[1]), "r"(a[2]), "r"(a[3]), "l"(db), "r"(sc));
}
__device__ __forceinline__ void wg_ss48(float* d, uint64_t da, uint64_t db, int sc) {
    asm volatile("{.reg .pred p; setp.ne.b32 p, %26, 0;\n"
                 "wgmma.mma_async.sync.aligned.m64n48k16.f32.bf16.bf16 {%0,%1,%2,%3,%4,%5,%6,%7,%8,%9,%10,%11,%12,%13,%14,%15,%16,%17,%18,%19,%20,%21,%22,%23}, %24, %25, p, 1, 1, 1, 0;}"
                 : "+f"(d[0]), "+f"(d[1]), "+f"(d[2]), "+f"(d[3]), "+f"(d[4]), "+f"(d[5]), "+f"(d[6]), "+f"(d[7]),
                   "+f"(d[8]), "+f"(d[9]), "+f"(d[10]), "+f"(d[11]), "+f"(d[12]), "+f"(d[13]), "+f"(d[14]), "+f"(d[15]),
                   "+f"(d[16]), "+f"(d[17]), "+f"(d[18]), "+f"(d[19]), "+f"(d[20]), "+f"(d[21]), "+f"(d[22]), "+f"(d[23])
                 : "l"(da), "l"(db), "r"(sc));
}

__device__ __forceinline__ int warp_incl(int v) {
#pragma unroll
    for (int o = 1; o < 32; o <<= 1)
        asm volatile("{.reg .pred p; .reg .b32 u; shfl.sync.up.b32 u|p, %0, %1, 0, 0xffffffff; @p add.s32 %0, %0, u;}" : "+r"(v) : "r"(o));
    return v;
}
__device__ __forceinline__ void ldg128(uint32_t* r, const void* p, bool on) {
    asm volatile("{.reg .pred p; setp.ne.u32 p, %5, 0; @p ld.global.nc.v4.u32 {%0,%1,%2,%3}, [%4];}"
                 : "=r"(r[0]), "=r"(r[1]), "=r"(r[2]), "=r"(r[3]) : "l"(p), "r"((uint32_t)on));
}

template <int V> struct IC { static constexpr int value = V; };
template <int N, int I = 0, class Fn> __device__ __forceinline__ void static_for(Fn f) { if constexpr (I < N) { f(IC<I>{}); static_for<N, I + 1>(f); } }

struct Acc {
    uint32_t p00[4], p110[4], p10[3][4];
    float t01[4], m[3][4];
};

#define LF(m) ldsm4t(f[m], so + xa + m * 256)
#define LY() ldsm4(yb, so + ya)
#define LC() ldsm4(yb + 4, so + yc)
#define LN() ph = lds32(so + S_N)
#define ADV() { if (F && ALT) asm volatile("{.reg .pred p; setp.ne.and.u32 p, %1, 0, lane0; @p mbarrier.arrive.shared::cta.b64 _, [%0];}" ::"r"(so + S_EMPTY), "r"(room) : "memory"); \
                else asm volatile("@lane0 mbarrier.arrive.shared::cta.b64 _, [%0];" ::"r"(so + S_EMPTY) : "memory"); \
                so = so == sm + O_RING + (NSLOT - 1) * SLOT ? sm + O_RING : so + SLOT; }
#define LA() asm volatile("{\n.reg .pred p, q;\n.reg .b64 s;\n.reg .f32 n;\nmov.b64 s, {0, %7};\nmbarrier.test_wait.shared::cta.b64 p, [%6], s;\n" \
                          "abs.f32 n, %7;\nsetp.gt.and.f32 q, n, 0f00000001, p;\nselp.u32 %4, 1, 0, p;\nselp.u32 %5, 1, 0, q;\n" \
                          "@p ldmatrix.sync.aligned.m8n8.x4.shared.b16 {%0,%1,%2,%3}, [%8];\n}" \
                          : "+r"(a[0]), "+r"(a[1]), "+r"(a[2]), "+r"(a[3]), "=r"(ok), "=r"(go) : "r"(so + S_FULL), "r"(ph), "r"(so + aa) : "memory")
#define RAD(p, s) { float c[4]; mma16z(c, wr[p], a[2 * s], a[2 * s + 1]); R[p][2 * s] = pack(c[0], c[1]); R[p][2 * s + 1] = pack(c[2], c[3]); }
#define MUL(n, x, y) (XS >> n & 1 ? hmul(y, x) : hmul(x, y))
#define FMA(n, x, y, z) (XS >> n & 1 ? hfma(y, x, z) : hfma(x, y, z))
#define ACC(n, x, y, z) z = F ? MUL(n, x, y) : FMA(n, x, y, z)
#define P00(i) ACC(0, f[0][i], R[0][i], A.p00[i ^ XA])
#define P10(k, i) ACC(1, f[1 + k][i], R[3][i], A.p10[k][i ^ XA])
#define S0(k, i) sd[i] = MUL(2, f[1 + k][i], yb[2 * k + (i >> 1)])
#define SD(k, i) sd[i] = FMA(2, f[1 + k][i], yb[2 * k + (i >> 1)], sd[i])
#define P110(i) ACC(3, sd[i], R[1][i], A.p110[i ^ XA])
#define TU(i) u[3][i ^ XU] = MUL(4, f[0][i], R[2][i])
#define TM() if (F) mma16z(A.t01, u[3], yb[6], yb[7]); else mma16(A.t01, u[3], yb[6], yb[7])
#define MU(k, i) u[k][i ^ XU] = MUL(5, f[1 + k][i], R[4][i])
#define MM(k) if (F) mma16z(A.m[k], u[k], yb[6], yb[7]); else mma16(A.m[k], u[k], yb[6], yb[7])
#define PK(v, h) pack(v[2 * (h)], v[2 * (h) + 1])
#define LM() { sts32(na + sof, mt); asm volatile("ld.shared.u16 %0, [%1];" : "=r"(mt) : "r"(so + ya + 48) : "memory"); }
#define FY(k) if (k == 0) mma16z(y, A.p10[0], oh[0][0], oh[0][1]); else mma16(y, k < 3 ? A.p10[k % 3] : A.p00, oh[k][0], oh[k][1])
#define FZ(k) if (k == 0) mma16z(z, A.p110, oh[3][0], oh[3][1]); \
              else if (k == 1) { const uint32_t mp[4] = {PK(A.m[0], XA ^ XU), PK(A.m[0], 1 ^ XA ^ XU), PK(A.m[1], XA ^ XU), PK(A.m[1], 1 ^ XA ^ XU)}; mma16(z, mp, eb[0], eb[1]); } \
              else mma8(z, PK(A.m[2], XA ^ XU), PK(A.m[2], 1 ^ XA ^ XU), eb[2])
#define SX() stsm2t(fx + sof, PK(A.t01, XU), PK(A.t01, 1 ^ XU))
#define SY() stsm4t(fyz + sof, PK(y, XA), PK(y, 1 ^ XA), PK(z, XA), PK(z, 1 ^ XA))
#define G0(k) wg_rs16(d0, w0[k], db + ((((k) & 7) * PW + (((k) >> 3) ? P_0P1 : P_0P0)) >> 4), k)
#define G1(i) { constexpr int k_ = RSL ? ((i) + KR) % 24 : (i); const uint64_t bk = db + (((k_ & 7) * PW + ((k_ >> 3) == 0 ? P_1P0 : (k_ >> 3) == 1 ? P_1P1 : P_1P2)) >> 4); \
                if (k_ < KR) wg_rs48(d1, w1[k_ % KR], bk, i); else wg_ss48(d1, (da + (k_ - KR) / 2 * 512 + (k_ & 1) * 128) | (64ull << 32) | (1ull << 62), bk, i); }
#define X4(op) op(0); op(1); op(2); op(3)
#define Y4(op, k) op(k, 0); op(k, 1); op(k, 2); op(k, 3)
#define XA 1
#define XU 0
#define XS_R 63
#define SEQ_R LF(2); LN(); RAD(1,0); RAD(1,1); LC(); LY(); RAD(2,0); RAD(2,1); RAD(4,0); RAD(4,1); RAD(3,0); RAD(3,1); LF(3); LF(0); P10(1,1); \
    P10(1,0); P10(1,3); P10(1,2); S0(2,3); S0(2,2); S0(2,1); S0(2,0); RAD(0,1); RAD(0,0); P00(2); MU(2,0); MU(2,2); MU(2,1); MU(2,3); MM(2); MU(1,3); \
    P00(3); MU(1,2); LF(1); ADV(); LA(); P10(0,0); P10(0,1); P10(0,2); P10(0,3); SD(0,0); SD(0,2); SD(0,1); SD(0,3); SD(1,0); P110(0); SD(1,2); \
    P110(2); SD(1,1); P110(1); SD(1,3); P110(3); P00(0); MU(0,0); TU(0); TU(2); MU(1,1); TU(3); TU(1); TM(); P00(1); MU(0,2); MU(1,0); MM(1); MU(0,1); \
    MU(0,3); MM(0); P10(2,0); P10(2,2); P10(2,3); P10(2,1);
#define XS_F 0
#define SEQ_F LN(); LF(2); LY(); LF(1); LM(); RAD(2,0); RAD(2,1); LF(3); RAD(0,1); RAD(3,0); RAD(0,0); LC(); RAD(3,1); RAD(1,0); FZ(0); LF(0); \
    RAD(4,0); FY(0); FY(1); FZ(1); RAD(4,1); TU(0); MU(1,1); MU(1,0); MU(1,3); MU(1,2); TU(2); SX(); TU(1); TU(3); TM(); RAD(1,1); MM(1); ADV(); LA(); \
    FZ(2); P10(1,1); FY(3); P10(1,0); P10(1,3); S0(2,0); SD(0,0); SD(1,0); P10(1,2); P110(0); S0(2,2); SD(0,2); SD(1,2); P110(2); MU(2,1); MU(2,0); \
    MU(2,3); MU(2,2); MM(2); S0(2,3); SD(0,3); SD(1,3); P110(3); P00(0); MU(0,0); FY(2); SY(); P10(2,2); P10(2,3); P10(2,0); P10(2,1); S0(2,1); \
    SD(0,1); SD(1,1); P110(1); P00(1); MU(0,1); P00(2); MU(0,2); P10(0,3); P10(0,2); P10(0,1); P10(0,0); P00(3); MU(0,3); MM(0);

__global__ void __launch_bounds__(NT, 1)
tp_kernel(const int4* __restrict__ dst, const int4* __restrict__ src, const char* __restrict__ rhat, Scratch* __restrict__ gs,
          const char* __restrict__ x, const char* __restrict__ ea, const __nv_bfloat16* __restrict__ eps, char* __restrict__ out,
          const __grid_constant__ CUtensorMap m_wr, const __grid_constant__ CUtensorMap m_w0, const __grid_constant__ CUtensorMap m_w1,
          const __grid_constant__ CUtensorMap m_x) {
    extern __shared__ __align__(1024) char smem_raw[];
    constexpr uint32_t sm = 1024;
    spin_check((uint32_t)__cvta_generic_to_shared(smem_raw) == sm ? 0 : 2 * SPIN_LIMIT);
    int t;
    asm volatile("mov.u32 %0, %%tid.x;" : "=r"(t));
    const int w = t >> 5, lane = t & 31, b = blockIdx.x;

    const int g = lane >> 2, q = lane & 3, mat = lane >> 3, r = lane & 7;
    const int e0 = b * CH + t * 8, ne = min(CH, NE - b * CH);
    const bool act = t * 8 < ne;
    uint32_t d[8];
#pragma unroll
    for (int k = 0; k < 2; k++) ldg128(d + 4 * k, dst + e0 / 4 + k, act);
    uint32_t tag = ld_rlx(&gs->epoch[b * 32]), epl;
    asm volatile("ld.global.nc.u16 %0, [%1];" : "=r"(epl) : "l"(eps + min(lane, 26)));
    if (t < 60) sts128(sm + O_BCNT + 16 * t, make_uint4(0, 0, 0, 0));
    if (t == NT - 1) {
#pragma unroll
        for (int i = 0; i < 5; i++) mbar_init(sm + O_WBA + 8 * i, 1);
        fence_async();
        mbar_expect(sm + O_WBC, ne * 10); mbar_expect(sm + O_WBA, 20480); mbar_expect(sm + O_WBB, NB1 * 8192); mbar_expect(sm + O_WBD, 65536 + KR * 4096);
        mbar_expect(sm + O_WBE, (((TP & 15) != 15) + ((TP >> 4 & 15) != 15) + ((TP >> 8 & 15) != 15) + ((TP >> 12) != 15)) * (NLOC / 4 * 128));
        WLD(6);
        spin_check(tag);
        bulk(sm + O_RH, rhat + b * (CH * 6), ne * 6, sm + O_WBC);
        bulk(sm + O_SRC, src + b * (CH / 4), ne * 4, sm + O_WBC);
        tma3d(sm + O_WR0, &m_wr, 0, 0, sm + O_WBA);
        tma3d(sm + O_WR1, &m_wr, 0, 5, sm + O_WBA);
        WLD(0);
    }
    if (t == 320) {
#pragma unroll
        for (int i = 0; i < NSLOT; i++) {
            sts128(sm + O_RING + i * SLOT + S_C + 64, make_uint4(0, 0, 0, 0));
            mbar_init(sm + O_RING + i * SLOT + S_FULL, 32); mbar_init(sm + O_RING + i * SLOT + S_EMPTY, 8);
        }
    }
#pragma unroll
    for (int k = 0; k < LZ; k++) sts128(sm + O_L + 16 * (t + k * NT), make_uint4(0, 0, 0, 0));
    if (t < 80) sts32(sm + O_NCNT + 4 * t, t <= NLOC ? 4 * t : 0);
    if (t < 68) sts32(sm + O_NODE + 4 * t, 0);
    uint32_t ba[8], rk[8];
    if (w < 10) bar_sync(1, 320);
    tag = (tag + 1) << 30;
    if (act) {
#pragma unroll
        for (int i = 0; i < 8; i++) {
            const uint32_t l = __umulhi(d[i], (uint32_t)((1ull << 32) / G + 1));
            ba[i] = d[i] * 4 - l * (4 * G);
            d[i] = l * 4 + (tag + ((e0 + i + 1) << 9) + 4);
            rk[i] = atoms_add(sm + O_BCNT + ba[i], 4);
        }
#pragma unroll
        for (int i = 0; i < 8; i++)
            asm volatile("{.reg .pred p; setp.lt.u32 p, %2, 124; @p st.shared.u32 [%0], %1;}"
                         ::"r"(sm + O_KT + ba[i] * 32 + ((ba[i] + rk[i]) & 127)), "r"(d[i]), "r"(rk[i]) : "memory");
    }
    TS(0);
    __syncthreads();
    {
        int v[5], sum = 0;
#pragma unroll
        for (int i = 0; i < 5; i++) { v[i] = lds32(sm + O_BCNT + 4 * (lane * 5 + i)); sum += v[i]; }
        int e = warp_incl(sum) - sum;
        if (w == 10) {
#pragma unroll
            for (int i = 0; i < 5; i++) {
                const int k = lane * 5 + i;
                if (k < G) sts32(sm + O_KT + k * 128 + ((k * 4 + 124) & 127), tag | v[i] << 10 | e >> 2);
                e += v[i];
            }
            __syncwarp();
            if (lane == 0) {
                fence_async();
                bulk_st(&gs->keys[b * (G * 32)], sm + O_KT, G * 128);
                WLD(5);
            }
        } else {
#pragma unroll
            for (int i = 0; i < 5; i++) { sts32(sm + O_BOFF + 4 * (lane * 5 + i), e); e += v[i]; }
        }
        __syncwarp();
    }
    TS(11);
    const uint32_t sw = (uint32_t)(((2 * (w & 3) + (mat & 1)) ^ r) * 16 + ((mat >> 1) * 8 + r) * 128);
    uint32_t wr[5][4];
    const uint32_t* kp = &gs->keys[(w * SEGW * G + b) * 32 + ((lane + b) & 31)];
    uint32_t kv[SEGW + 1], ho[SEGW + 1], nk[SEGW + 1], old;
    if (act) {
        uint32_t mx = 0;
#pragma unroll
        for (int i = 0; i < 8; i++) { mx = max(mx, rk[i]); ba[i] = rk[i] + lds32(sm + O_BOFF + ba[i]); }
        if (mx >= 124) {
#pragma unroll
            for (int i = 0; i < 8; i++)
                if (rk[i] >= 124) st_rlx(&gs->more[b * CH + (ba[i] >> 2)], d[i]);
        }
    }
#define WRP 0
    auto ldwr = [&]() {
    if (w < 8) {
        mbar_wait(sm + O_WBA, 0);
#pragma unroll
        for (int p = 0; p < 5; p++) {
            const int c = 2 * p + (w >> 2);
            ldsm4t(wr[p], sm + (c < 5 ? O_WR0 : O_WR1 - 5 * 2048) + c * 2048 + sw);
        }
    } else {
        const uint64_t xl = (uint64_t)(x - 1024 + r * 16) - (tag >> 6), al = (uint64_t)(ea - 32 + (lane & 1) * 16) - (tag >> 4);
        const uint64_t ml = (uint64_t)gs->list + lane * 8;
        const uint32_t row = 0x76b821a3u >> 4 * r & 15, row0 = 0xc5bfe0cbu >> 4 * r & 15;
        const uint32_t c[13] = {(uint32_t)xl, (uint32_t)(xl >> 32), (uint32_t)al, (uint32_t)(al >> 32), (uint32_t)ml, (uint32_t)(ml >> 32),
            mat * 2048u + (r ^ 2 * mat) * 16, mat * 2048u + 1024 + (r ^ 2 * mat ^ 1) * 16,
            S_A + (lane & 2) * 128u + g * 32 + ((lane ^ lane >> 4) & 1) * 16, S_C + (mat & 1 ? row : row0) * 16, lane & 1 ? 16u : 9u, lane & 30u,
            lane == 4 ? 0xffff0000u : 0u};
#pragma unroll
        for (int i = 0; i < 20; i++) wr[i >> 2][i & 3] = i < 13 ? opaque(c[i % 13], lane) : 0;
    }
    };
    if (!WRP) ldwr();
    TS(21);
    mbar_wait(sm + O_WBC, 0);
    TS(22);
    if (act) {
        uint32_t s[8], y[12];
#pragma unroll
        for (int k = 0; k < 3; k++) *(uint4*)&y[4 * k] = lds128(sm + O_RH + t * 48 + k * 16);
#pragma unroll
        for (int k = 0; k < 2; k++) *(uint4*)&s[4 * k] = lds128(sm + O_SRC + t * 32 + k * 16);
#pragma unroll
        for (int i = 0; i < 8; i++) {
            const int k = 3 * i / 2;
            sts64(sm + O_OUT + ba[i] * 2, __byte_perm(y[k], s[i] + (tag >> 16) + 1, i & 1 ? 0x5432 : 0x5410),
                  i & 1 ? y[k + 1] : __byte_perm(y[k], y[k + 1], 0x5432));
        }
    }
    TS(12);
    __syncthreads();
    if (t == 352) { fence_async(); bulk_st(&gs->vals[b * CH], sm + O_OUT, ne * 8); WLD(7); }
    if (WRP) ldwr();

    const uint32_t am = lane < 31 ? 511 : 0, none = tag | (320 + 4 * lane);
    auto check = [&]() {
        old = 0;
#pragma unroll
        for (int j = 0; j < SEGW; j++) {
            ho[j] = __shfl_sync(0xffffffffu, kv[j], 31);
            kv[j] = ho[j] >= (lane < 31 ? tag + ((lane + 1) << 12) : 0u) ? kv[j] : none;
            old |= kv[j] ^ tag;
        }
        return __any_sync(0xffffffffu, old >> 30);
    };
#pragma unroll
    for (int j = 0; j < SEGW; j++) kv[j] = ld_rlx(kp + j * (G * 32));
    TS(1);
    if (t == 352) WLD(1);
    TV(19, 0); TV(23, 0);
    for (int it = 0; check(); it++) {
        spin_check(it);
        if (it == 0) TS(20);
        TV(19, (it + 1) * 100);
#pragma unroll
        for (int j = 0; j < SEGW; j++)
            if (__any_sync(0xffffffffu, (kv[j] ^ tag) >> 30)) kv[j] = ld_rlx(kp + j * (G * 32));
    }
    TS(3);
    if (t == 352) WLD(2);
    kv[SEGW] = none; ho[SEGW] = 0;
    bool slow = false;
    const bool more = __any_sync(0xffffffffu, lane == 31 && (old & 0xfe0000));
    if (more) {
        int c = lane;
#pragma unroll
        for (int j = 0; j < SEGW; j++) {
            const int n = max((int)(ho[j] >> 12 & 0xfff) - 31, 0);
            if ((unsigned)c < (unsigned)n) ho[SEGW] = j * CH + (ho[j] & 0xfff) + 31 + c - lane;
            c -= n;
        }
        slow = lane == 31 && c < 0;
        if (c < 0 && lane < 31)
            for (int it = 0; ((kv[SEGW] = ld_rlx(&gs->more[w * SEGW * CH + lane + ho[SEGW]])) ^ tag) >> 30; it++) spin_check(it);
        __syncwarp();
    }
#define EV 0
    uint32_t na_[SEGW + 1];
    uint64_t vp = (uint64_t)&gs->vals[w * SEGW * CH + lane], vv[SEGW + 1];
#pragma unroll
    for (int j = 0; j <= SEGW; j++) vv[j] = tag;
    auto ldv = [&](bool again) {
#pragma unroll
        for (int j = 0; j <= SEGW; j++)
            asm volatile("{.reg .pred p; setp.lt.u32 p, %2, 320; @p ld.relaxed.gpu.global.b64 %0, [%1];}" : "+l"(vv[j])
                         : "l"(madw(j < SEGW ? ho[j] & 0xfff : ho[j], 8, vp) + (j < SEGW ? j * CH * 8 : 0)),
                           "r"(again ? (((uint32_t)vv[j] ^ tag) >> 30 ? 0 : 320) : na_[j]) : "memory");
    };
#pragma unroll
    for (int j = 0; j <= SEGW; j++) na_[j] = (kv[j] & am) | (none & 511 & ~am);
    if (EV == 4) ldv(false);
#pragma unroll
    for (int j = 0; j <= SEGW; j++) nk[j] = atoms_add(sm + O_NCNT + na_[j], 512);
    if (EV == 3) ldv(false);
    auto visit = [&](auto f) {
#pragma unroll 1
        for (int j = 0; j < SEGW; j++) {
            const uint32_t* kl = &gs->keys[((w * SEGW + j) * G + b) * 32];
            const uint32_t h = ld_rlx(kl + ((31 + b) & 31));
#pragma unroll 1
            for (int i = lane; i < (h >> 12 & 0xfff); i += 32) {
                const int o = (w * SEGW + j) * CH + (h & 0xfff) + i;
                uint32_t k;
                int it = 0;
                do { k = ld_rlx(i < 31 ? kl + ((i + b) & 31) : &gs->more[o]); spin_check(it++); } while ((k ^ tag) >> 30);
                f(k, o, i);
            }
        }
    };
    slow = __syncthreads_or(slow);
    if (slow) {
        if (t < 80) sts32(sm + O_NCNT + 4 * t, t <= NLOC ? 4 * t : 0);
        __syncthreads();
        visit([&](uint32_t k, int, int) { atoms_add(sm + O_NCNT + (k & 511), 512); });
        __syncthreads();
    }
    TS(4);
    if (t == 352) WLD(3);
    if (EV == 2) ldv(false);
    if (w < 10) {
        const uint32_t key = lds32(sm + O_NCNT + 4 + (t & ~3));
        uint4 k[5];
#pragma unroll
        for (int i = 0; i < 5; i++) k[i] = lds128(sm + O_NCNT + q * 80 + i * 16);
        uint32_t c[4] = {0, 0, 0, 0};
#pragma unroll
        for (int i = 0; i < 5; i++) { c[0] += (key - k[i].x) >> 31; c[1] += (key - k[i].y) >> 31; c[2] += (key - k[i].z) >> 31; c[3] += (key - k[i].w) >> 31; }
        int rank = c[0] + c[1] + c[2] + c[3];
        rank += __shfl_xor_sync(0xffffffffu, rank, 1);
        rank += __shfl_xor_sync(0xffffffffu, rank, 2);
        if (ASC && rank < 2 * NPRIV) rank = (2 * NPRIV - 1 - rank) ^ 1;
        if (t < NLOC * 4) sts32(sm + O_SORT + 4 * rank, key);
    }
    if (EV == 5) ldv(false);
    __syncthreads();
    TS(2);
    const bool on = lane < NLOC / 4;
    const uint4 k4 = lds128(sm + O_SORT + 16 * (on ? lane : 0));
    if (EV == 1) ldv(false);
    const uint32_t ks[4] = {k4.x, k4.y, k4.z, k4.w};
    const int n0 = on ? max(1u, (ks[0] + 3584) >> 12) : 0, n1 = on ? max(1u, (ks[2] + 3584) >> 12) : 0;
    const int u2 = warp_incl(n0 + n1), u1 = u2 - n1, u0 = u1 - n0;
    const int total = __shfl_sync(0xffffffffu, u2, 31);
    slow |= total > CAPT;
    int gbase = b * CAPT + 1;
    if (on) {
#pragma unroll
        for (int i = 0; i < 4; i++) {
            const int a = ks[i] & 511, node = a * (G / 4) - G + b, o = (i >> 1 ? u1 : u0) * 256 + (i & 1) * 16;
            const uint32_t mk = (node < NN ? node + 1 : 0) + ((i >> 1 ? n1 : n0) << 16);
            sts64(sm + O_NOFF + 2 * a, o - (a >> 4), mk + a * 16);
            if (!slow && ks[i] < 512) sts32(sm + O_L + 4 + o, mk);
        }
    }
    __syncwarp();
    if (t == 352) WLD(8);
    if (!slow) {
        uint32_t mk[SEGW + 1];
        TS(13);
        if (t == 352) { asm volatile("cp.async.bulk.wait_group.read 0;" ::: "memory"); }
        if (EV == 0) ldv(false);
        if (t == 352) WLD(4);
        TS(16);
#pragma unroll
        for (int j = 0; j <= SEGW; j++) {
            const uint2 o = lds64(sm + O_NOFF + 2 * na_[j]);
            mk[j] = o.y - nk[j] * 16; nk[j] = o.x + (nk[j] >> 4);
        }
        for (int it = 0;; it++) {
            old = 0;
#pragma unroll
            for (int j = 0; j <= SEGW; j++) old |= (uint32_t)vv[j] ^ tag;
            if (!__any_sync(0xffffffffu, old >> 30)) break;
            spin_check(it);
            vp = __shfl_sync(0xffffffffu, vp, lane);
            ldv(true);
            TV(23, (it + 1) * 100);
        }
        TS(17);
#pragma unroll
        for (int j = 0; j <= SEGW; j++)
            asm volatile("{.reg .pred p; setp.ne.u32 p, %3, %5; @p st.shared.v4.u32 [%0], {%1,%2,%3,%4};}"
                         ::"r"(sm + O_L + nk[j]), "r"(kv[j]), "r"(mk[j]), "r"((uint32_t)vv[j]), "r"((uint32_t)(vv[j] >> 32)), "r"(tag) : "memory");
        TS(18);
        if (na_[SEGW] < 320) gs->more[w * SEGW * CH + lane + ho[SEGW]] = 0;
    } else {
        int so = 0;
        if (t == 352) WLD(4);
#pragma unroll
        for (int j = 0; j < SEGW; j++) so += ho[j] & 0xfff;
        if (lane == 0) atoms_add(sm + O_SUM, so);
        if (t == 352) asm volatile("cp.async.bulk.wait_group.read 0;" ::: "memory");
        __syncthreads();
        gbase = TBIG + (lds32(sm + O_SUM) >> 3) + (NLOC + 5) * b;
        auto put = [&](uint32_t k, uint64_t e, uint32_t a, int rank) {
            const uint2 o = lds64(sm + O_NOFF + 2 * a);
            gs->list[gbase * 16 + ((o.x + (a >> 4)) >> 4) + rank * 2] = make_uint4(k, o.y - a * 16 - (rank << 13), e, e >> 32);
        };
        visit([&](uint32_t k, int o, int i) {
            uint64_t e;
            int it = 0;
            do {
                asm volatile("ld.relaxed.gpu.global.b64 %0, [%1];" : "=l"(e) : "l"(&gs->vals[o]) : "memory");
                spin_check(it++);
            } while (((uint32_t)e ^ tag) >> 30);
            if (i >= 31) gs->more[o] = 0;
            put(k, e, k & 511, atoms_add(sm + O_NCUR + (k & 511), 1));
        });
#pragma unroll 1
        for (int i = 0; i < 4; i++) {
            const uint32_t k = i == 0 ? ks[0] : i == 1 ? ks[1] : i == 2 ? ks[2] : ks[3];
#pragma unroll 1
            for (int p = (k >> 9) + w; p < (i >> 1 ? n1 : n0) * 8; p += NT / 32) put(0, 0, k & 511, p);
        }
        __threadfence();
    }
    if (t == 352) WLD(9);
    const uint32_t iw0 = (gbase + u0) << 12 | n0, iw1 = (gbase + u1) << 12 | n1;
    __syncthreads();
    TS(5);

    if (w >= 8) {
        asm volatile("setmaxnreg.dec.sync.aligned.u32 " STR(PREG) ";");
        const int h = __reduce_max_sync(0xffffffffu, w & 3);
        if (h == 0) TSW(28);
        gbase = __reduce_min_sync(0xffffffffu, iw0) >> 12;
        int pos = gbase + h, end = __reduce_max_sync(0xffffffffu, lane == NPRIV / 2 ? (NPRIV & 1 ? iw1 : iw0) : 0) >> 12;
        const int bytes = gbase < TBIG ? ((__reduce_max_sync(0xffffffffu, iw0) >> 12) - gbase) * 256 : 0;
        const uint32_t ring = sm + O_RING;
        const uint64_t xl = wr[0][0] | (uint64_t)wr[0][1] << 32, al = wr[0][2] | (uint64_t)wr[0][3] << 32, ml = wr[1][0] | (uint64_t)wr[1][1] << 32;
        const uint32_t xoff[2] = {wr[1][2], wr[1][3]}, aoff = wr[2][0], coff = wr[2][1], sh = wr[2][2], ial = wr[2][3], sel = wr[3][0];
        auto lde = [&](uint2& e, int p) {
            asm volatile("{.reg .pred p; setp.gt.s32 p, %3, 0; @p ld.relaxed.gpu.global.v2.u32 {%0,%1}, [%2];}" : "+r"(e.x), "+r"(e.y) : "l"(madw(p, 256, ml)), "r"(p) : "memory");
        };
        uint2 e0[3] = {};
#pragma unroll
        for (int k = 0; k < 3; k++) {
            e0[k] = lds64(sm + O_L - 2048 + k * 1024 + t * 8);
            lde(e0[k], bytes ? 0 : pos + 4 * k);
        }
        if (h == 3) fence_async();
        else if (B4) asm volatile("bar.arrive 4, %0;" ::"n"(NT) : "memory");
        pos += 4;

        int ev = 0, state = -2, tk = 0, nr = 0;
        uint32_t inf = 0;
        int ii = 0;
        auto take = [&]() {
            int v = 0;
            asm volatile("{.reg .pred p; setp.eq.s32 p, %2, 0; @p atom.relaxed.gpu.global.add.u32 %0, [%1], 1;}" : "+r"(v) : "l"(&gs->ticket), "r"(lane) : "memory");
            return v;
        };
        auto resolve = [&]() {
            const int k = __reduce_max_sync(0xffffffffu, tk);
            inf = tag;
            if (k < G * NPOOL) { const int l = k / G; ii = (k - l * G) * NPOOL + l; inf = ld_rlx(&gs->info[ii]);
                const int j = NPRIV + 1 + nr + (STAG), gd = __reduce_max_sync(0xffffffffu, lds32(sm + O_SUM + 4));
                tk = (QOK) && (j & ~7) > gd + GM && k >= G * NPOOL - (j & 7 ? THETB : THETA) ? G * NPOOL : take(); }
        };
        uint32_t so = ring + h * SLOT, ph = 0x80000000u;
        uint32_t spins = 0;
        asm volatile(".reg .pred z<5>;");
#define HD 300
        { const uint32_t c0 = clock(); while (__any_sync(0xffffffffu, (uint32_t)clock() - c0 < h * HD)); }
        while (true) {
            const uint2 e = e0[0];
            const uint32_t o = e.x >> sh, id = __shfl_sync(0xffffffffu, o, ial);
            uint32_t s[4];
#pragma unroll
            for (int j = 0; j < 4; j++) s[j] = __shfl_sync(0xffffffffu, o, 2 * j + 1, 8);
            const uint32_t nx = so == ring + (NSLOT - 1) * SLOT ? ph : ph ^ 0x80000000u, ey = lop_sel(e.y, nx, sel);
            const uint64_t ga = madw(id, 32, al);
            uint64_t gx[4];
#pragma unroll
            for (int j = 0; j < 4; j++) gx[j] = madw(s[j], 1024, xl);
            const uint32_t da = so + aoff, dx[2] = {so + xoff[0], so + xoff[1]}, dc = so + coff;
            asm volatile("setp.eq.u32 z0, %0, 0;\nsetp.eq.u32 z1, %1, 0;\nsetp.eq.u32 z2, %2, 0;\nsetp.eq.u32 z3, %3, 0;\nsetp.eq.u32 z4, %4, 0;\n"
                         ::"r"(NULLP(s[0])), "r"(NULLP(s[1])), "r"(NULLP(s[2])), "r"(NULLP(s[3])), "r"(id), "l"(ga), "r"(da), "r"(dx[0]), "r"(dx[1]), "r"(dc));
            lde(e0[0], state < 0 ? 0 : pos);
            if (HS == 2) asm volatile("{.reg .pred p; setp.eq.s32 p, %1, -2; @p bar.arrive 5, %0;}" ::"n"(NT), "r"(state) : "memory");
            if (h == 0 && state == -2) TSW(29);
            if (h == 0 && state == -1) TSW(30);
            asm volatile("{\n.reg .pred p;\n.reg .b64 s;\nmov.b64 s, {0, %2};\n"
                         "LOOP:\nmbarrier.try_wait.shared::cta.b64 p, [%1], s;\n@p bra DONE;\n"
                         "add.u32 %0, %0, 1;\nsetp.gt.u32 p, %0, %3;\n@p trap;\nbra LOOP;\nDONE:\n}"
                         : "+r"(spins) : "r"(so + S_EMPTY), "r"(ph), "n"(SPIN_LIMIT) : "memory");
            asm volatile("cp.async.cg.shared.global [%0], [%1], 16, z4;" ::"r"(da), "l"(ga) : "memory");
#define ROW(j) _Pragma("unroll") for (int k = 0; k < 8; k++) \
                asm volatile("cp.async.cg.shared.global [%0], [%1], 16, z" #j ";" ::"r"(dx[j >> 1] + (j & 1) * 8192 + k * 128), "l"(gx[j] + k * 128) : "memory")
            X4(ROW);
            stsm2t(dc, e.x, ey);
            asm volatile("cp.async.mbarrier.arrive.noinc.shared::cta.b64 [%0];" ::"r"(so + S_FULL) : "memory");
            const bool wrap = NSLOT == 5 ? so != ring : so >= ring + (NSLOT - 4) * SLOT;
            ph ^= wrap ? 0x80000000u : 0u;
            so = wrap ? so - (NSLOT - 4) * SLOT : so + 4 * SLOT;
            pos += 4;
            if (pos >= ev) {
                if (state < 0) {
                    e0[0] = e0[1]; e0[1] = e0[2];
                    if (state == -2) {
                        if (h == 0) TSW(24);
                        if (h == 3) TSW(25);
                        if (HS == 1) asm volatile("bar.arrive 5, %0;" ::"n"(NT) : "memory");
                        if (HS >= 4 && h == HS - 4) asm volatile("bar.arrive 5, 288;" ::: "memory");
                        if (h < 2) bar_sync(7, 320);
                        if (h == 3) bar_sync(4, NT);
                        if (h == 0) mbar_wait(sm + O_WBE, 0);
                        if (h == 3) {
                            if (lane == 0) {
                                if (bytes) bulk_st(gs->list + gbase * 16, sm + O_L, bytes);
                                asm volatile("cp.async.bulk.wait_group.read 0;" ::: "memory");
                            }
                            __syncwarp();
                            if (lane == 0) {
                                for (int j = 0; j < NB1; j++) tma3d(sm + O_W1 + j * 8192, &m_w1, KR * 16 + 32 * j, 0, sm + O_WBB);
                            }
                            __syncwarp();
                        }
                        state = -1;
                    } else {
                        if (h == 3) {
                            if (lane == 0) asm volatile("cp.async.bulk.wait_group 0;\nfence.proxy.async;" ::: "memory");
                            __syncwarp();
                            const int i = opaque(2 * lane - NPRIV, lane);
                            if ((unsigned)i < NPOOL) st_rlx(&gs->info[b * NPOOL + i], tag | iw0);
                            if ((unsigned)(i + 1) < NPOOL) st_rlx(&gs->info[b * NPOOL + i + 1], tag | iw1);
                        }
                        bar_sync(6, 128);
                        ev = h ? end : end - 12; state = h ? 2 : 0;
                    }
                } else if (state == 0) { ev = end - 6; state = 1; tk = take(); }
                else if (state == 1) { resolve(); ev = end; state = 2; }
                else {
                    if (state == 3) break;
                    do {
                        const uint32_t mb = sm + O_MB + (nr & 15) * 8;
                        uint32_t rg;
                        nr++;
                        if (h == 0) {
                            for (int it = 0; (rg = __reduce_max_sync(0xffffffffu, inf ^ tag)) >> 30; it++) { spin_check(it); inf = ld_rlx(&gs->info[ii]); }
                            asm volatile("st.release.cta.shared.b64 [%0], %1;" ::"r"(mb), "l"(rg | (uint64_t)nr << 32) : "memory");
                            if (rg) resolve();
                        } else {
                            uint64_t m;
                            for (int it = 0;; it++) {
                                asm volatile("ld.acquire.cta.shared.b64 %0, [%1];" : "=l"(m) : "r"(mb) : "memory");
                                if (__all_sync(0xffffffffu, (int)(m >> 32) == nr)) break;
                                spin_check(it);
                            }
                            rg = __reduce_max_sync(0xffffffffu, (uint32_t)m);
                        }
                        pos = rg ? (int)(rg >> 12) + pos - end : 0;
                        end = rg ? (rg >> 12) + (rg & 0xfff) : 1;
                        state = rg ? 2 : 3;
                    } while (pos >= end);
                    ev = end;
                }
            }
        }
        mbar_wait31(so + S_EMPTY, ph);
        TSW(8 + (h & 1));
        if (lane == 0) sts32(so + S_N, 0);
        mbar_arrive(so + S_FULL);
        if (t == 256) {
            gs->epoch[b * 32] = (tag >> 30) % 3;
            if (atomicInc(&gs->done, G - 1) == G - 1) gs->ticket = 0;
        }
        asm volatile("cp.async.wait_all;" ::: "memory");
    } else {
        asm volatile("setmaxnreg.inc.sync.aligned.u32 " STR(CREG) ";");
        if (HS && !HL) bar_sync(5, HS < 4 ? NT : 288);
        const uint32_t xa = opaque(((mat >> 1) * 8 + r) * 1024 + (w >> 2) * 128 + (((2 * (w & 3) + (mat & 1)) ^ r) * 16), lane);
        const uint32_t aa = opaque(S_A + ((mat >> 1) * 8 + r) * 32 + (((mat & 1) ^ (r >> 2)) * 16), lane);
        const uint32_t ya = opaque(S_C + (mat & 1) * 80 + (mat >> 1) * 16, lane);
        const uint32_t yc = opaque(S_C + (mat < 2 ? mat * 80 + 32 : (r >> 2) == (mat & 1) && q < 3 ? (mat & 1) * 80 + q * 16 : 64), lane);
        const uint32_t na = opaque(sm + O_NODE + mat * 4, lane);
        const uint32_t pw = sm + O_P + w * PW;
        const uint32_t fx = opaque(pw + (q < 3 ? P_1P0 + 2 * q * PSBO : P_1P1 + PSBO) + (mat & 1) * 128 + (r >> 2) * PSBO, lane);
        const uint32_t fyz = opaque(pw + (q < 3 ? (mat < 2 ? P_1P1 : P_1P2) + 2 * q * PSBO : mat < 2 ? P_0P0 : P_0P1) + (mat & 1) * 128 + (r >> 2) * PSBO, lane);
        uint32_t oh[4][2];
#pragma unroll
        for (int c = 0; c < 8; c++) oh[c & 3][c >> 2] = opaque(g == c ? 0x3F803F80u : 0u, lane);
        uint32_t eb[3];
#pragma unroll
        for (int k = 0; k < 3; k++) {
            const int i = (g & 3) * 9 + (q & 1) * 6 + k;
            const uint32_t lo = __shfl_sync(0xffffffffu, epl, i), hi = __shfl_sync(0xffffffffu, epl, i + 3);
            eb[k] = (g & 3) < 3 && (q >> 1) == (g >> 2) ? (q & 1 ? lo : lo | hi << 16) : 0u;
        }
        asm volatile(".reg .pred lane0;\nsetp.eq.u32 lane0, %0, 0;" ::"r"(lane));
        uint32_t w0[16][4], w1[KR][4];
        mbar_wait(sm + O_WBD, 0);
        if (HS && HL) bar_sync(5, HS < 4 ? NT : 288);
#pragma unroll
        for (int k = 0; k < 16; k++) ldsm4t(w0[k], sm + O_W0S + (k >> 2) * 16384 + (w >> 2) * 8192 + (k & 3) * 2048 + sw);
#pragma unroll
        for (int k = 0; k < KR; k++) ldsm4t(w1[k], sm + (k < 4 ? O_W1S + (k >> 1) * 8192 : O_WR1) + (w >> 2) * 4096 + (k & 1) * 2048 + sw);
        if (B4) asm volatile("bar.arrive 4, %0;" ::"n"(NT) : "memory");
        bar_sync(7, B4 ? 320 : NT);
        TS(6);
        Acc A;
#pragma unroll
        for (int i = 0; i < 4; i++) { A.p00[i] = A.p110[i] = A.p10[0][i] = A.p10[1][i] = A.p10[2][i] = 0; A.t01[i] = A.m[0][i] = A.m[1][i] = A.m[2][i] = 0.f; }
        uint32_t room = 144 - (STAG) * 16;
        uint32_t so = sm + O_RING, ph, a[4], ok, go, mt = 0;
        mbar_wait(so + S_FULL, 0);
        ldsm4(a, so + aa);
        TS(7);
        while (true) {
            {
                constexpr int F = 1, XS = XS_F;
                uint32_t yb[8], f[4][4], R[5][4], u[4][4], sd[4];
                float y[4], z[4];
                const uint32_t sof = room & 112;
                room -= 16;
                SEQ_F
            }
            if (!(go && room)) {
                const uint32_t pu = __reduce_max_sync(0xffffffffu, ph);
                if (!room || !pu) {
                    if (GD == 2) asm volatile("@lane0 red.shared.add.u32 [%0], 1;" ::"r"(sm + O_SUM + 4) : "memory");
                    GT(0);
                    const uint32_t wg = __reduce_max_sync(0xffffffffu, w >> 2);
                    if (!FEN) asm volatile("fence.proxy.async.shared::cta;" ::: "memory");
                    mbar_wait(sm + O_WBB, 0);
                    GT(1);
                    if (ALT == 1) asm volatile("{.reg .pred p; setp.ne.u32 p, %0, 0;\n@p bar.arrive 1, 256;\n@p bar.sync 2, 256;\n@!p bar.sync 1, 256;}" ::"r"(wg ^ AWG) : "memory");
                    else bar_sync(1, 256);
                    if (FEN) asm volatile("fence.proxy.async::generic.acquire.sync_restrict::shared::cluster.cluster;" ::: "memory");
                    GT(2);
                    float d0[8], d1[24];
                    const uint64_t db = (uint64_t)((sm + O_P) >> 4) | (8ull << 16) | ((uint64_t)(PSBO / 16) << 32);
                    const uint32_t da = ((sm + O_W1) >> 4 | 1 << 16) + wg * 256;
                    asm volatile("wgmma.fence.sync.aligned;" ::: "memory");
                    if (!IL) {
#pragma unroll
                        for (int k = 0; k < 16; k++) G0(k);
                        asm volatile("wgmma.commit_group.sync.aligned;" ::: "memory");
                    }
                    const uint32_t sp = so == sm + O_RING ? sm + O_RING + (NSLOT - 1) * SLOT : so - SLOT, sr = (r & 6) + (mat & 1);
                    const uint32_t nd = (sr * 16 - 16 & 112) >= room ? lds32(sm + O_NODE + sr * 16 + (mat >> 1) * 4) : 0;
                    const uint64_t oa = madw(nd, 1024, (uint64_t)(out - 1024 + w * 32 + (r & 1) * 16));
                    const uint32_t sl = sp + ((mat >> 1) * 8 + sr) * 1024 + (w >> 2) * 128 + (((2 * (w & 3) + (r & 1)) ^ sr) * 16);
                    auto put = [&](int j) {
                        const uint4 v = lds128(sl + j * 256);
                        asm volatile("{.reg .pred p; setp.ne.u32 p, %5, 0; @p st.global.v4.u32 [%0], {%1,%2,%3,%4};}"
                                     ::"l"(oa + j * 256), "r"(v.x), "r"(v.y), "r"(v.z), "r"(v.w), "r"(nd) : "memory");
                    };
                    float gt[8];
#pragma unroll
                    static_for<25>([&](auto kc) {
                        constexpr int k = kc.value;
                        if (IL && k == 16 / (IL + !IL)) asm volatile("wgmma.commit_group.sync.aligned;" ::: "memory");
                        if (ALT == 1 && k == ASP) asm volatile("{.reg .pred p; setp.eq.u32 p, %0, 0;\n@p bar.arrive 2, 256;}" ::"r"(wg ^ AWG) : "memory");
                        if (k == GP || k == 24) asm volatile("wgmma.commit_group.sync.aligned;" ::: "memory");
                        if (k == GP) {
                            asm volatile("wgmma.wait_group.sync.aligned 1;" ::: "memory");
#pragma unroll
                            for (int i = 0; i < 8; i++) asm volatile("" : "+f"(d0[i])::"memory");
                            stsm4t(sp + xa, pack(d0[0], d0[1]), pack(d0[2], d0[3]), pack(d0[4], d0[5]), pack(d0[6], d0[7]));
                            __syncwarp();
                        }
                        if (k == min(GP + GS, 24)) put(0);
#pragma unroll
                        for (int i = 0; i < 8; i++) {
                            if (k == min(GP + i / 2 * GS, 24)) asm volatile("ex2.approx.ftz.f32 %0, %1;" : "=f"(gt[i]) : "f"(d0[i] * -1.4426950408889634f) : "memory");
                            if (k == min(GP + (i / 2 + 1) * GS, 24)) asm volatile("rcp.approx.ftz.f32 %0, %1;" : "=f"(gt[i]) : "f"(gt[i] + 1.f) : "memory");
                        }
                        if (k == min(GP + 5 * GS, 24)) {
                            uint32_t chk = -1;
#pragma unroll
                            for (int i = 0; i < 8; i++) chk &= __float_as_uint(gt[i]);
                            sts32(sm + O_TRASH, chk);
                        }
                        if (k < 24) G1(k % 24);
#pragma unroll
                        for (int i = 0; i < IL; i++) if (k * IL + i < 16) G0((k * IL + i) % 16);
                    });
                    GT(3);
                    asm volatile("wgmma.wait_group.sync.aligned 0;" ::: "memory");
                    GT(4);
#pragma unroll
                    for (int i = 0; i < 24; i++) asm volatile("" : "+f"(d1[i])::"memory");
                    if (ALT == 1) asm volatile("{.reg .pred p; setp.ne.u32 p, %0, 0;\n@p bar.sync 3, 256;}" ::"r"(wg ^ AWG) : "memory");
#pragma unroll
                    for (int j = 0; j < 3; j++) {
                        uint32_t o[4];
#pragma unroll
                        for (int i = 0; i < 4; i++) o[i] = pack(d1[8 * j + 2 * i] * gt[2 * i], d1[8 * j + 2 * i + 1] * gt[2 * i + 1]);
                        stsm4t(sp + xa + 256 + j * 256, o[0], o[1], o[2], o[3]);
                    }
                    __syncwarp();
#pragma unroll
                    for (int j = 1; j < 4; j++) put(j);
                    __syncwarp();
                    asm volatile("@lane0 mbarrier.arrive.shared::cta.b64 _, [%0];" ::"r"(sp + S_EMPTY) : "memory");
                    if (GD == 1) asm volatile("@lane0 red.shared.add.u32 [%0], 1;" ::"r"(sm + O_SUM + 4) : "memory");
                    GT(5);
                    if (ALT == 1) asm volatile("{.reg .pred p; setp.eq.u32 p, %0, 0;\n@p bar.sync 3, 256;}" ::"r"(wg ^ AWG) : "memory");
                    else bar_sync(3, 256);
                    GT(6);
                    room = 128;
                    if (!pu) break;
                }
                if (!ok) { mbar_wait31(so + S_FULL, pu); ldsm4(a, so + aa); }
                if (!(pu & 0xfffe)) continue;
            }
            while (true) {
                do {
                    constexpr int F = 0, XS = XS_R;
                    uint32_t yb[8], f[4][4], R[5][4], u[4][4], sd[4];
                    SEQ_R
                } while (go);
                if (ok) break;
                const uint32_t pu = __reduce_max_sync(0xffffffffu, ph);
                mbar_wait31(so + S_FULL, pu); ldsm4(a, so + aa);
                if (!(pu & 0xfffe)) break;
            }
        }
        TS(10);
    }
}

typedef CUresult (*EncFn)(CUtensorMap*, CUtensorMapDataType, cuuint32_t, void*, const cuuint64_t*, const cuuint64_t*,
                          const cuuint32_t*, const cuuint32_t*, CUtensorMapInterleave, CUtensorMapSwizzle,
                          CUtensorMapL2promotion, CUtensorMapFloatOOBfill);

void make_map(EncFn fn, CUtensorMap* m, void* p, int rows, int cols, int brows, int bcols, int bblk) {
    cuuint64_t dims[3] = {64, (cuuint64_t)rows, (cuuint64_t)cols / 64}, strides[2] = {(cuuint64_t)cols * 2, 128};
    cuuint32_t box[3] = {(cuuint32_t)bcols, (cuuint32_t)brows, (cuuint32_t)bblk}, es[3] = {1, 1, 1};
    fn(m, CU_TENSOR_MAP_DATA_TYPE_BFLOAT16, 3, p, dims, strides, box, es, CU_TENSOR_MAP_INTERLEAVE_NONE,
       bcols == 64 ? CU_TENSOR_MAP_SWIZZLE_128B : CU_TENSOR_MAP_SWIZZLE_NONE, CU_TENSOR_MAP_L2_PROMOTION_L2_128B, CU_TENSOR_MAP_FLOAT_OOB_FILL_NONE);
}

}

extern "C" void kernel_launch(void* const* d_in, const int* in_sizes, int n_in, void* d_out, int out_size) {
    static EncFn enc = nullptr;
    static void* scratch = nullptr;
    if (!enc) {
        void* fn = nullptr;
        cudaDriverEntryPointQueryResult qr;
        cudaGetDriverEntryPoint("cuTensorMapEncodeTiled", &fn, cudaEnableDefault, &qr);
        enc = (EncFn)fn;
        cudaGetSymbolAddress(&scratch, g_scratch);
        cudaFuncSetAttribute(tp_kernel, cudaFuncAttributeMaxDynamicSharedMemorySize, SMEM_BYTES);
    }
    CUtensorMap m_wr, m_w0, m_w1, m_x;
    make_map(enc, &m_wr, d_in[5], 16, 640, 16, 64, 5);
    make_map(enc, &m_w0, d_in[6], 256, 128, 64, 64, 2);
    make_map(enc, &m_w1, d_in[7], 384, 128, 32, 64, 2);
    make_map(enc, &m_x, d_in[0], NN * 8, 64, NLOC * 2, 8, 1);
    tp_kernel<<<G, NT, SMEM_BYTES>>>((const int4*)d_in[4], (const int4*)d_in[3], (const char*)d_in[1], (Scratch*)scratch,
                                     (const char*)d_in[0], (const char*)d_in[2], (const __nv_bfloat16*)d_in[8], (char*)d_out,
                                     m_wr, m_w0, m_w1, m_x);
}
```

```cpp
#include <cuda_runtime.h>
#include <cuda_bf16.h>
#include <cuda.h>
#include <stdint.h>
#include <stddef.h>

namespace {

constexpr int NN = 10000;
constexpr int NE = 320000;
constexpr int G = 132;
constexpr int NT = 384;
constexpr int CH = 2432;
constexpr int NLOC = (NN + G - 1) / G;
#define NPOOL 3
constexpr int NPAIR = NLOC / 2, NPRIV = NPAIR - NPOOL;
constexpr int SEGW = 11;

#define NSLOT 6
#define PP 0xffff
#define TP 0x9375
#define STAG (b & 7)
#define ASC (b & 1)
#define THETA (5 * G / 3)
#define THETB G
#define QOK (STAG)
#define QJ 3
#define WP 0x2222255
#define KR 6
#define WLD(p) { _Pragma("unroll") for (int j = 0; j < 4 + KR / 2; j++) if ((WP >> 4 * j & 15) == p) \
    tma3d(sm + (j < 4 ? O_W0S + j * 16384 : j < 6 ? O_W1S + (j - 4) * 8192 : O_WR1), j < 4 ? &m_w0 : &m_w1, j < 4 ? j * 64 : (j - 4) * 32, 0, sm + O_WBD); \
    _Pragma("unroll") for (int j = 0; j < 4; j++) { const int r0 = (b * 4 + j) * (NLOC / 4); \
        if ((PP >> 4 * j & 15) == p) pf_l2(x + r0 * 1024, min(NLOC / 4, NN - r0) * 1024); \
        if ((TP >> 4 * j & 15) == p) tma3d(sm + O_WR1 + 10240, &m_x, r0 * 8, 0, sm + O_WBE); } }
#define ALT 1
#define AWG 0
#define IL 1
#define RSL 1
#define FEN 1
#define HS 4
#define HL 0
#define B4 1
#define NB1 (12 - KR / 2)
#define GD 1
#define HT 1
#define PH 1
#define MA 1
#define GM 0
#define GP 24
#define GS 2
#define ASP 20
#define INV 0
#define NULLP(v) v
#define CREG 224
#define PREG 56
#define STR2(x) #x
#define STR(x) STR2(x)

constexpr int S_A = 16384, S_C = S_A + 512, S_FULL = S_C + 144, S_EMPTY = S_FULL + 8, S_N = S_C + 160, SLOT = S_C + 512;

constexpr int PSBO = 272;
constexpr int PB1 = 5 * PSBO + 256, PB0 = PSBO + 256;
constexpr int P_1P0 = 0, P_1P1 = PB1, P_0P1 = 2 * PB1, P_0P0 = P_0P1 + PB0, P_1P2 = P_0P0 + PB0;
constexpr int PW = P_1P2 + PB1;

constexpr int up1k(int a) { return (a + 1023) / 1024 * 1024; }
constexpr int O_W1 = 0;
constexpr int O_P = 79744;
constexpr int O_RING = O_P + 8 * PW;
constexpr int O_WBA = O_RING + 6 * SLOT, O_WBB = O_WBA + 8, O_WBC = O_WBA + 16, O_WBD = O_WBA + 24, O_WBE = O_WBA + 32, O_TRASH = O_WBA + 40, O_NODE = O_WBA + 48;
constexpr int O_SUM = O_NODE + 128, O_MB = O_SUM + 16;
constexpr int SMEM_BYTES = O_MB + 128;
constexpr int CAPT = 192;
constexpr int O_L = 0, LZ = CAPT * 256 / (NT * 16), O_W0S = O_L + CAPT * 256, O_OUT = O_W0S + 65536, O_SRC = O_OUT + CH * 8;
constexpr int O_KT = O_RING + SLOT, O_RH = O_RING + 2 * SLOT;
constexpr int O_WR0 = up1k(O_RING + 3 * SLOT), O_WR1 = up1k(O_RING + 4 * SLOT), O_W1S = up1k(O_RING + 5 * SLOT);
constexpr int O_BCNT = O_WR0 + 10240, O_NCUR = O_BCNT + 640, O_NCNT = O_NCUR + 320;
constexpr int O_BOFF = O_NCNT + 512, O_SORT = O_BOFF + 640, O_NOFF = O_SORT + 320;
constexpr int TBIG = G * CAPT + 8, NTILE = TBIG + NE / 8 + G * (NLOC + 5);
static_assert(SMEM_BYTES <= 232448 && CAPT % 16 == 0 && NTILE < (1 << 18), "smem");
static_assert(LZ * NT * 16 == CAPT * 256 && O_W0S % 1024 == 0 && O_OUT <= O_RING && O_SRC + CH * 4 <= O_RING + S_C && G * 128 <= S_C, "staging");
static_assert(O_NOFF + 1024 <= O_RING + 3 * SLOT + S_C && O_W1S + 16384 <= O_RING + 5 * SLOT + S_C, "staging");
static_assert(O_RING % 128 == 0 && SLOT % 128 == 0 && O_W0S <= O_P && O_NOFF % 8 == 0, "layout");
static_assert(G * CH >= NE && NE % 8 == 0 && CH < 4096 && CH / 8 <= 320 && NE < (1 << 21), "chunks");
static_assert(SEGW * (NT / 32) == G && G <= 160 && G % 4 == 0, "segments");
static_assert(NLOC % 4 == 0 && NLOC < 80 && NLOC * 4 <= 320 && NN < 0x3fff && NE / 8 < 0xbfff && NPRIV >= 30, "scan width");

struct __align__(256) Scratch {
    uint32_t keys[G * G * 32];
    uint64_t vals[G * CH];
    uint32_t more[G * CH];
    uint32_t epoch[G * 32];
    uint32_t info[(G * NPOOL + 127) / 128 * 128];
    unsigned done, pad0[31], ticket, pad1[31];
    uint4 list[NTILE * 16];
};
static_assert(offsetof(Scratch, list) % 256 == 0, "list");
__device__ Scratch g_scratch;
#define GT(i)
#define TS(i)
#define TSW(i)
#define TV(i, v)

constexpr int SPIN_LIMIT = 1 << 24;

__device__ __forceinline__ void mbar_init(uint32_t a, int c) { asm volatile("mbarrier.init.shared::cta.b64 [%0], %1;" ::"r"(a), "r"(c) : "memory"); }
__device__ __forceinline__ void mbar_expect(uint32_t a, int b) { asm volatile("mbarrier.arrive.expect_tx.shared::cta.b64 _, [%0], %1;" ::"r"(a), "r"(b) : "memory"); }
__device__ __forceinline__ void mbar_arrive(uint32_t a) { asm volatile("mbarrier.arrive.shared::cta.b64 _, [%0];" ::"r"(a) : "memory"); }
__device__ __forceinline__ void mbar_wait(uint32_t a, uint32_t ph) {
    asm volatile("{\n.reg .pred p, q;\n.reg .u32 it;\n"
                 "mbarrier.try_wait.parity.shared::cta.b64 p, [%0], %1;\n"
                 "@p bra DONE;\n"
                 "mov.u32 it, 0;\n"
                 "LOOP:\n"
                 "mbarrier.try_wait.parity.shared::cta.b64 p, [%0], %1;\n"
                 "@p bra DONE;\n"
                 "add.u32 it, it, 1;\n"
                 "setp.gt.u32 q, it, %2;\n"
                 "@q trap;\n"
                 "bra LOOP;\n"
                 "DONE:\n}" ::"r"(a), "r"(ph), "n"(SPIN_LIMIT) : "memory");
}
__device__ __forceinline__ void mbar_wait31(uint32_t a, uint32_t ph) {
    asm volatile("{\n.reg .pred p, q;\n.reg .u32 it;\n.reg .b64 s;\n"
                 "mov.b64 s, {0, %1};\n"
                 "mbarrier.try_wait.shared::cta.b64 p, [%0], s;\n"
                 "@p bra DONE;\n"
                 "mov.u32 it, 0;\n"
                 "LOOP:\n"
                 "mbarrier.try_wait.shared::cta.b64 p, [%0], s;\n"
                 "@p bra DONE;\n"
                 "add.u32 it, it, 1;\n"
                 "setp.gt.u32 q, it, %2;\n"
                 "@q trap;\n"
                 "bra LOOP;\n"
                 "DONE:\n}" ::"r"(a), "r"(ph), "n"(SPIN_LIMIT) : "memory");
}
__device__ __forceinline__ void spin_check(int it) {
    asm volatile("{\n.reg .pred q;\nsetp.gt.s32 q, %0, %1;\n@q trap;\n}" ::"r"(it), "n"(SPIN_LIMIT));
}
__device__ __forceinline__ void ldsm4(uint32_t* r, uint32_t a) { asm volatile("ldmatrix.sync.aligned.m8n8.x4.shared.b16 {%0,%1,%2,%3}, [%4];" : "=r"(r[0]), "=r"(r[1]), "=r"(r[2]), "=r"(r[3]) : "r"(a) : "memory"); }
__device__ __forceinline__ void ldsm4t(uint32_t* r, uint32_t a) { asm volatile("ldmatrix.sync.aligned.m8n8.x4.trans.shared.b16 {%0,%1,%2,%3}, [%4];" : "=r"(r[0]), "=r"(r[1]), "=r"(r[2]), "=r"(r[3]) : "r"(a) : "memory"); }
__device__ __forceinline__ void ldsm2t(uint32_t* r, uint32_t a) { asm volatile("ldmatrix.sync.aligned.m8n8.x2.trans.shared.b16 {%0,%1}, [%2];" : "=r"(r[0]), "=r"(r[1]) : "r"(a) : "memory"); }
__device__ __forceinline__ void stsm4t(uint32_t a, uint32_t r0, uint32_t r1, uint32_t r2, uint32_t r3) { asm volatile("stmatrix.sync.aligned.m8n8.x4.trans.shared.b16 [%0], {%1,%2,%3,%4};" ::"r"(a), "r"(r0), "r"(r1), "r"(r2), "r"(r3) : "memory"); }
__device__ __forceinline__ void stsm2t(uint32_t a, uint32_t r0, uint32_t r1) { asm volatile("stmatrix.sync.aligned.m8n8.x2.trans.shared.b16 [%0], {%1,%2};" ::"r"(a), "r"(r0), "r"(r1) : "memory"); }
__device__ __forceinline__ void mma16(float* d, const uint32_t* a, uint32_t b0, uint32_t b1) {
    asm("mma.sync.aligned.m16n8k16.row.col.f32.bf16.bf16.f32 {%0,%1,%2,%3}, {%4,%5,%6,%7}, {%8,%9}, {%0,%1,%2,%3};"
        : "+f"(d[0]), "+f"(d[1]), "+f"(d[2]), "+f"(d[3]) : "r"(a[0]), "r"(a[1]), "r"(a[2]), "r"(a[3]), "r"(b0), "r"(b1));
}
__device__ __forceinline__ void mma8(float* d, uint32_t a0, uint32_t a1, uint32_t b0) {
    asm("mma.sync.aligned.m16n8k8.row.col.f32.bf16.bf16.f32 {%0,%1,%2,%3}, {%4,%5}, {%6}, {%0,%1,%2,%3};"
        : "+f"(d[0]), "+f"(d[1]), "+f"(d[2]), "+f"(d[3]) : "r"(a0), "r"(a1), "r"(b0));
}
__device__ __forceinline__ void mma16z(float* d, const uint32_t* a, uint32_t b0, uint32_t b1) {
    asm("mma.sync.aligned.m16n8k16.row.col.f32.bf16.bf16.f32 {%0,%1,%2,%3}, {%4,%5,%6,%7}, {%8,%9}, {%10,%10,%10,%10};"
        : "=f"(d[0]), "=f"(d[1]), "=f"(d[2]), "=f"(d[3]) : "r"(a[0]), "r"(a[1]), "r"(a[2]), "r"(a[3]), "r"(b0), "r"(b1), "f"(0.f));
}
__device__ __forceinline__ uint32_t pack(float lo, float hi) { uint32_t r; asm("cvt.rn.bf16x2.f32 %0, %1, %2;" : "=r"(r) : "f"(hi), "f"(lo)); return r; }
__device__ __forceinline__ uint32_t hmul(uint32_t a, uint32_t b) { uint32_t r; asm("mul.rn.bf16x2 %0, %1, %2;" : "=r"(r) : "r"(a), "r"(b)); return r; }
__device__ __forceinline__ uint32_t hfma(uint32_t a, uint32_t b, uint32_t c) { uint32_t r; asm("fma.rn.bf16x2 %0, %1, %2, %3;" : "=r"(r) : "r"(a), "r"(b), "r"(c)); return r; }
__device__ __forceinline__ uint4 lds128(uint32_t a) { uint4 v; asm volatile("ld.shared.v4.u32 {%0,%1,%2,%3}, [%4];" : "=r"(v.x), "=r"(v.y), "=r"(v.z), "=r"(v.w) : "r"(a) : "memory"); return v; }
__device__ __forceinline__ void sts128(uint32_t a, uint4 v) { asm volatile("st.shared.v4.u32 [%0], {%1,%2,%3,%4};" ::"r"(a), "r"(v.x), "r"(v.y), "r"(v.z), "r"(v.w) : "memory"); }
__device__ __forceinline__ int lds32(uint32_t a) { int v; asm volatile("ld.shared.u32 %0, [%1];" : "=r"(v) : "r"(a) : "memory"); return v; }
__device__ __forceinline__ void sts32(uint32_t a, int v) { asm volatile("st.shared.u32 [%0], %1;" ::"r"(a), "r"(v) : "memory"); }
__device__ __forceinline__ int atoms_add(uint32_t a, int v) { int r; asm volatile("atom.shared.add.u32 %0, [%1], %2;" : "=r"(r) : "r"(a), "r"(v) : "memory"); return r; }
__device__ __forceinline__ uint32_t ld_rlx(const void* p) { uint32_t v; asm volatile("ld.relaxed.gpu.global.u32 %0, [%1];" : "=r"(v) : "l"(p) : "memory"); return v; }
__device__ __forceinline__ void st_rlx(void* p, uint32_t v) { asm volatile("st.relaxed.gpu.global.u32 [%0], %1;" ::"l"(p), "r"(v) : "memory"); }
__device__ __forceinline__ void bulk(uint32_t dst, const void* g, int n, uint32_t bar) {
    asm volatile("cp.async.bulk.shared::cluster.global.mbarrier::complete_tx::bytes [%0], [%1], %2, [%3];" ::"r"(dst), "l"(g), "r"(n), "r"(bar) : "memory");
}
__device__ __forceinline__ void bulk_st(void* g, uint32_t src, int n) {
    asm volatile("cp.async.bulk.global.shared::cta.bulk_group [%0], [%1], %2;\ncp.async.bulk.commit_group;" ::"l"(g), "r"(src), "r"(n) : "memory");
}
__device__ __forceinline__ uint2 lds64(uint32_t a) { uint2 v; asm volatile("ld.shared.v2.u32 {%0,%1}, [%2];" : "=r"(v.x), "=r"(v.y) : "r"(a) : "memory"); return v; }
__device__ __forceinline__ void sts64(uint32_t a, uint32_t x, uint32_t y) { asm volatile("st.shared.v2.u32 [%0], {%1,%2};" ::"r"(a), "r"(x), "r"(y) : "memory"); }
__device__ __forceinline__ void tma3d(uint32_t dst, const CUtensorMap* m, int c1, int c2, uint32_t bar) {
    asm volatile("cp.async.bulk.tensor.3d.shared::cluster.global.mbarrier::complete_tx::bytes [%0], [%1, {0, %3, %4}], [%2];"
                 ::"r"(dst), "l"(m), "r"(bar), "r"(c1), "r"(c2) : "memory");
}
__device__ __forceinline__ void pf_l2(const void* g, int n) {
    asm volatile("{.reg .pred p; setp.gt.s32 p, %1, 0; @p cp.async.bulk.prefetch.L2.global [%0], %1;}" ::"l"(g), "r"(n) : "memory");
}
__device__ __forceinline__ void fence_async() { asm volatile("fence.proxy.async.shared::cta;" ::: "memory"); }
__device__ __forceinline__ uint64_t madw(uint32_t a, uint32_t b, uint64_t c) { uint64_t r; asm("mad.wide.u32 %0, %1, %2, %3;" : "=l"(r) : "r"(a), "r"(b), "l"(c)); return r; }
__device__ __forceinline__ uint32_t lop_sel(uint32_t a, uint32_t b, uint32_t m) { uint32_t r; asm("lop3.b32 %0, %1, %2, %3, 0xd8;" : "=r"(r) : "r"(a), "r"(b), "r"(m)); return r; }
__device__ __forceinline__ uint32_t opaque(uint32_t v, int lane) { return __shfl_sync(0xffffffffu, v, lane); }
__device__ __forceinline__ void bar_sync(int id, int n) { asm volatile("bar.sync %0, %1;" ::"r"(id), "r"(n) : "memory"); }

__device__ __forceinline__ void wg_rs16(float* d, const uint32_t* a, uint64_t db, int sc) {
    asm volatile("{.reg .pred p; setp.ne.b32 p, %13, 0;\n"
                 "wgmma.mma_async.sync.aligned.m64n16k16.f32.bf16.bf16 {%0,%1,%2,%3,%4,%5,%6,%7}, {%8,%9,%10,%11}, %12, p, 1, 1, 0;}"
                 : "+f"(d[0]), "+f"(d[1]), "+f"(d[2]), "+f"(d[3]), "+f"(d[4]), "+f"(d[5]), "+f"(d[6]), "+f"(d[7])
                 : "r"(a[0]), "r"(a[1]), "r"(a[2]), "r"(a[3]), "l"(db), "r"(sc));
}
__device__ __forceinline__ void wg_rs48(float* d, const uint32_t* a, uint64_t db, int sc) {
    asm volatile("{.reg .pred p; setp.ne.b32 p, %29, 0;\n"
                 "wgmma.mma_async.sync.aligned.m64n48k16.f32.bf16.bf16 {%0,%1,%2,%3,%4,%5,%6,%7,%8,%9,%10,%11,%12,%13,%14,%15,%16,%17,%18,%19,%20,%21,%22,%23}, {%24,%25,%26,%27}, %28, p, 1, 1, 0;}"
                 : "+f"(d[0]), "+f"(d[1]), "+f"(d[2]), "+f"(d[3]), "+f"(d[4]), "+f"(d[5]), "+f"(d[6]), "+f"(d[7]),
                   "+f"(d[8]), "+f"(d[9]), "+f"(d[10]), "+f"(d[11]), "+f"(d[12]), "+f"(d[13]), "+f"(d[14]), "+f"(d[15]),
                   "+f"(d[16]), "+f"(d[17]), "+f"(d[18]), "+f"(d[19]), "+f"(d[20]), "+f"(d[21]), "+f"(d[22]), "+f"(d[23])
                 : "r"(a[0]), "r"(a[1]), "r"(a[2]), "r"(a[3]), "l"(db), "r"(sc));
}
__device__ __forceinline__ void wg_ss48(float* d, uint64_t da, uint64_t db, int sc) {
    asm volatile("{.reg .pred p; setp.ne.b32 p, %26, 0;\n"
                 "wgmma.mma_async.sync.aligned.m64n48k16.f32.bf16.bf16 {%0,%1,%2,%3,%4,%5,%6,%7,%8,%9,%10,%11,%12,%13,%14,%15,%16,%17,%18,%19,%20,%21,%22,%23}, %24, %25, p, 1, 1, 1, 0;}"
                 : "+f"(d[0]), "+f"(d[1]), "+f"(d[2]), "+f"(d[3]), "+f"(d[4]), "+f"(d[5]), "+f"(d[6]), "+f"(d[7]),
                   "+f"(d[8]), "+f"(d[9]), "+f"(d[10]), "+f"(d[11]), "+f"(d[12]), "+f"(d[13]), "+f"(d[14]), "+f"(d[15]),
                   "+f"(d[16]), "+f"(d[17]), "+f"(d[18]), "+f"(d[19]), "+f"(d[20]), "+f"(d[21]), "+f"(d[22]), "+f"(d[23])
                 : "l"(da), "l"(db), "r"(sc));
}

__device__ __forceinline__ int warp_incl(int v) {
#pragma unroll
    for (int o = 1; o < 32; o <<= 1)
        asm volatile("{.reg .pred p; .reg .b32 u; shfl.sync.up.b32 u|p, %0, %1, 0, 0xffffffff; @p add.s32 %0, %0, u;}" : "+r"(v) : "r"(o));
    return v;
}
__device__ __forceinline__ void ldg128(uint32_t* r, const void* p, bool on) {
    asm volatile("{.reg .pred p; setp.ne.u32 p, %5, 0; @p ld.global.nc.v4.u32 {%0,%1,%2,%3}, [%4];}"
                 : "=r"(r[0]), "=r"(r[1]), "=r"(r[2]), "=r"(r[3]) : "l"(p), "r"((uint32_t)on));
}

template <int V> struct IC { static constexpr int value = V; };
template <int N, int I = 0, class Fn> __device__ __forceinline__ void static_for(Fn f) { if constexpr (I < N) { f(IC<I>{}); static_for<N, I + 1>(f); } }

struct Acc {
    uint32_t p[5][MA ? 2 : 4];
    float t01[4], m[3][4];
};

#define LF(m) if (H) ldsm2t(f[m], so + xa + m * 256); else ldsm4t(f[m], so + xa + m * 256)
#define LY() ldsm4(yb, so + ya)
#define LC() ldsm4(yb + 4, so + yc)
#define LN() ph = lds32(so + S_N)
#define ADV() { if (F && ALT) asm volatile("{.reg .pred p; setp.ne.and.u32 p, %1, 0, lane0; @p mbarrier.arrive.shared::cta.b64 _, [%0];}" ::"r"(so + S_EMPTY), "r"(room) : "memory"); \
                else asm volatile("@lane0 mbarrier.arrive.shared::cta.b64 _, [%0];" ::"r"(so + S_EMPTY) : "memory"); \
                so = so == sm + O_RING + (NSLOT - 1) * SLOT ? sm + O_RING : so + SLOT; }
#define LA() asm volatile("{\n.reg .pred p, q;\n.reg .b64 s;\n.reg .f32 n;\nmov.b64 s, {0, %7};\nmbarrier.test_wait.shared::cta.b64 p, [%6], s;\n" \
                          "abs.f32 n, %7;\nsetp.gt.and.f32 q, n, 0f00000003, p;\nselp.u32 %4, 1, 0, p;\nselp.u32 %5, 1, 0, q;\n" \
                          "@p ldmatrix.sync.aligned.m8n8.x4.shared.b16 {%0,%1,%2,%3}, [%8];\n}" \
                          : "+r"(a[0]), "+r"(a[1]), "+r"(a[2]), "+r"(a[3]), "=r"(ok), "=r"(go) : "r"(so + S_FULL), "r"(ph), "r"(so + aa) : "memory")
#define RAD(p, s) if (!H || !s) { float c[4]; mma16z(c, wr[p], a[2 * s], a[2 * s + 1]); R[p][2 * s] = pack(c[0], c[1]); R[p][2 * s + 1] = pack(c[2], c[3]); }
#define MUL(n, x, y) (XS >> n & 1 ? hmul(y, x) : hmul(x, y))
#define FMA(n, x, y, z) (XS >> n & 1 ? hfma(y, x, z) : hfma(x, y, z))
#define ON(i) if (!H || i < 2)
#define AI(i) ((i ^ XA) & (MA ? 1 : 3))
#define ACC(n, m, i, x, y, z) ON(i) { z[AI(i)] = F && !(seen >> (4 * m + AI(i)) & 1) ? MUL(n, x, y) : FMA(n, x, y, z[AI(i)]); seen |= 1 << (4 * m + AI(i)); }
#define P00(i) ACC(0, 3, i, f[0][i], R[0][i], A.p[3])
#define P10(k, i) ACC(1, k, i, f[1 + k][i], R[3][i], A.p[k])
#define S0(k, i) ON(i) sd[i] = MUL(2, f[1 + k][i], yb[2 * k + (i >> 1)])
#define SD(k, i) ON(i) sd[i] = FMA(2, f[1 + k][i], yb[2 * k + (i >> 1)], sd[i])
#define P110(i) ACC(3, 4, i, sd[i], R[1][i], A.p[4])
#define TU(i) ON(i) u[3][i ^ XU] = MUL(4, f[0][i], R[2][i])
#define EM(d, u) if (F) mma16z(d, u, yb[6], yb[7]); else if (H) mma8(d, u[0], u[1], yb[6]); else mma16(d, u, yb[6], yb[7])
#define TM() EM(A.t01, u[3])
#define MU(k, i) ON(i) u[k][i ^ XU] = MUL(5, f[1 + k][i], R[4][i])
#define MM(k) EM(A.m[k], u[k])
#define PK(v, h) pack(v[2 * (h)], v[2 * (h) + 1])
#define LM() { sts32(na + (sof + sm + O_NODE), mt); asm volatile("ld.shared.u16 %0, [%1];" : "=r"(mt) : "r"(na + (so + S_C + 48)) : "memory"); }
#define MP(k) PK(A.m[k], XA ^ XU), PK(A.m[k], 1 ^ XA ^ XU)
#define FY(k) if (k == 0) mma16z(y, A.p[0], oh[0], oh[1]); else if (k > 1 && !(seen >> 30)) { mma16(y, A.p[2], oh[2], oh[3]); seen |= 1 << 30; }
#define FZ(k) if (k == 0) { const uint32_t mp[4] = {A.p[4][0], A.p[4][1], MP(2)}; mma16z(z, mp, oh[4], eb[2]); } \
              else if (k == 1) { const uint32_t mp[4] = {MP(0), MP(1)}; mma16(z, mp, eb[0], eb[1]); }
#define SX() stsm2t(fx + sof, PK(A.t01, XU), PK(A.t01, 1 ^ XU))
#define SY() stsm4t(fyz + sof, PK(y, XA), PK(y, 1 ^ XA), PK(z, XA), PK(z, 1 ^ XA))
#define G0(k) wg_rs16(d0, w0[k], db + ((((k) & 7) * PW + (((k) >> 3) ? P_0P1 : P_0P0)) >> 4), k)
#define G1(i) { constexpr int k_ = RSL ? ((i) + KR) % 24 : (i); const uint64_t bk = db + (((k_ & 7) * PW + ((k_ >> 3) == 0 ? P_1P0 : (k_ >> 3) == 1 ? P_1P1 : P_1P2)) >> 4); \
                if (k_ < KR) wg_rs48(d1, w1[k_ % KR], bk, i); else wg_ss48(d1, (da + (k_ - KR) / 2 * 512 + (k_ & 1) * 128) | (64ull << 32) | (1ull << 62), bk, i); }
#define X4(op) op(0); op(1); op(2); op(3)
#define Y4(op, k) op(k, 0); op(k, 1); op(k, 2); op(k, 3)
#define XA 1
#define XU 0
#define XS_R 63
#define SEQ_R LF(2); LN(); RAD(1,0); RAD(1,1); LC(); LY(); RAD(2,0); RAD(2,1); RAD(4,0); RAD(4,1); RAD(3,0); RAD(3,1); LF(3); LF(0); P10(1,1); \
    P10(1,0); P10(1,3); P10(1,2); S0(2,3); S0(2,2); S0(2,1); S0(2,0); RAD(0,1); RAD(0,0); P00(2); MU(2,0); MU(2,2); MU(2,1); MU(2,3); MM(2); MU(1,3); \
    P00(3); MU(1,2); LF(1); ADV(); LA(); P10(0,0); P10(0,1); P10(0,2); P10(0,3); SD(0,0); SD(0,2); SD(0,1); SD(0,3); SD(1,0); P110(0); SD(1,2); \
    P110(2); SD(1,1); P110(1); SD(1,3); P110(3); P00(0); MU(0,0); TU(0); TU(2); MU(1,1); TU(3); TU(1); TM(); P00(1); MU(0,2); MU(1,0); MM(1); MU(0,1); \
    MU(0,3); MM(0); P10(2,0); P10(2,2); P10(2,3); P10(2,1);
#define XS_H XS_R
#define SEQ_H SEQ_R
#define XS_F 0
#define SEQ_F LN(); LF(2); LY(); LF(1); LM(); RAD(2,0); RAD(2,1); LF(3); RAD(0,1); RAD(3,0); RAD(0,0); LC(); RAD(3,1); RAD(1,0); FZ(0); LF(0); \
    RAD(4,0); FY(0); FY(1); FZ(1); RAD(4,1); TU(0); MU(1,1); MU(1,0); MU(1,3); MU(1,2); TU(2); SX(); TU(1); TU(3); TM(); RAD(1,1); MM(1); ADV(); LA(); \
    FZ(2); P10(1,1); FY(3); P10(1,0); P10(1,3); S0(2,0); SD(0,0); SD(1,0); P10(1,2); P110(0); S0(2,2); SD(0,2); SD(1,2); P110(2); MU(2,1); MU(2,0); \
    MU(2,3); MU(2,2); MM(2); S0(2,3); SD(0,3); SD(1,3); P110(3); P00(0); MU(0,0); FY(2); SY(); P10(2,2); P10(2,3); P10(2,0); P10(2,1); S0(2,1); \
    SD(0,1); SD(1,1); P110(1); P00(1); MU(0,1); P00(2); MU(0,2); P10(0,3); P10(0,2); P10(0,1); P10(0,0); P00(3); MU(0,3); MM(0);

__global__ void __launch_bounds__(NT, 1)
tp_kernel(const int4* __restrict__ dst, const int4* __restrict__ src, const char* __restrict__ rhat, Scratch* __restrict__ gs,
          const char* __restrict__ x, const char* __restrict__ ea, const __nv_bfloat16* __restrict__ eps, char* __restrict__ out,
          const __grid_constant__ CUtensorMap m_wr, const __grid_constant__ CUtensorMap m_w0, const __grid_constant__ CUtensorMap m_w1,
          const __grid_constant__ CUtensorMap m_x) {
    extern __shared__ __align__(1024) char smem_raw[];
    constexpr uint32_t sm = 1024;
    spin_check((uint32_t)__cvta_generic_to_shared(smem_raw) == sm ? 0 : 2 * SPIN_LIMIT);
    int t;
    asm volatile("mov.u32 %0, %%tid.x;" : "=r"(t));
    const int w = t >> 5, lane = t & 31, b = blockIdx.x;

    const int g = lane >> 2, q = lane & 3, mat = lane >> 3, r = lane & 7;
    const int e0 = b * CH + t * 8, ne = min(CH, NE - b * CH);
    const bool act = t * 8 < ne;
    uint32_t d[8];
#pragma unroll
    for (int k = 0; k < 2; k++) ldg128(d + 4 * k, dst + e0 / 4 + k, act);
    uint32_t tag = ld_rlx(&gs->epoch[b * 32]), epl;
    asm volatile("ld.global.nc.u16 %0, [%1];" : "=r"(epl) : "l"(eps + min(lane, 26)));
    if (t < 60) sts128(sm + O_BCNT + 16 * t, make_uint4(0, 0, 0, 0));
    if (t == NT - 1) {
#pragma unroll
        for (int i = 0; i < 5; i++) mbar_init(sm + O_WBA + 8 * i, 1);
        fence_async();
        mbar_expect(sm + O_WBC, ne * 10); mbar_expect(sm + O_WBA, 20480); mbar_expect(sm + O_WBB, NB1 * 8192); mbar_expect(sm + O_WBD, 65536 + KR * 4096);
        mbar_expect(sm + O_WBE, (((TP & 15) != 15) + ((TP >> 4 & 15) != 15) + ((TP >> 8 & 15) != 15) + ((TP >> 12) != 15)) * (NLOC / 4 * 128));
        WLD(6);
        spin_check(tag);
        bulk(sm + O_RH, rhat + b * (CH * 6), ne * 6, sm + O_WBC);
        bulk(sm + O_SRC, src + b * (CH / 4), ne * 4, sm + O_WBC);
        tma3d(sm + O_WR0, &m_wr, 0, 0, sm + O_WBA);
        tma3d(sm + O_WR1, &m_wr, 0, 5, sm + O_WBA);
        WLD(0);
    }
    if (t == 320) {
#pragma unroll
        for (int i = 0; i < NSLOT; i++) {
            sts128(sm + O_RING + i * SLOT + S_C + 64, make_uint4(0, 0, 0, 0));
            mbar_init(sm + O_RING + i * SLOT + S_FULL, 32); mbar_init(sm + O_RING + i * SLOT + S_EMPTY, 8);
        }
    }
#pragma unroll
    for (int k = 0; k < LZ; k++) sts128(sm + O_L + 16 * (t + k * NT), make_uint4(0, 0, 0, 0));
    if (t < 80) sts32(sm + O_NCNT + 4 * t, t <= NLOC ? 4 * t : 0);
    if (t < 68) sts32(sm + O_NODE + 4 * t, 0);
    uint32_t ba[8], rk[8];
    if (w < 10) bar_sync(1, 320);
    tag = (tag + 1) << 30;
    if (act) {
#pragma unroll
        for (int i = 0; i < 8; i++) {
            const uint32_t l = __umulhi(d[i], (uint32_t)((1ull << 32) / G + 1));
            ba[i] = d[i] * 4 - l * (4 * G);
            d[i] = l * 4 + (tag + ((e0 + i + 1) << 9) + 4);
            rk[i] = atoms_add(sm + O_BCNT + ba[i], 4);
        }
#pragma unroll
        for (int i = 0; i < 8; i++)
            asm volatile("{.reg .pred p; setp.lt.u32 p, %2, 124; @p st.shared.u32 [%0], %1;}"
                         ::"r"(sm + O_KT + ba[i] * 32 + ((ba[i] + rk[i]) & 127)), "r"(d[i]), "r"(rk[i]) : "memory");
    }
    TS(0);
    __syncthreads();
    {
        int v[5], sum = 0;
#pragma unroll
        for (int i = 0; i < 5; i++) { v[i] = lds32(sm + O_BCNT + 4 * (lane * 5 + i)); sum += v[i]; }
        int e = warp_incl(sum) - sum;
        if (w == 10) {
#pragma unroll
            for (int i = 0; i < 5; i++) {
                const int k = lane * 5 + i;
                if (k < G) sts32(sm + O_KT + k * 128 + ((k * 4 + 124) & 127), tag | v[i] << 10 | e >> 2);
                e += v[i];
            }
            __syncwarp();
            if (lane == 0) {
                fence_async();
                bulk_st(&gs->keys[b * (G * 32)], sm + O_KT, G * 128);
                WLD(5);
            }
        } else {
#pragma unroll
            for (int i = 0; i < 5; i++) { sts32(sm + O_BOFF + 4 * (lane * 5 + i), e); e += v[i]; }
        }
        __syncwarp();
    }
    TS(11);
    const uint32_t sw = (uint32_t)(((2 * (w & 3) + (mat & 1)) ^ r) * 16 + ((mat >> 1) * 8 + r) * 128);
    const uint32_t lo = (lane & 2) * 64 + (lane & 12) * 8 + (lane & 16) + (lane & 1) * 8;
    uint32_t wr[5][4];
    const uint32_t* kp = &gs->keys[(w * SEGW * G + b) * 32 + ((lane + b) & 31)];
    uint32_t kv[SEGW + 1], ho[SEGW + 1], nk[SEGW + 1], old;
    if (act) {
        uint32_t mx = 0;
#pragma unroll
        for (int i = 0; i < 8; i++) { mx = max(mx, rk[i]); ba[i] = rk[i] + lds32(sm + O_BOFF + ba[i]); }
        if (mx >= 124) {
#pragma unroll
            for (int i = 0; i < 8; i++)
                if (rk[i] >= 124) st_rlx(&gs->more[b * CH + (ba[i] >> 2)], d[i]);
        }
    }
#define WRP 0
    auto ldwr = [&]() {
    if (w < 8) {
        mbar_wait(sm + O_WBA, 0);
#pragma unroll
        for (int p = 0; p < 5; p++) {
            const int c = 2 * p + (w >> 2);
            ldsm4t(wr[p], sm + (c < 5 ? O_WR0 : O_WR1 - 5 * 2048) + c * 2048 + sw);
        }
    } else {
        const uint64_t xl = (uint64_t)(x - 1024 + r * 16) - (tag >> 6), al = (uint64_t)(ea - 32 + (lane & 1) * 16) - (tag >> 4);
        const uint64_t ml = (uint64_t)gs->list + lo;
        const uint32_t row = ((mat & 2 ? mat & 1 ? 0xa9c876b5u : 0xfe4d2130u : mat & 1 ? 0x76b821a3u : 0xc5bfe0cbu) >> 4 * r & 15) + (mat & 2) * 8;
        const uint32_t c[13] = {(uint32_t)xl, (uint32_t)(xl >> 32), (uint32_t)al, (uint32_t)(al >> 32), (uint32_t)ml, (uint32_t)(ml >> 32),
            mat * 2048u + (r ^ 2 * mat) * 16, mat * 2048u + 1024 + (r ^ 2 * mat ^ 1) * 16,
            S_A + (lane & 2) * 128u + g * 32 + ((lane ^ lane >> 4) & 1) * 16, S_C + row * 16, lane & 1 ? 16u : 9u, lane & 30u,
            lane == 4 ? 0xffff0000u : 0u};
#pragma unroll
        for (int i = 0; i < 20; i++) wr[i >> 2][i & 3] = i < 13 ? opaque(c[i % 13], lane) : 0;
    }
    };
    if (!WRP) ldwr();
    TS(21);
    mbar_wait(sm + O_WBC, 0);
    TS(22);
    if (act) {
        uint32_t s[8], y[12];
#pragma unroll
        for (int k = 0; k < 3; k++) *(uint4*)&y[4 * k] = lds128(sm + O_RH + t * 48 + k * 16);
#pragma unroll
        for (int k = 0; k < 2; k++) *(uint4*)&s[4 * k] = lds128(sm + O_SRC + t * 32 + k * 16);
#pragma unroll
        for (int i = 0; i < 8; i++) {
            const int k = 3 * i / 2;
            sts64(sm + O_OUT + ba[i] * 2, __byte_perm(y[k], s[i] + (tag >> 16) + 1, i & 1 ? 0x5432 : 0x5410),
                  i & 1 ? y[k + 1] : __byte_perm(y[k], y[k + 1], 0x5432));
        }
    }
    TS(12);
    __syncthreads();
    if (t == 352) { fence_async(); bulk_st(&gs->vals[b * CH], sm + O_OUT, ne * 8); WLD(7); }
    if (WRP) ldwr();

    const uint32_t am = lane < 31 ? 511 : 0, none = tag | (320 + 4 * lane);
    auto check = [&]() {
        old = 0;
#pragma unroll
        for (int j = 0; j < SEGW; j++) {
            ho[j] = __shfl_sync(0xffffffffu, kv[j], 31);
            kv[j] = ho[j] >= (lane < 31 ? tag + ((lane + 1) << 12) : 0u) ? kv[j] : none;
            old |= kv[j] ^ tag;
        }
        return __any_sync(0xffffffffu, old >> 30);
    };
#pragma unroll
    for (int j = 0; j < SEGW; j++) kv[j] = ld_rlx(kp + j * (G * 32));
    TS(1);
    if (t == 352) WLD(1);
    TV(19, 0); TV(23, 0);
    for (int it = 0; check(); it++) {
        spin_check(it);
        if (it == 0) TS(20);
        TV(19, (it + 1) * 100);
#pragma unroll
        for (int j = 0; j < SEGW; j++)
            if (__any_sync(0xffffffffu, (kv[j] ^ tag) >> 30)) kv[j] = ld_rlx(kp + j * (G * 32));
    }
    TS(3);
    if (t == 352) WLD(2);
    kv[SEGW] = none; ho[SEGW] = 0;
    bool slow = false;
    const bool more = __any_sync(0xffffffffu, lane == 31 && (old & 0xfe0000));
    if (more) {
        int c = lane;
#pragma unroll
        for (int j = 0; j < SEGW; j++) {
            const int n = max((int)(ho[j] >> 12 & 0xfff) - 31, 0);
            if ((unsigned)c < (unsigned)n) ho[SEGW] = j * CH + (ho[j] & 0xfff) + 31 + c - lane;
            c -= n;
        }
        slow = lane == 31 && c < 0;
        if (c < 0 && lane < 31)
            for (int it = 0; ((kv[SEGW] = ld_rlx(&gs->more[w * SEGW * CH + lane + ho[SEGW]])) ^ tag) >> 30; it++) spin_check(it);
        __syncwarp();
    }
#define EV 0
    uint32_t na_[SEGW + 1];
    uint64_t vp = (uint64_t)&gs->vals[w * SEGW * CH + lane], vv[SEGW + 1];
#pragma unroll
    for (int j = 0; j <= SEGW; j++) vv[j] = tag;
    auto ldv = [&](bool again) {
#pragma unroll
        for (int j = 0; j <= SEGW; j++)
            asm volatile("{.reg .pred p; setp.lt.u32 p, %2, 320; @p ld.relaxed.gpu.global.b64 %0, [%1];}" : "+l"(vv[j])
                         : "l"(madw(j < SEGW ? ho[j] & 0xfff : ho[j], 8, vp) + (j < SEGW ? j * CH * 8 : 0)),
                           "r"(again ? (((uint32_t)vv[j] ^ tag) >> 30 ? 0 : 320) : na_[j]) : "memory");
    };
#pragma unroll
    for (int j = 0; j <= SEGW; j++) na_[j] = (kv[j] & am) | (none & 511 & ~am);
    if (EV == 4) ldv(false);
#pragma unroll
    for (int j = 0; j <= SEGW; j++) nk[j] = atoms_add(sm + O_NCNT + na_[j], 512);
    if (EV == 3) ldv(false);
    auto visit = [&](auto f) {
#pragma unroll 1
        for (int j = 0; j < SEGW; j++) {
            const uint32_t* kl = &gs->keys[((w * SEGW + j) * G + b) * 32];
            const uint32_t h = ld_rlx(kl + ((31 + b) & 31));
#pragma unroll 1
            for (int i = lane; i < (h >> 12 & 0xfff); i += 32) {
                const int o = (w * SEGW + j) * CH + (h & 0xfff) + i;
                uint32_t k;
                int it = 0;
                do { k = ld_rlx(i < 31 ? kl + ((i + b) & 31) : &gs->more[o]); spin_check(it++); } while ((k ^ tag) >> 30);
                f(k, o, i);
            }
        }
    };
    slow = __syncthreads_or(slow);
    if (slow) {
        if (t < 80) sts32(sm + O_NCNT + 4 * t, t <= NLOC ? 4 * t : 0);
        __syncthreads();
        visit([&](uint32_t k, int, int) { atoms_add(sm + O_NCNT + (k & 511), 512); });
        __syncthreads();
    }
    TS(4);
    if (t == 352) WLD(3);
    if (EV == 2) ldv(false);
    if (w < 10) {
        const uint32_t key = lds32(sm + O_NCNT + 4 + (t & ~3));
        uint4 k[5];
#pragma unroll
        for (int i = 0; i < 5; i++) k[i] = lds128(sm + O_NCNT + q * 80 + i * 16);
        uint32_t c[4] = {0, 0, 0, 0};
#pragma unroll
        for (int i = 0; i < 5; i++) { c[0] += (key - k[i].x) >> 31; c[1] += (key - k[i].y) >> 31; c[2] += (key - k[i].z) >> 31; c[3] += (key - k[i].w) >> 31; }
        int rank = c[0] + c[1] + c[2] + c[3];
        rank += __shfl_xor_sync(0xffffffffu, rank, 1);
        rank += __shfl_xor_sync(0xffffffffu, rank, 2);
        if (ASC && rank < 2 * NPRIV) rank = (2 * NPRIV - 1 - rank) ^ 1;
        if (t < NLOC * 4) sts32(sm + O_SORT + 4 * rank, key);
    }
    if (EV == 5) ldv(false);
    __syncthreads();
    TS(2);
    const bool on = lane < NLOC / 4;
    const uint4 k4 = lds128(sm + O_SORT + 16 * (on ? lane : 0));
    if (EV == 1) ldv(false);
    const uint32_t ks[4] = {k4.x, k4.y, k4.z, k4.w};
    const int n0 = on ? max(1u, (ks[0] + 3584) >> 12) : 0, n1 = on ? max(1u, (ks[2] + 3584) >> 12) : 0;
    const int u2 = warp_incl(n0 + n1), u1 = u2 - n1, u0 = u1 - n0;
    const int total = __shfl_sync(0xffffffffu, u2, 31);
    slow |= total > CAPT;
    const int m0 = slow ? n0 : HT ? max(2u, (ks[0] + 1536) >> 11) : 2 * n0, m1 = slow ? n1 : HT ? max(2u, (ks[2] + 1536) >> 11) : 2 * n1;
    int gbase = b * CAPT + 1;
    if (on) {
#pragma unroll
        for (int i = 0; i < 4; i++) {
            const int a = ks[i] & 511, node = a * (G / 4) - G + b, o = (i >> 1 ? u1 : u0) * 256 + (i & 1) * 16;
            const uint32_t mk = (node < NN ? node + 1 : 0) + ((i >> 1 ? m1 : m0) << 16);
            sts64(sm + O_NOFF + 2 * a, o - (a >> 4), mk + a * 32);
            if (!slow && ks[i] < 512) sts32(sm + O_L + 4 + o, mk);
        }
    }
    __syncwarp();
    if (t == 352) WLD(8);
    if (!slow) {
        uint32_t mk[SEGW + 1];
        TS(13);
        if (t == 352) { asm volatile("cp.async.bulk.wait_group.read 0;" ::: "memory"); }
        if (EV == 0) ldv(false);
        if (t == 352) WLD(4);
        TS(16);
#pragma unroll
        for (int j = 0; j <= SEGW; j++) {
            const uint2 o = lds64(sm + O_NOFF + 2 * na_[j]);
            mk[j] = o.y - nk[j] * 32; nk[j] = o.x + (nk[j] >> 4);
        }
        for (int it = 0;; it++) {
            old = 0;
#pragma unroll
            for (int j = 0; j <= SEGW; j++) old |= (uint32_t)vv[j] ^ tag;
            if (!__any_sync(0xffffffffu, old >> 30)) break;
            spin_check(it);
            vp = __shfl_sync(0xffffffffu, vp, lane);
            ldv(true);
            TV(23, (it + 1) * 100);
        }
        TS(17);
#pragma unroll
        for (int j = 0; j <= SEGW; j++)
            asm volatile("{.reg .pred p; setp.ne.u32 p, %3, %5; @p st.shared.v4.u32 [%0], {%1,%2,%3,%4};}"
                         ::"r"(sm + O_L + nk[j]), "r"(kv[j]), "r"(mk[j]), "r"((uint32_t)vv[j]), "r"((uint32_t)(vv[j] >> 32)), "r"(tag) : "memory");
        TS(18);
        if (na_[SEGW] < 320) gs->more[w * SEGW * CH + lane + ho[SEGW]] = 0;
    } else {
        int so = 0;
        if (t == 352) WLD(4);
#pragma unroll
        for (int j = 0; j < SEGW; j++) so += ho[j] & 0xfff;
        if (lane == 0) atoms_add(sm + O_SUM, so);
        if (t == 352) asm volatile("cp.async.bulk.wait_group.read 0;" ::: "memory");
        __syncthreads();
        gbase = TBIG + (lds32(sm + O_SUM) >> 3) + (NLOC + 5) * b;
        auto put = [&](uint32_t k, uint64_t e, uint32_t a, int rank) {
            const uint2 o = lds64(sm + O_NOFF + 2 * a);
            const uint32_t m = o.y - a * 32 - (rank << 13);
            gs->list[gbase * 16 + ((o.x + (a >> 4)) >> 4) + rank * 2] = make_uint4(k, (m & 0xffff) | min(m >> 16, 0x7fffu) << 17, e, e >> 32);
        };
        visit([&](uint32_t k, int o, int i) {
            uint64_t e;
            int it = 0;
            do {
                asm volatile("ld.relaxed.gpu.global.b64 %0, [%1];" : "=l"(e) : "l"(&gs->vals[o]) : "memory");
                spin_check(it++);
            } while (((uint32_t)e ^ tag) >> 30);
            if (i >= 31) gs->more[o] = 0;
            put(k, e, k & 511, atoms_add(sm + O_NCUR + (k & 511), 1));
        });
#pragma unroll 1
        for (int i = 0; i < 4; i++) {
            const uint32_t k = i == 0 ? ks[0] : i == 1 ? ks[1] : i == 2 ? ks[2] : ks[3];
#pragma unroll 1
            for (int p = (k >> 9) + w; p < (i >> 1 ? n1 : n0) * 8; p += NT / 32) put(0, 0, k & 511, p);
        }
        __threadfence();
    }
    if (t == 352) WLD(9);
    const uint32_t iw0 = (gbase + u0) << 12 | n0, iw1 = (gbase + u1) << 12 | n1;
    __syncthreads();
    TS(5);

    if (w >= 8) {
        asm volatile("setmaxnreg.dec.sync.aligned.u32 " STR(PREG) ";");
        const int h = __reduce_max_sync(0xffffffffu, w & 3);
        if (h == 0) TSW(28);
        gbase = __reduce_min_sync(0xffffffffu, iw0) >> 12;
        int pos = gbase + h, end = __reduce_max_sync(0xffffffffu, lane == NPRIV / 2 ? (NPRIV & 1 ? iw1 : iw0) : 0) >> 12;
        const int bytes = gbase < TBIG ? ((__reduce_max_sync(0xffffffffu, iw0) >> 12) - gbase) * 256 : 0;
        const uint32_t ring = sm + O_RING;
        const uint64_t xl = wr[0][0] | (uint64_t)wr[0][1] << 32, al = wr[0][2] | (uint64_t)wr[0][3] << 32, ml = wr[1][0] | (uint64_t)wr[1][1] << 32;
        const uint32_t xoff[2] = {wr[1][2], wr[1][3]}, aoff = wr[2][0], coff = wr[2][1], sh = wr[2][2], ial = wr[2][3], sel = wr[3][0];
        auto lde = [&](uint2& e, int p) {
            asm volatile("{.reg .pred p; setp.gt.s32 p, %3, 0; @p ld.relaxed.gpu.global.v2.u32 {%0,%1}, [%2];}" : "+r"(e.x), "+r"(e.y) : "l"(madw(p, 256, ml)), "r"(p) : "memory");
        };
        uint2 e0[3] = {};
#pragma unroll
        for (int k = 0; k < 3; k++) {
            e0[k] = lds64(sm + O_L + k * 1024 + h * 256 + ((uint32_t)ml & 255));
            lde(e0[k], bytes ? 0 : pos + 4 * k);
        }
        if (h == 3) fence_async();
        else if (B4) asm volatile("bar.arrive 4, %0;" ::"n"(NT) : "memory");
        pos += 4;

        int ev = 0, state = -2, tk = 0, nr = 0;
        uint32_t inf = 0;
        int ii = 0;
        auto take = [&]() {
            int v = 0;
            asm volatile("{.reg .pred p; setp.eq.s32 p, %2, 0; @p atom.relaxed.gpu.global.add.u32 %0, [%1], 1;}" : "+r"(v) : "l"(&gs->ticket), "r"(lane) : "memory");
            return v;
        };
        auto resolve = [&]() {
            const int k = __reduce_max_sync(0xffffffffu, tk);
            inf = tag;
            if (k < G * NPOOL) { const int l = k / G; ii = (k - l * G) * NPOOL + l; inf = ld_rlx(&gs->info[ii]);
                const int j = NPRIV + 1 + nr + (STAG), gd = __reduce_max_sync(0xffffffffu, lds32(sm + O_SUM + 4));
                tk = (QOK) && (j & ~7) > gd + GM && k >= G * NPOOL - (j & 7 ? THETB : THETA) ? G * NPOOL : take(); }
        };
        uint32_t so = ring + h * SLOT, ph = 0x80000000u;
        uint32_t spins = 0;
        asm volatile(".reg .pred z<5>;");
#define HD 300
        { const uint32_t c0 = clock(); while (__any_sync(0xffffffffu, (uint32_t)clock() - c0 < h * HD)); }
        while (true) {
            const uint2 e = e0[0];
            const uint32_t o = e.x >> sh, id = __shfl_sync(0xffffffffu, o, ial);
            uint32_t s[4];
#pragma unroll
            for (int j = 0; j < 4; j++) s[j] = __shfl_sync(0xffffffffu, o, 2 * j + 1, 8);
            const uint32_t nx = so == ring + (NSLOT - 1) * SLOT ? ph : ph ^ 0x80000000u, ey = lop_sel(e.y, nx, sel);
            const uint32_t y0 = __shfl_xor_sync(0xffffffffu, e.x, 1), ym = lane & 1 ? e.y : y0;
            const bool full = __ballot_sync(0xffffffffu, e.y >> 16 != 1) & 1;
            const uint64_t ga = madw(id, 32, al);
            uint64_t gx[4];
#pragma unroll
            for (int j = 0; j < 4; j++) gx[j] = madw(s[j], 1024, xl);
            const uint32_t da = so + aoff, dx[2] = {so + xoff[0], so + xoff[1]}, dc = so + coff;
            asm volatile("setp.eq.u32 z0, %0, 0;\nsetp.eq.u32 z1, %1, 0;\nsetp.eq.u32 z2, %2, 0;\nsetp.eq.u32 z3, %3, 0;\nsetp.eq.u32 z4, %4, 0;\n"
                         ::"r"(NULLP(s[0])), "r"(NULLP(s[1])), "r"(NULLP(s[2])), "r"(NULLP(s[3])), "r"(id), "l"(ga), "r"(da), "r"(dx[0]), "r"(dx[1]), "r"(dc));
            lde(e0[0], state < 0 ? 0 : pos);
            if (HS == 2) asm volatile("{.reg .pred p; setp.eq.s32 p, %1, -2; @p bar.arrive 5, %0;}" ::"n"(NT), "r"(state) : "memory");
            if (h == 0 && state == -2) TSW(29);
            if (h == 0 && state == -1) TSW(30);
            asm volatile("{\n.reg .pred p;\n.reg .b64 s;\nmov.b64 s, {0, %2};\n"
                         "LOOP:\nmbarrier.try_wait.shared::cta.b64 p, [%1], s;\n@p bra DONE;\n"
                         "add.u32 %0, %0, 1;\nsetp.gt.u32 p, %0, %3;\n@p trap;\nbra LOOP;\nDONE:\n}"
                         : "+r"(spins) : "r"(so + S_EMPTY), "r"(ph), "n"(SPIN_LIMIT) : "memory");
            asm volatile("cp.async.cg.shared.global [%0], [%1], 16, z4;" ::"r"(da), "l"(ga) : "memory");
#define ROW(j) _Pragma("unroll") for (int k = 0; k < 8; k++) \
                asm volatile("cp.async.cg.shared.global [%0], [%1], 16, z" #j ";" ::"r"(dx[j >> 1] + (j & 1) * 8192 + k * 128), "l"(gx[j] + k * 128) : "memory")
            ROW(0); ROW(2);
            if (full) { ROW(1); ROW(3); }
            stsm4t(dc, e.x, ey, lane < 16 ? ym : 0, lane < 16 ? 0 : ym);
            asm volatile("cp.async.mbarrier.arrive.noinc.shared::cta.b64 [%0];" ::"r"(so + S_FULL) : "memory");
            const bool wrap = NSLOT == 5 ? so != ring : so >= ring + (NSLOT - 4) * SLOT;
            ph ^= wrap ? 0x80000000u : 0u;
            so = wrap ? so - (NSLOT - 4) * SLOT : so + 4 * SLOT;
            pos += 4;
            if (pos >= ev) {
                if (state < 0) {
                    e0[0] = e0[1]; e0[1] = e0[2];
                    if (state == -2) {
                        if (h == 0) TSW(24);
                        if (h == 3) TSW(25);
                        if (HS == 1) asm volatile("bar.arrive 5, %0;" ::"n"(NT) : "memory");
                        if (HS >= 4 && h == HS - 4) asm volatile("bar.arrive 5, 288;" ::: "memory");
                        if (h < 2) bar_sync(7, 320);
                        if (h == 3) bar_sync(4, NT);
                        if (h == 0) mbar_wait(sm + O_WBE, 0);
                        if (h == 3) {
                            if (lane == 0) {
                                if (bytes) bulk_st(gs->list + gbase * 16, sm + O_L, bytes);
                                asm volatile("cp.async.bulk.wait_group.read 0;" ::: "memory");
                            }
                            __syncwarp();
                            if (lane == 0) {
                                for (int j = 0; j < NB1; j++) tma3d(sm + O_W1 + j * 8192, &m_w1, KR * 16 + 32 * j, 0, sm + O_WBB);
                            }
                            __syncwarp();
                        }
                        state = -1;
                    } else {
                        if (h == 3) {
                            if (lane == 0) asm volatile("cp.async.bulk.wait_group 0;\nfence.proxy.async;" ::: "memory");
                            __syncwarp();
                            const int i = opaque(2 * lane - NPRIV, lane);
                            if ((unsigned)i < NPOOL) st_rlx(&gs->info[b * NPOOL + i], tag | iw0);
                            if ((unsigned)(i + 1) < NPOOL) st_rlx(&gs->info[b * NPOOL + i + 1], tag | iw1);
                        }
                        bar_sync(6, 128);
                        ev = h ? end : end - 12; state = h ? 2 : 0;
                    }
                } else if (state == 0) { ev = end - 6; state = 1; tk = take(); }
                else if (state == 1) { resolve(); ev = end; state = 2; }
                else {
                    if (state == 3) break;
                    do {
                        const uint32_t mb = sm + O_MB + (nr & 15) * 8;
                        uint32_t rg;
                        nr++;
                        if (h == 0) {
                            for (int it = 0; (rg = __reduce_max_sync(0xffffffffu, inf ^ tag)) >> 30; it++) { spin_check(it); inf = ld_rlx(&gs->info[ii]); }
                            asm volatile("st.release.cta.shared.b64 [%0], %1;" ::"r"(mb), "l"(rg | (uint64_t)nr << 32) : "memory");
                            if (rg) resolve();
                        } else {
                            uint64_t m;
                            for (int it = 0;; it++) {
                                asm volatile("ld.acquire.cta.shared.b64 %0, [%1];" : "=l"(m) : "r"(mb) : "memory");
                                if (__all_sync(0xffffffffu, (int)(m >> 32) == nr)) break;
                                spin_check(it);
                            }
                            rg = __reduce_max_sync(0xffffffffu, (uint32_t)m);
                        }
                        pos = rg ? (int)(rg >> 12) + pos - end : 0;
                        end = rg ? (rg >> 12) + (rg & 0xfff) : 1;
                        state = rg ? 2 : 3;
                    } while (pos >= end);
                    ev = end;
                }
            }
        }
        mbar_wait31(so + S_EMPTY, ph);
        TSW(8 + (h & 1));
        if (lane == 0) sts32(so + S_N, 0);
        mbar_arrive(so + S_FULL);
        if (t == 256) {
            gs->epoch[b * 32] = (tag >> 30) % 3;
            if (atomicInc(&gs->done, G - 1) == G - 1) gs->ticket = 0;
        }
        asm volatile("cp.async.wait_all;" ::: "memory");
    } else {
        asm volatile("setmaxnreg.inc.sync.aligned.u32 " STR(CREG) ";");
        if (HS && !HL) bar_sync(5, HS < 4 ? NT : 288);
        const uint32_t xa = opaque(((mat >> 1) * 8 + r) * 1024 + (w >> 2) * 128 + (((2 * (w & 3) + (mat & 1)) ^ r) * 16), lane);
        const uint32_t aa = opaque(S_A + ((mat >> 1) * 8 + r) * 32 + (((mat & 1) ^ (r >> 2)) * 16), lane);
        const uint32_t ya = opaque(S_C + (mat & 1) * 80 + (mat >> 1) * 16, lane);
        const uint32_t yc = opaque(S_C + (mat < 2 ? mat * 80 + 32 : q < 3 ? mat * 128 + ((r >> 2) ^ (mat & 1)) * 80 + q * 16 : 64), lane);
        const uint32_t na = opaque((mat & 1) * 8, lane);
        const uint32_t pw = sm + O_P + w * PW;
        const uint32_t fx = opaque(pw + (q < 3 ? P_1P0 + 2 * q * PSBO : P_1P1 + PSBO) + (mat & 1) * 128 + (r >> 2) * PSBO, lane);
        const uint32_t fyz = opaque(pw + (q < 3 ? (mat < 2 ? P_1P1 : P_1P2) + 2 * q * PSBO : mat < 2 ? P_0P0 : P_0P1) + (mat & 1) * 128 + (r >> 2) * PSBO, lane);
        uint32_t oh[MA ? 5 : 8];
#pragma unroll
        for (int c = 0; c < (MA ? 5 : 8); c++) oh[c] = opaque(g == (q >> 1) * 4 + (MA ? min(c, 3) : c & 3) ? 0x3F803F80u : 0u, lane ^ c >> 2);
        uint32_t eb[3];
#pragma unroll
        for (int k = 0; k < 3; k++) {
            const int i = (g & 3) * 9 + (q & 1) * 6 + k;
            const uint32_t lo = __shfl_sync(0xffffffffu, epl, i), hi = __shfl_sync(0xffffffffu, epl, i + 3);
            eb[k] = (g & 3) < 3 && (q >> 1) == (g >> 2) ? (q & 1 ? lo : lo | hi << 16) : 0u;
        }
        asm volatile(".reg .pred lane0;\nsetp.eq.u32 lane0, %0, 0;" ::"r"(lane));
        uint32_t w0[16][4], w1[KR][4];
        mbar_wait(sm + O_WBD, 0);
        if (HS && HL) bar_sync(5, HS < 4 ? NT : 288);
#pragma unroll
        for (int k = 0; k < 16; k++) ldsm4t(w0[k], sm + O_W0S + (k >> 2) * 16384 + (w >> 2) * 8192 + (k & 3) * 2048 + sw);
#pragma unroll
        for (int k = 0; k < KR; k++) ldsm4t(w1[k], sm + (k < 4 ? O_W1S + (k >> 1) * 8192 : O_WR1) + (w >> 2) * 4096 + (k & 1) * 2048 + sw);
        if (B4) asm volatile("bar.arrive 4, %0;" ::"n"(NT) : "memory");
        bar_sync(7, B4 ? 320 : NT);
        TS(6);
        Acc A;
#pragma unroll
        for (int i = 0; i < 4; i++) { A.p[0][AI(i)] = A.p[1][AI(i)] = A.p[2][AI(i)] = A.p[3][AI(i)] = A.p[4][AI(i)] = 0; A.t01[i] = A.m[0][i] = A.m[1][i] = A.m[2][i] = 0.f; }
        uint32_t room = 144 - (STAG) * 16;
        uint32_t so = sm + O_RING, ph, a[4], ok, go, mt = 0;
        mbar_wait(so + S_FULL, 0);
        ldsm4(a, so + aa);
        TS(7);
        while (true) {
            {
                constexpr int F = 1, H = 0, XS = XS_F;
                int seen = 0;
                uint32_t yb[8], f[4][4], R[5][4], u[4][4], sd[4];
                float y[4], z[4];
                const uint32_t sof = room & 112;
                room -= 16;
                SEQ_F
            }
            if (!(go && room)) {
                const uint32_t pu = __reduce_max_sync(0xffffffffu, ph);
                if (!room || !pu) {
                    if (GD == 2) asm volatile("@lane0 red.shared.add.u32 [%0], 1;" ::"r"(sm + O_SUM + 4) : "memory");
                    GT(0);
                    const uint32_t wg = __reduce_max_sync(0xffffffffu, w >> 2);
                    if (!FEN) asm volatile("fence.proxy.async.shared::cta;" ::: "memory");
                    mbar_wait(sm + O_WBB, 0);
                    GT(1);
                    if (ALT == 1) asm volatile("{.reg .pred p; setp.ne.u32 p, %0, 0;\n@p bar.arrive 1, 256;\n@p bar.sync 2, 256;\n@!p bar.sync 1, 256;}" ::"r"(wg ^ AWG) : "memory");
                    else bar_sync(1, 256);
                    if (FEN) asm volatile("fence.proxy.async::generic.acquire.sync_restrict::shared::cluster.cluster;" ::: "memory");
                    GT(2);
                    float d0[8], d1[24];
                    const uint64_t db = (uint64_t)((sm + O_P) >> 4) | (8ull << 16) | ((uint64_t)(PSBO / 16) << 32);
                    const uint32_t da = ((sm + O_W1) >> 4 | 1 << 16) + wg * 256;
                    asm volatile("wgmma.fence.sync.aligned;" ::: "memory");
                    if (!IL) {
#pragma unroll
                        for (int k = 0; k < 16; k++) G0(k);
                        asm volatile("wgmma.commit_group.sync.aligned;" ::: "memory");
                    }
                    const uint32_t sp = so == sm + O_RING ? sm + O_RING + (NSLOT - 1) * SLOT : so - SLOT, sr = (r & 6) + (mat & 1);
                    const uint32_t nd = (sr * 16 - 16 & 112) >= room ? lds32(sm + O_NODE + sr * 16 + (mat >> 1) * 8) : 0;
                    const uint64_t oa = madw(nd, 1024, (uint64_t)(out - 1024 + w * 32 + (r & 1) * 16));
                    const uint32_t sl = sp + ((mat >> 1) * 8 + sr) * 1024 + (w >> 2) * 128 + (((2 * (w & 3) + (r & 1)) ^ sr) * 16);
                    auto put = [&](int j) {
                        const uint4 v = lds128(sl + j * 256);
                        asm volatile("{.reg .pred p; setp.ne.u32 p, %5, 0; @p st.global.v4.u32 [%0], {%1,%2,%3,%4};}"
                                     ::"l"(oa + j * 256), "r"(v.x), "r"(v.y), "r"(v.z), "r"(v.w), "r"(nd) : "memory");
                    };
                    float gt[8];
#pragma unroll
                    static_for<25>([&](auto kc) {
                        constexpr int k = kc.value;
                        if (IL && k == 16 / (IL + !IL)) asm volatile("wgmma.commit_group.sync.aligned;" ::: "memory");
                        if (ALT == 1 && k == ASP) asm volatile("{.reg .pred p; setp.eq.u32 p, %0, 0;\n@p bar.arrive 2, 256;}" ::"r"(wg ^ AWG) : "memory");
                        if (k == GP || k == 24) asm volatile("wgmma.commit_group.sync.aligned;" ::: "memory");
                        if (k == GP) {
                            asm volatile("wgmma.wait_group.sync.aligned 1;" ::: "memory");
#pragma unroll
                            for (int i = 0; i < 8; i++) asm volatile("" : "+f"(d0[i])::"memory");
                            stsm4t(sp + xa, pack(d0[0], d0[1]), pack(d0[2], d0[3]), pack(d0[4], d0[5]), pack(d0[6], d0[7]));
                            __syncwarp();
                        }
                        if (k == min(GP + GS, 24)) put(0);
#pragma unroll
                        for (int i = 0; i < 8; i++) {
                            if (k == min(GP + i / 2 * GS, 24)) asm volatile("ex2.approx.ftz.f32 %0, %1;" : "=f"(gt[i]) : "f"(d0[i] * -1.4426950408889634f) : "memory");
                            if (k == min(GP + (i / 2 + 1) * GS, 24)) asm volatile("rcp.approx.ftz.f32 %0, %1;" : "=f"(gt[i]) : "f"(gt[i] + 1.f) : "memory");
                        }
                        if (k == min(GP + 5 * GS, 24)) {
                            uint32_t chk = -1;
#pragma unroll
                            for (int i = 0; i < 8; i++) chk &= __float_as_uint(gt[i]);
                            sts32(sm + O_TRASH, chk);
                        }
                        if (k < 24) G1(k % 24);
#pragma unroll
                        for (int i = 0; i < IL; i++) if (k * IL + i < 16) G0((k * IL + i) % 16);
                    });
                    GT(3);
                    asm volatile("wgmma.wait_group.sync.aligned 0;" ::: "memory");
                    GT(4);
#pragma unroll
                    for (int i = 0; i < 24; i++) asm volatile("" : "+f"(d1[i])::"memory");
                    if (ALT == 1) asm volatile("{.reg .pred p; setp.ne.u32 p, %0, 0;\n@p bar.sync 3, 256;}" ::"r"(wg ^ AWG) : "memory");
#pragma unroll
                    for (int j = 0; j < 3; j++) {
                        uint32_t o[4];
#pragma unroll
                        for (int i = 0; i < 4; i++) o[i] = pack(d1[8 * j + 2 * i] * gt[2 * i], d1[8 * j + 2 * i + 1] * gt[2 * i + 1]);
                        stsm4t(sp + xa + 256 + j * 256, o[0], o[1], o[2], o[3]);
                    }
                    __syncwarp();
#pragma unroll
                    for (int j = 1; j < 4; j++) put(j);
                    __syncwarp();
                    asm volatile("@lane0 mbarrier.arrive.shared::cta.b64 _, [%0];" ::"r"(sp + S_EMPTY) : "memory");
                    if (GD == 1) asm volatile("@lane0 red.shared.add.u32 [%0], 1;" ::"r"(sm + O_SUM + 4) : "memory");
                    GT(5);
                    if (ALT == 1) asm volatile("{.reg .pred p; setp.eq.u32 p, %0, 0;\n@p bar.sync 3, 256;}" ::"r"(wg ^ AWG) : "memory");
                    else bar_sync(3, 256);
                    GT(6);
                    room = 128;
                    if (!pu) break;
                }
                if (!ok) { mbar_wait31(so + S_FULL, pu); ldsm4(a, so + aa); }
                if (!(pu & 0xfffc)) { if (pu & 1) goto half; continue; }
            }
            while (true) {
                do {
                    constexpr int F = 0, H = 0, XS = XS_R;
                    int seen = 0;
                    uint32_t yb[8], f[4][4], R[5][4], u[4][4], sd[4];
                    SEQ_R
                } while (go);
                if (ok) {
                    asm volatile("{.reg .pred p; .reg .f32 n; abs.f32 n, %1; setp.gt.f32 p, n, 0f00000002; selp.u32 %0, 1, 0, p;}" : "=r"(go) : "r"(ph));
                    break;
                }
                const uint32_t pu = __reduce_max_sync(0xffffffffu, ph);
                mbar_wait31(so + S_FULL, pu); ldsm4(a, so + aa);
                if (!(pu & 0xfffc)) { go = pu & 1; break; }
            }
            if (!go) continue;
        half: {
                constexpr int F = 0, H = 1, XS = XS_H;
                int seen = 0;
                uint32_t yb[8], f[4][4], R[5][4], u[4][4], sd[4];
                SEQ_H
                if (!ok) { mbar_wait31(so + S_FULL, __reduce_max_sync(0xffffffffu, ph)); ldsm4(a, so + aa); }
            }
        }
        TS(10);
    }
}

typedef CUresult (*EncFn)(CUtensorMap*, CUtensorMapDataType, cuuint32_t, void*, const cuuint64_t*, const cuuint64_t*,
                          const cuuint32_t*, const cuuint32_t*, CUtensorMapInterleave, CUtensorMapSwizzle,
                          CUtensorMapL2promotion, CUtensorMapFloatOOBfill);

void make_map(EncFn fn, CUtensorMap* m, void* p, int rows, int cols, int brows, int bcols, int bblk) {
    cuuint64_t dims[3] = {64, (cuuint64_t)rows, (cuuint64_t)cols / 64}, strides[2] = {(cuuint64_t)cols * 2, 128};
    cuuint32_t box[3] = {(cuuint32_t)bcols, (cuuint32_t)brows, (cuuint32_t)bblk}, es[3] = {1, 1, 1};
    fn(m, CU_TENSOR_MAP_DATA_TYPE_BFLOAT16, 3, p, dims, strides, box, es, CU_TENSOR_MAP_INTERLEAVE_NONE,
       bcols == 64 ? CU_TENSOR_MAP_SWIZZLE_128B : CU_TENSOR_MAP_SWIZZLE_NONE, CU_TENSOR_MAP_L2_PROMOTION_L2_128B, CU_TENSOR_MAP_FLOAT_OOB_FILL_NONE);
}

}

extern "C" void kernel_launch(void* const* d_in, const int* in_sizes, int n_in, void* d_out, int out_size) {
    static EncFn enc = nullptr;
    static void* scratch = nullptr;
    if (!enc) {
        void* fn = nullptr;
        cudaDriverEntryPointQueryResult qr;
        cudaGetDriverEntryPoint("cuTensorMapEncodeTiled", &fn, cudaEnableDefault, &qr);
        enc = (EncFn)fn;
        cudaGetSymbolAddress(&scratch, g_scratch);
        cudaFuncSetAttribute(tp_kernel, cudaFuncAttributeMaxDynamicSharedMemorySize, SMEM_BYTES);
    }
    CUtensorMap m_wr, m_w0, m_w1, m_x;
    make_map(enc, &m_wr, d_in[5], 16, 640, 16, 64, 5);
    make_map(enc, &m_w0, d_in[6], 256, 128, 64, 64, 2);
    make_map(enc, &m_w1, d_in[7], 384, 128, 32, 64, 2);
    make_map(enc, &m_x, d_in[0], NN * 8, 64, NLOC * 2, 8, 1);
    tp_kernel<<<G, NT, SMEM_BYTES>>>((const int4*)d_in[4], (const int4*)d_in[3], (const char*)d_in[1], (Scratch*)scratch,
                                     (const char*)d_in[0], (const char*)d_in[2], (const __nv_bfloat16*)d_in[8], (char*)d_out,
                                     m_wr, m_w0, m_w1, m_x);
}
```

```cpp
#include <cuda_runtime.h>
#include <cuda_bf16.h>
#include <cuda.h>
#include <stdint.h>
#include <stddef.h>

namespace {

constexpr int NN = 10000;
constexpr int NE = 320000;
constexpr int G = 132;
constexpr int NT = 384;
constexpr int CH = 2432;
constexpr int NLOC = (NN + G - 1) / G;
#define NPOOL 3
constexpr int NPAIR = NLOC / 2, NPRIV = NPAIR - NPOOL;
constexpr int SEGW = 11;

#define NSLOT 7
#define EH ""
#define EPF 0
#define TP 0x9375
#define STAG (b & 7)
#define ASC (b & 1)
#define THETA (5 * G / 3)
#define THETB G
#define QOK (STAG)
#define QJ 3
#define WP 0x5357575
#define KR 9
#define WLD(p) { _Pragma("unroll") for (int j = 0; j < 4 + KR; j++) if ((WP >> 4 * (j < 4 ? j : j < 8 ? 4 : j < 11 ? 5 : 6) & 15) == p) \
    tma3d(sm + (j < 4 ? w0s(j) : w1s(j - 4)), j < 4 ? &m_w0 : &m_w1, j < 4 ? j * 64 : (j - 4) * 16, 0, sm + O_WBD); \
    _Pragma("unroll") for (int j = 0; j < 4; j++) { const int r0 = (b * 4 + j) * (NLOC / 4); \
        if ((TP >> 4 * j & 15) == p) tma3d(sm + O_WR1 + 12288, &m_x, r0 * 8, 0, sm + O_WBE); } }
#define ALT 1
#define AWG 0
#define IL 1
#define RSL 1
#define FEN 1
#define HS 4
#define HL 0
#define B4 1
#define GD 1
#define HT 1
#define PH 1
#define MA 1
#define GM 0
#define GP 24
#define GS 2
#define ASP 20
#define INV 0
#define NULLP(v) v
#define CREG 224
#define PREG 56
#define STR2(x) #x
#define STR(x) STR2(x)

constexpr int S_A = 16384, S_C = S_A + 512, S_FULL = S_C + 144, S_EMPTY = S_FULL + 8, S_N = S_C + 160, SLOT = S_C + 512;

constexpr int PSBO = 272;
constexpr int PB1 = 5 * PSBO + 256, PB0 = PSBO + 256;
constexpr int P_1P0 = 0, P_1P1 = PB1, P_0P1 = 2 * PB1, P_0P0 = P_0P1 + PB0, P_1P2 = P_0P0 + PB0;
constexpr int PW = P_1P2 + PB1;

constexpr int O_W1 = 0;
constexpr int O_P = 62336;
constexpr int O_RING = O_P + 8 * PW;
constexpr int O_WBA = O_RING + 7 * SLOT, O_WBB = O_WBA + 8, O_WBC = O_WBA + 16, O_WBD = O_WBA + 24, O_WBE = O_WBA + 32, O_TRASH = O_WBA + 40, O_NODE = O_WBA + 48;
constexpr int O_SUM = O_NODE + 128, O_MB = O_SUM + 16;
constexpr int SMEM_BYTES = O_MB + 128;
constexpr int CAPT = 192;
constexpr int O_L = 0, LZ = CAPT * 256 / (NT * 16), O_W0S = O_L + CAPT * 256, O_OUT = O_RING + S_C - CH * 8, O_SRC = O_RING + 6 * SLOT;
constexpr int O_KT = O_RING + SLOT, O_RH = O_RING + 2 * SLOT;
constexpr int O_WR0 = O_RING + 3 * SLOT, O_WR1 = O_RING + 4 * SLOT;
__host__ __device__ constexpr int w0s(int j) { return j < 3 ? O_W0S + j * 16384 : O_SRC; }
__host__ __device__ constexpr int w1s(int k) { return k < 4 ? O_RING + 5 * SLOT + k * 4096 : k < 7 ? O_WR1 + (k - 4) * 4096 : O_W0S + 49152 + (k - 7) * 4096; }
constexpr int O_BCNT = O_WR0 + 10240, O_NCUR = O_BCNT + 640, O_NCNT = O_NCUR + 320;
constexpr int O_BOFF = O_NCNT + 512, O_SORT = O_BOFF + 640, O_NOFF = O_SORT + 320;
constexpr int TBIG = G * CAPT + 8, NTILE = TBIG + NE / 8 + G * (NLOC + 5);
static_assert(SMEM_BYTES <= 232448 && CAPT % 16 == 0 && NTILE < (1 << 18), "smem");
static_assert(LZ * NT * 16 == CAPT * 256 && O_W0S % 1024 == 0 && w1s(KR) <= O_OUT && O_OUT % 128 == 0 && CH * 6 <= S_C && G * 128 <= S_C, "staging");
static_assert(O_NOFF + 1024 <= O_RING + 3 * SLOT + S_C && 12288 + NLOC * 32 <= S_C && (24 - KR) * 4096 <= O_P && KR <= 9, "staging");
static_assert(O_RING % 1024 == 0 && SLOT % 1024 == 0 && O_W0S <= O_P && O_NOFF % 8 == 0, "layout");
static_assert(G * CH >= NE && NE % 8 == 0 && CH < 4096 && CH / 8 <= 320 && NE < (1 << 21), "chunks");
static_assert(SEGW * (NT / 32) == G && G <= 160 && G % 4 == 0, "segments");
static_assert(NLOC % 4 == 0 && NLOC < 80 && NLOC * 4 <= 320 && NN < 0x3fff && NE / 8 < 0xbfff && NPRIV >= 30, "scan width");

struct __align__(256) Scratch {
    uint32_t keys[G * G * 32];
    uint64_t vals[G * CH];
    uint32_t more[G * CH];
    uint32_t epoch[G * 32];
    uint32_t info[(G * NPOOL + 127) / 128 * 128];
    unsigned done, pad0[31], ticket, pad1[31];
    uint4 list[NTILE * 16];
};
static_assert(offsetof(Scratch, list) % 256 == 0, "list");
__device__ Scratch g_scratch;
#define GT(i)
#define TS(i)
#define TSW(i)
#define TV(i, v)

constexpr int SPIN_LIMIT = 1 << 24;

__device__ __forceinline__ void mbar_init(uint32_t a, int c) { asm volatile("mbarrier.init.shared::cta.b64 [%0], %1;" ::"r"(a), "r"(c) : "memory"); }
__device__ __forceinline__ void mbar_expect(uint32_t a, int b) { asm volatile("mbarrier.arrive.expect_tx.shared::cta.b64 _, [%0], %1;" ::"r"(a), "r"(b) : "memory"); }
__device__ __forceinline__ void mbar_arrive(uint32_t a) { asm volatile("mbarrier.arrive.shared::cta.b64 _, [%0];" ::"r"(a) : "memory"); }
__device__ __forceinline__ void mbar_wait(uint32_t a, uint32_t ph) {
    asm volatile("{\n.reg .pred p, q;\n.reg .u32 it;\n"
                 "mbarrier.try_wait.parity.shared::cta.b64 p, [%0], %1;\n"
                 "@p bra DONE;\n"
                 "mov.u32 it, 0;\n"
                 "LOOP:\n"
                 "mbarrier.try_wait.parity.shared::cta.b64 p, [%0], %1;\n"
                 "@p bra DONE;\n"
                 "add.u32 it, it, 1;\n"
                 "setp.gt.u32 q, it, %2;\n"
                 "@q trap;\n"
                 "bra LOOP;\n"
                 "DONE:\n}" ::"r"(a), "r"(ph), "n"(SPIN_LIMIT) : "memory");
}
__device__ __forceinline__ void mbar_wait31(uint32_t a, uint32_t ph) {
    asm volatile("{\n.reg .pred p, q;\n.reg .u32 it;\n.reg .b64 s;\n"
                 "mov.b64 s, {0, %1};\n"
                 "mbarrier.try_wait.shared::cta.b64 p, [%0], s;\n"
                 "@p bra DONE;\n"
                 "mov.u32 it, 0;\n"
                 "LOOP:\n"
                 "mbarrier.try_wait.shared::cta.b64 p, [%0], s;\n"
                 "@p bra DONE;\n"
                 "add.u32 it, it, 1;\n"
                 "setp.gt.u32 q, it, %2;\n"
                 "@q trap;\n"
                 "bra LOOP;\n"
                 "DONE:\n}" ::"r"(a), "r"(ph), "n"(SPIN_LIMIT) : "memory");
}
__device__ __forceinline__ void spin_check(int it) {
    asm volatile("{\n.reg .pred q;\nsetp.gt.s32 q, %0, %1;\n@q trap;\n}" ::"r"(it), "n"(SPIN_LIMIT));
}
__device__ __forceinline__ void ldsm4(uint32_t* r, uint32_t a) { asm volatile("ldmatrix.sync.aligned.m8n8.x4.shared.b16 {%0,%1,%2,%3}, [%4];" : "=r"(r[0]), "=r"(r[1]), "=r"(r[2]), "=r"(r[3]) : "r"(a) : "memory"); }
__device__ __forceinline__ void ldsm4t(uint32_t* r, uint32_t a) { asm volatile("ldmatrix.sync.aligned.m8n8.x4.trans.shared.b16 {%0,%1,%2,%3}, [%4];" : "=r"(r[0]), "=r"(r[1]), "=r"(r[2]), "=r"(r[3]) : "r"(a) : "memory"); }
__device__ __forceinline__ void ldsm2t(uint32_t* r, uint32_t a) { asm volatile("ldmatrix.sync.aligned.m8n8.x2.trans.shared.b16 {%0,%1}, [%2];" : "=r"(r[0]), "=r"(r[1]) : "r"(a) : "memory"); }
__device__ __forceinline__ void stsm4t(uint32_t a, uint32_t r0, uint32_t r1, uint32_t r2, uint32_t r3) { asm volatile("stmatrix.sync.aligned.m8n8.x4.trans.shared.b16 [%0], {%1,%2,%3,%4};" ::"r"(a), "r"(r0), "r"(r1), "r"(r2), "r"(r3) : "memory"); }
__device__ __forceinline__ void stsm2t(uint32_t a, uint32_t r0, uint32_t r1) { asm volatile("stmatrix.sync.aligned.m8n8.x2.trans.shared.b16 [%0], {%1,%2};" ::"r"(a), "r"(r0), "r"(r1) : "memory"); }
__device__ __forceinline__ void mma16(float* d, const uint32_t* a, uint32_t b0, uint32_t b1) {
    asm("mma.sync.aligned.m16n8k16.row.col.f32.bf16.bf16.f32 {%0,%1,%2,%3}, {%4,%5,%6,%7}, {%8,%9}, {%0,%1,%2,%3};"
        : "+f"(d[0]), "+f"(d[1]), "+f"(d[2]), "+f"(d[3]) : "r"(a[0]), "r"(a[1]), "r"(a[2]), "r"(a[3]), "r"(b0), "r"(b1));
}
__device__ __forceinline__ void mma8(float* d, uint32_t a0, uint32_t a1, uint32_t b0) {
    asm("mma.sync.aligned.m16n8k8.row.col.f32.bf16.bf16.f32 {%0,%1,%2,%3}, {%4,%5}, {%6}, {%0,%1,%2,%3};"
        : "+f"(d[0]), "+f"(d[1]), "+f"(d[2]), "+f"(d[3]) : "r"(a0), "r"(a1), "r"(b0));
}
__device__ __forceinline__ void mma16z(float* d, const uint32_t* a, uint32_t b0, uint32_t b1) {
    asm("mma.sync.aligned.m16n8k16.row.col.f32.bf16.bf16.f32 {%0,%1,%2,%3}, {%4,%5,%6,%7}, {%8,%9}, {%10,%10,%10,%10};"
        : "=f"(d[0]), "=f"(d[1]), "=f"(d[2]), "=f"(d[3]) : "r"(a[0]), "r"(a[1]), "r"(a[2]), "r"(a[3]), "r"(b0), "r"(b1), "f"(0.f));
}
__device__ __forceinline__ uint32_t pack(float lo, float hi) { uint32_t r; asm("cvt.rn.bf16x2.f32 %0, %1, %2;" : "=r"(r) : "f"(hi), "f"(lo)); return r; }
__device__ __forceinline__ uint32_t hmul(uint32_t a, uint32_t b) { uint32_t r; asm("mul.rn.bf16x2 %0, %1, %2;" : "=r"(r) : "r"(a), "r"(b)); return r; }
__device__ __forceinline__ uint32_t hfma(uint32_t a, uint32_t b, uint32_t c) { uint32_t r; asm("fma.rn.bf16x2 %0, %1, %2, %3;" : "=r"(r) : "r"(a), "r"(b), "r"(c)); return r; }
__device__ __forceinline__ uint4 lds128(uint32_t a) { uint4 v; asm volatile("ld.shared.v4.u32 {%0,%1,%2,%3}, [%4];" : "=r"(v.x), "=r"(v.y), "=r"(v.z), "=r"(v.w) : "r"(a) : "memory"); return v; }
__device__ __forceinline__ void sts128(uint32_t a, uint4 v) { asm volatile("st.shared.v4.u32 [%0], {%1,%2,%3,%4};" ::"r"(a), "r"(v.x), "r"(v.y), "r"(v.z), "r"(v.w) : "memory"); }
__device__ __forceinline__ int lds32(uint32_t a) { int v; asm volatile("ld.shared.u32 %0, [%1];" : "=r"(v) : "r"(a) : "memory"); return v; }
__device__ __forceinline__ void sts32(uint32_t a, int v) { asm volatile("st.shared.u32 [%0], %1;" ::"r"(a), "r"(v) : "memory"); }
__device__ __forceinline__ int atoms_add(uint32_t a, int v) { int r; asm volatile("atom.shared.add.u32 %0, [%1], %2;" : "=r"(r) : "r"(a), "r"(v) : "memory"); return r; }
__device__ __forceinline__ uint32_t ld_rlx(const void* p) { uint32_t v; asm volatile("ld.relaxed.gpu.global.u32 %0, [%1];" : "=r"(v) : "l"(p) : "memory"); return v; }
__device__ __forceinline__ void st_rlx(void* p, uint32_t v) { asm volatile("st.relaxed.gpu.global.u32 [%0], %1;" ::"l"(p), "r"(v) : "memory"); }
__device__ __forceinline__ void bulk(uint32_t dst, const void* g, int n, uint32_t bar) {
    asm volatile("cp.async.bulk.shared::cluster.global.mbarrier::complete_tx::bytes [%0], [%1], %2, [%3];" ::"r"(dst), "l"(g), "r"(n), "r"(bar) : "memory");
}
__device__ __forceinline__ void bulk_st(void* g, uint32_t src, int n) {
    asm volatile("cp.async.bulk.global.shared::cta.bulk_group [%0], [%1], %2;\ncp.async.bulk.commit_group;" ::"l"(g), "r"(src), "r"(n) : "memory");
}
__device__ __forceinline__ uint2 lds64(uint32_t a) { uint2 v; asm volatile("ld.shared.v2.u32 {%0,%1}, [%2];" : "=r"(v.x), "=r"(v.y) : "r"(a) : "memory"); return v; }
__device__ __forceinline__ void sts64(uint32_t a, uint32_t x, uint32_t y) { asm volatile("st.shared.v2.u32 [%0], {%1,%2};" ::"r"(a), "r"(x), "r"(y) : "memory"); }
__device__ __forceinline__ void tma3d(uint32_t dst, const CUtensorMap* m, int c1, int c2, uint32_t bar) {
    asm volatile("cp.async.bulk.tensor.3d.shared::cluster.global.mbarrier::complete_tx::bytes [%0], [%1, {0, %3, %4}], [%2];"
                 ::"r"(dst), "l"(m), "r"(bar), "r"(c1), "r"(c2) : "memory");
}
__device__ __forceinline__ void pf_l2(const void* g, int n) {
    asm volatile("{.reg .pred p; setp.gt.s32 p, %1, 0; @p cp.async.bulk.prefetch.L2.global [%0], %1;}" ::"l"(g), "r"(n) : "memory");
}
__device__ __forceinline__ void fence_async() { asm volatile("fence.proxy.async.shared::cta;" ::: "memory"); }
__device__ __forceinline__ uint64_t madw(uint32_t a, uint32_t b, uint64_t c) { uint64_t r; asm("mad.wide.u32 %0, %1, %2, %3;" : "=l"(r) : "r"(a), "r"(b), "l"(c)); return r; }
__device__ __forceinline__ uint32_t lop_sel(uint32_t a, uint32_t b, uint32_t m) { uint32_t r; asm("lop3.b32 %0, %1, %2, %3, 0xd8;" : "=r"(r) : "r"(a), "r"(b), "r"(m)); return r; }
__device__ __forceinline__ uint32_t opaque(uint32_t v, int lane) { return __shfl_sync(0xffffffffu, v, lane); }
__device__ __forceinline__ void bar_sync(int id, int n) { asm volatile("bar.sync %0, %1;" ::"r"(id), "r"(n) : "memory"); }

__device__ __forceinline__ void wg_rs16(float* d, const uint32_t* a, uint64_t db, int sc) {
    asm volatile("{.reg .pred p; setp.ne.b32 p, %13, 0;\n"
                 "wgmma.mma_async.sync.aligned.m64n16k16.f32.bf16.bf16 {%0,%1,%2,%3,%4,%5,%6,%7}, {%8,%9,%10,%11}, %12, p, 1, 1, 0;}"
                 : "+f"(d[0]), "+f"(d[1]), "+f"(d[2]), "+f"(d[3]), "+f"(d[4]), "+f"(d[5]), "+f"(d[6]), "+f"(d[7])
                 : "r"(a[0]), "r"(a[1]), "r"(a[2]), "r"(a[3]), "l"(db), "r"(sc));
}
__device__ __forceinline__ void wg_rs48(float* d, const uint32_t* a, uint64_t db, int sc) {
    asm volatile("{.reg .pred p; setp.ne.b32 p, %29, 0;\n"
                 "wgmma.mma_async.sync.aligned.m64n48k16.f32.bf16.bf16 {%0,%1,%2,%3,%4,%5,%6,%7,%8,%9,%10,%11,%12,%13,%14,%15,%16,%17,%18,%19,%20,%21,%22,%23}, {%24,%25,%26,%27}, %28, p, 1, 1, 0;}"
                 : "+f"(d[0]), "+f"(d[1]), "+f"(d[2]), "+f"(d[3]), "+f"(d[4]), "+f"(d[5]), "+f"(d[6]), "+f"(d[7]),
                   "+f"(d[8]), "+f"(d[9]), "+f"(d[10]), "+f"(d[11]), "+f"(d[12]), "+f"(d[13]), "+f"(d[14]), "+f"(d[15]),
                   "+f"(d[16]), "+f"(d[17]), "+f"(d[18]), "+f"(d[19]), "+f"(d[20]), "+f"(d[21]), "+f"(d[22]), "+f"(d[23])
                 : "r"(a[0]), "r"(a[1]), "r"(a[2]), "r"(a[3]), "l"(db), "r"(sc));
}
__device__ __forceinline__ void wg_ss48(float* d, uint64_t da, uint64_t db, int sc) {
    asm volatile("{.reg .pred p; setp.ne.b32 p, %26, 0;\n"
                 "wgmma.mma_async.sync.aligned.m64n48k16.f32.bf16.bf16 {%0,%1,%2,%3,%4,%5,%6,%7,%8,%9,%10,%11,%12,%13,%14,%15,%16,%17,%18,%19,%20,%21,%22,%23}, %24, %25, p, 1, 1, 1, 0;}"
                 : "+f"(d[0]), "+f"(d[1]), "+f"(d[2]), "+f"(d[3]), "+f"(d[4]), "+f"(d[5]), "+f"(d[6]), "+f"(d[7]),
                   "+f"(d[8]), "+f"(d[9]), "+f"(d[10]), "+f"(d[11]), "+f"(d[12]), "+f"(d[13]), "+f"(d[14]), "+f"(d[15]),
                   "+f"(d[16]), "+f"(d[17]), "+f"(d[18]), "+f"(d[19]), "+f"(d[20]), "+f"(d[21]), "+f"(d[22]), "+f"(d[23])
                 : "l"(da), "l"(db), "r"(sc));
}

__device__ __forceinline__ int warp_incl(int v) {
#pragma unroll
    for (int o = 1; o < 32; o <<= 1)
        asm volatile("{.reg .pred p; .reg .b32 u; shfl.sync.up.b32 u|p, %0, %1, 0, 0xffffffff; @p add.s32 %0, %0, u;}" : "+r"(v) : "r"(o));
    return v;
}
__device__ __forceinline__ void ldg128(uint32_t* r, const void* p, bool on) {
    asm volatile("{.reg .pred p; setp.ne.u32 p, %5, 0; @p ld.global.nc.v4.u32 {%0,%1,%2,%3}, [%4];}"
                 : "=r"(r[0]), "=r"(r[1]), "=r"(r[2]), "=r"(r[3]) : "l"(p), "r"((uint32_t)on));
}

template <int V> struct IC { static constexpr int value = V; };
template <int N, int I = 0, class Fn> __device__ __forceinline__ void static_for(Fn f) { if constexpr (I < N) { f(IC<I>{}); static_for<N, I + 1>(f); } }

struct Acc {
    uint32_t p[5][MA ? 2 : 4];
    float t01[4], m[3][4];
};

#define LF(m) if (H) ldsm2t(f[m], so + xa + m * 256); else ldsm4t(f[m], so + xa + m * 256)
#define LY() ldsm4(yb, so + ya)
#define LC() ldsm4(yb + 4, so + yc)
#define LN() ph = lds32(so + S_N)
#define ADV() { if (F && ALT) asm volatile("{.reg .pred p; setp.ne.and.u32 p, %1, 0, lane0; @p mbarrier.arrive.shared::cta.b64 _, [%0];}" ::"r"(so + S_EMPTY), "r"(room) : "memory"); \
                else asm volatile("@lane0 mbarrier.arrive.shared::cta.b64 _, [%0];" ::"r"(so + S_EMPTY) : "memory"); \
                so = so == sm + O_RING + (NSLOT - 1) * SLOT ? sm + O_RING : so + SLOT; }
#define LA() asm volatile("{\n.reg .pred p, q;\n.reg .b64 s;\n.reg .f32 n;\nmov.b64 s, {0, %7};\nmbarrier.test_wait.shared::cta.b64 p, [%6], s;\n" \
                          "abs.f32 n, %7;\nsetp.gt.and.f32 q, n, 0f00000003, p;\nselp.u32 %4, 1, 0, p;\nselp.u32 %5, 1, 0, q;\n" \
                          "@p ldmatrix.sync.aligned.m8n8.x4.shared.b16 {%0,%1,%2,%3}, [%8];\n}" \
                          : "+r"(a[0]), "+r"(a[1]), "+r"(a[2]), "+r"(a[3]), "=r"(ok), "=r"(go) : "r"(so + S_FULL), "r"(ph), "r"(so + aa) : "memory")
#define RAD(p, s) if (!H || !s) { float c[4]; mma16z(c, wr[p], a[2 * s], a[2 * s + 1]); R[p][2 * s] = pack(c[0], c[1]); R[p][2 * s + 1] = pack(c[2], c[3]); }
#define MUL(n, x, y) (XS >> n & 1 ? hmul(y, x) : hmul(x, y))
#define FMA(n, x, y, z) (XS >> n & 1 ? hfma(y, x, z) : hfma(x, y, z))
#define ON(i) if (!H || i < 2)
#define AI(i) ((i ^ XA) & (MA ? 1 : 3))
#define ACC(n, m, i, x, y, z) ON(i) { z[AI(i)] = F && !(seen >> (4 * m + AI(i)) & 1) ? MUL(n, x, y) : FMA(n, x, y, z[AI(i)]); seen |= 1 << (4 * m + AI(i)); }
#define P00(i) ACC(0, 3, i, f[0][i], R[0][i], A.p[3])
#define P10(k, i) ACC(1, k, i, f[1 + k][i], R[3][i], A.p[k])
#define S0(k, i) ON(i) sd[i] = MUL(2, f[1 + k][i], yb[2 * k + (i >> 1)])
#define SD(k, i) ON(i) sd[i] = FMA(2, f[1 + k][i], yb[2 * k + (i >> 1)], sd[i])
#define P110(i) ACC(3, 4, i, sd[i], R[1][i], A.p[4])
#define TU(i) ON(i) u[3][i ^ XU] = MUL(4, f[0][i], R[2][i])
#define EM(d, u) if (F) mma16z(d, u, yb[6], yb[7]); else if (H) mma8(d, u[0], u[1], yb[6]); else mma16(d, u, yb[6], yb[7])
#define TM() EM(A.t01, u[3])
#define MU(k, i) ON(i) u[k][i ^ XU] = MUL(5, f[1 + k][i], R[4][i])
#define MM(k) EM(A.m[k], u[k])
#define PK(v, h) pack(v[2 * (h)], v[2 * (h) + 1])
#define LM() { sts32(na + (sof + sm + O_NODE), mt); asm volatile("ld.shared.u16 %0, [%1];" : "=r"(mt) : "r"(na + (so + S_C + 48)) : "memory"); }
#define MP(k) PK(A.m[k], XA ^ XU), PK(A.m[k], 1 ^ XA ^ XU)
#define FY(k) if (k == 0) mma16z(y, A.p[0], oh[0], oh[1]); else if (k > 1 && !(seen >> 30)) { mma16(y, A.p[2], oh[2], oh[3]); seen |= 1 << 30; }
#define FZ(k) if (k == 0) { const uint32_t mp[4] = {A.p[4][0], A.p[4][1], MP(2)}; mma16z(z, mp, oh[4], eb[2]); } \
              else if (k == 1) { const uint32_t mp[4] = {MP(0), MP(1)}; mma16(z, mp, eb[0], eb[1]); }
#define SX() stsm2t(fx + sof, PK(A.t01, XU), PK(A.t01, 1 ^ XU))
#define SY() stsm4t(fyz + sof, PK(y, XA), PK(y, 1 ^ XA), PK(z, XA), PK(z, 1 ^ XA))
#define G0(k) wg_rs16(d0, w0[k], db + ((((k) & 7) * PW + (((k) >> 3) ? P_0P1 : P_0P0)) >> 4), k)
#define G1(i) { constexpr int k_ = RSL ? ((i) + KR) % 24 : (i); const uint64_t bk = db + (((k_ & 7) * PW + ((k_ >> 3) == 0 ? P_1P0 : (k_ >> 3) == 1 ? P_1P1 : P_1P2)) >> 4); \
                if (k_ < KR) wg_rs48(d1, w1[k_ % KR], bk, i); else wg_ss48(d1, (da + (k_ - KR) * 256) | (64ull << 32) | (1ull << 62), bk, i); }
#define X4(op) op(0); op(1); op(2); op(3)
#define Y4(op, k) op(k, 0); op(k, 1); op(k, 2); op(k, 3)
#define XA 1
#define XU 0
#define XS_R 63
#define SEQ_R LF(2); LN(); RAD(1,0); RAD(1,1); LC(); LY(); RAD(2,0); RAD(2,1); RAD(4,0); RAD(4,1); RAD(3,0); RAD(3,1); LF(0); P10(1,1); P10(1,0); \
    P10(1,3); P10(1,2); LF(3); MU(2,3); S0(2,3); S0(2,2); S0(2,1); S0(2,0); RAD(0,1); RAD(0,0); MU(2,2); P00(2); MU(2,1); MU(1,3); MU(2,0); MM(2); P00(3); \
    MU(1,2); LF(1); ADV(); LA(); P10(0,0); P10(0,1); P10(0,2); P10(0,3); SD(0,0); SD(0,2); SD(0,1); SD(0,3); SD(1,0); P110(0); SD(1,2); P110(2); SD(1,1); \
    P110(1); SD(1,3); P110(3); P00(0); MU(0,0); TU(0); P10(2,0); TU(2); MU(1,1); TU(3); TU(1); TM(); P10(2,2); P00(1); MU(0,2); P10(2,1); MU(1,0); MM(1); \
    P10(2,3); MU(0,1); MU(0,3); MM(0);
#define XS_H XS_R
#define SEQ_H SEQ_R
#define XS_F 63
#define SEQ_F LY(); LF(2); LF(0); SX(); FZ(0); FY(0); FY(2); RAD(1,0); LM(); RAD(0,1); RAD(2,1); RAD(3,0); RAD(3,1); RAD(2,0); LC(); RAD(0,0); \
    RAD(4,0); LN(); FZ(2); LF(1); LF(3); ADV(); FY(1); RAD(4,1); RAD(1,1); LA(); TU(1); TU(0); TU(3); TU(2); P10(0,0); P10(0,2); P10(2,3); P10(0,1); \
    P10(2,2); TM(); P10(0,3); FY(3); P10(2,1); P10(1,0); P10(2,0); P10(1,1); P10(1,2); S0(0,1); SD(2,1); SD(1,1); P110(1); S0(0,0); S0(0,3); S0(0,2); \
    SD(2,0); SD(1,0); P110(0); FZ(1); SY(); P10(1,3); MU(0,1); MU(0,0); MU(0,3); MU(0,2); SD(2,3); SD(1,3); P110(3); MU(2,2); MU(2,3); MU(2,0); MU(2,1); \
    MM(2); P00(2); SD(2,2); SD(1,2); P110(2); MU(1,0); P00(3); MU(1,2); MU(1,3); MU(1,1); MM(1); P00(0); P00(1); MM(0);

__global__ void __launch_bounds__(NT, 1)
tp_kernel(const int4* __restrict__ dst, const int4* __restrict__ src, const char* __restrict__ rhat, Scratch* __restrict__ gs,
          const char* __restrict__ x, const char* __restrict__ ea, const __nv_bfloat16* __restrict__ eps, char* __restrict__ out,
          const __grid_constant__ CUtensorMap m_wr, const __grid_constant__ CUtensorMap m_w0, const __grid_constant__ CUtensorMap m_w1,
          const __grid_constant__ CUtensorMap m_x) {
    extern __shared__ __align__(1024) char smem_raw[];
    constexpr uint32_t sm = 1024;
    spin_check((uint32_t)__cvta_generic_to_shared(smem_raw) == sm ? 0 : 2 * SPIN_LIMIT);
    int t;
    asm volatile("mov.u32 %0, %%tid.x;" : "=r"(t));
    const int w = t >> 5, lane = t & 31, b = blockIdx.x;

    const int g = lane >> 2, q = lane & 3, mat = lane >> 3, r = lane & 7;
    const int e0 = b * CH + t * 8, ne = min(CH, NE - b * CH);
    const bool act = t * 8 < ne;
    uint32_t d[8];
#pragma unroll
    for (int k = 0; k < 2; k++) ldg128(d + 4 * k, dst + e0 / 4 + k, act);
    uint32_t tag = ld_rlx(&gs->epoch[b * 32]), epl;
    asm volatile("ld.global.nc.u16 %0, [%1];" : "=r"(epl) : "l"(eps + min(lane, 26)));
    if (t < 60) sts128(sm + O_BCNT + 16 * t, make_uint4(0, 0, 0, 0));
    if (t == NT - 1) {
#pragma unroll
        for (int i = 0; i < 5; i++) mbar_init(sm + O_WBA + 8 * i, 1);
        fence_async();
        mbar_expect(sm + O_WBC, ne * 10); mbar_expect(sm + O_WBA, 20480); mbar_expect(sm + O_WBB, (24 - KR) * 4096); mbar_expect(sm + O_WBD, 65536 + KR * 4096);
        mbar_expect(sm + O_WBE, (((TP & 15) != 15) + ((TP >> 4 & 15) != 15) + ((TP >> 8 & 15) != 15) + ((TP >> 12) != 15)) * (NLOC / 4 * 128));
        WLD(6);
        spin_check(tag);
        bulk(sm + O_RH, rhat + b * (CH * 6), ne * 6, sm + O_WBC);
        bulk(sm + O_SRC, src + b * (CH / 4), ne * 4, sm + O_WBC);
        tma3d(sm + O_WR0, &m_wr, 0, 0, sm + O_WBA);
        tma3d(sm + O_WR1, &m_wr, 0, 5, sm + O_WBA);
        WLD(0);
    }
    if (t == 320) {
#pragma unroll
        for (int i = 0; i < NSLOT; i++) {
            sts128(sm + O_RING + i * SLOT + S_C + 64, make_uint4(0, 0, 0, 0));
            mbar_init(sm + O_RING + i * SLOT + S_FULL, 32); mbar_init(sm + O_RING + i * SLOT + S_EMPTY, 8);
        }
    }
#pragma unroll
    for (int k = 0; k < LZ; k++) sts128(sm + O_L + 16 * (t + k * NT), make_uint4(0, 0, 0, 0));
    if (t < 80) sts32(sm + O_NCNT + 4 * t, t <= NLOC ? 4 * t : 0);
    if (t < 68) sts32(sm + O_NODE + 4 * t, 0);
    uint32_t ba[8], rk[8];
    if (w < 10) bar_sync(1, 320);
    tag = (tag + 1) << 30;
    if (act) {
#pragma unroll
        for (int i = 0; i < 8; i++) {
            const uint32_t l = __umulhi(d[i], (uint32_t)((1ull << 32) / G + 1));
            ba[i] = d[i] * 4 - l * (4 * G);
            d[i] = l * 4 + (tag + ((e0 + i + 1) << 9) + 4);
            rk[i] = atoms_add(sm + O_BCNT + ba[i], 4);
        }
#pragma unroll
        for (int i = 0; i < 8; i++)
            asm volatile("{.reg .pred p; setp.lt.u32 p, %2, 124; @p st.shared.u32 [%0], %1;}"
                         ::"r"(sm + O_KT + ba[i] * 32 + ((ba[i] + rk[i]) & 127)), "r"(d[i]), "r"(rk[i]) : "memory");
    }
    TS(0);
    __syncthreads();
    {
        int v[5], sum = 0;
#pragma unroll
        for (int i = 0; i < 5; i++) { v[i] = lds32(sm + O_BCNT + 4 * (lane * 5 + i)); sum += v[i]; }
        int e = warp_incl(sum) - sum;
        if (w == 10) {
#pragma unroll
            for (int i = 0; i < 5; i++) {
                const int k = lane * 5 + i;
                if (k < G) sts32(sm + O_KT + k * 128 + ((k * 4 + 124) & 127), tag | v[i] << 10 | e >> 2);
                e += v[i];
            }
            __syncwarp();
            if (lane == 0) {
                fence_async();
                bulk_st(&gs->keys[b * (G * 32)], sm + O_KT, G * 128);
                WLD(5);
            }
        } else {
#pragma unroll
            for (int i = 0; i < 5; i++) { sts32(sm + O_BOFF + 4 * (lane * 5 + i), e); e += v[i]; }
        }
        __syncwarp();
    }
    TS(11);
    const uint32_t sw = (uint32_t)(((2 * (w & 3) + (mat & 1)) ^ r) * 16 + ((mat >> 1) * 8 + r) * 128);
    const uint32_t lo = (lane & 2) * 64 + (lane & 12) * 8 + (lane & 16) + (lane & 1) * 8;
    uint32_t wr[5][4];
    const uint32_t* kp = &gs->keys[(w * SEGW * G + b) * 32 + ((lane + b) & 31)];
    uint32_t kv[SEGW + 1], ho[SEGW + 1], nk[SEGW + 1], old;
    if (act) {
        uint32_t mx = 0;
#pragma unroll
        for (int i = 0; i < 8; i++) { mx = max(mx, rk[i]); ba[i] = rk[i] + lds32(sm + O_BOFF + ba[i]); }
        if (mx >= 124) {
#pragma unroll
            for (int i = 0; i < 8; i++)
                if (rk[i] >= 124) st_rlx(&gs->more[b * CH + (ba[i] >> 2)], d[i]);
        }
    }
#define WRP 0
    auto ldwr = [&]() {
    if (w < 8) {
        mbar_wait(sm + O_WBA, 0);
#pragma unroll
        for (int p = 0; p < 5; p++) {
            const int c = 2 * p + (w >> 2);
            ldsm4t(wr[p], sm + (c < 5 ? O_WR0 : O_WR1 - 5 * 2048) + c * 2048 + sw);
        }
    } else {
        const uint64_t xl = (uint64_t)(x - 1024 + r * 16) - (tag >> 6), al = (uint64_t)(ea - 32 + (lane & 1) * 16) - (tag >> 4);
        const uint64_t ml = (uint64_t)gs->list + lo;
        const uint32_t row = ((mat & 2 ? mat & 1 ? 0xa9c876b5u : 0xfe4d2130u : mat & 1 ? 0x76b821a3u : 0xc5bfe0cbu) >> 4 * r & 15) + (mat & 2) * 8;
        const uint32_t c[13] = {(uint32_t)xl, (uint32_t)(xl >> 32), (uint32_t)al, (uint32_t)(al >> 32), (uint32_t)ml, (uint32_t)(ml >> 32),
            mat * 2048u + (r ^ 2 * mat) * 16, mat * 2048u + 1024 + (r ^ 2 * mat ^ 1) * 16,
            S_A + (lane & 2) * 128u + g * 32 + ((lane ^ lane >> 4) & 1) * 16, S_C + row * 16, lane & 1 ? 16u : 9u, lane & 30u,
            lane == 4 ? 0xffff0000u : 0u};
#pragma unroll
        for (int i = 0; i < 20; i++) wr[i >> 2][i & 3] = i < 13 ? opaque(c[i % 13], lane) : 0;
    }
    };
    if (!WRP) ldwr();
    TS(21);
    mbar_wait(sm + O_WBC, 0);
    TS(22);
    if (act) {
        uint32_t s[8], y[12];
#pragma unroll
        for (int k = 0; k < 3; k++) *(uint4*)&y[4 * k] = lds128(sm + O_RH + t * 48 + k * 16);
#pragma unroll
        for (int k = 0; k < 2; k++) *(uint4*)&s[4 * k] = lds128(sm + O_SRC + t * 32 + k * 16);
#pragma unroll
        for (int i = 0; i < 8; i++) {
            const int k = 3 * i / 2;
            sts64(sm + O_OUT + ba[i] * 2, __byte_perm(y[k], s[i] + (tag >> 16) + 1, i & 1 ? 0x5432 : 0x5410),
                  i & 1 ? y[k + 1] : __byte_perm(y[k], y[k + 1], 0x5432));
        }
    }
    TS(12);
    __syncthreads();
    if (t == 352) { fence_async(); bulk_st(&gs->vals[b * CH], sm + O_OUT, ne * 8); WLD(7); }
    if (WRP) ldwr();

    const uint32_t am = lane < 31 ? 511 : 0, none = tag | (320 + 4 * lane);
    auto check = [&]() {
        old = 0;
#pragma unroll
        for (int j = 0; j < SEGW; j++) {
            ho[j] = __shfl_sync(0xffffffffu, kv[j], 31);
            kv[j] = ho[j] >= (lane < 31 ? tag + ((lane + 1) << 12) : 0u) ? kv[j] : none;
            old |= kv[j] ^ tag;
        }
        return __any_sync(0xffffffffu, old >> 30);
    };
#pragma unroll
    for (int j = 0; j < SEGW; j++) kv[j] = ld_rlx(kp + j * (G * 32));
    TS(1);
    if (t == 352) WLD(1);
    TV(19, 0); TV(23, 0);
    for (int it = 0; check(); it++) {
        spin_check(it);
        if (it == 0) TS(20);
        TV(19, (it + 1) * 100);
#pragma unroll
        for (int j = 0; j < SEGW; j++)
            if (__any_sync(0xffffffffu, (kv[j] ^ tag) >> 30)) kv[j] = ld_rlx(kp + j * (G * 32));
    }
    TS(3);
    if (t == 352) WLD(2);
    kv[SEGW] = none; ho[SEGW] = 0;
    bool slow = false;
    const bool more = __any_sync(0xffffffffu, lane == 31 && (old & 0xfe0000));
    if (more) {
        int c = lane;
#pragma unroll
        for (int j = 0; j < SEGW; j++) {
            const int n = max((int)(ho[j] >> 12 & 0xfff) - 31, 0);
            if ((unsigned)c < (unsigned)n) ho[SEGW] = j * CH + (ho[j] & 0xfff) + 31 + c - lane;
            c -= n;
        }
        slow = lane == 31 && c < 0;
        if (c < 0 && lane < 31)
            for (int it = 0; ((kv[SEGW] = ld_rlx(&gs->more[w * SEGW * CH + lane + ho[SEGW]])) ^ tag) >> 30; it++) spin_check(it);
        __syncwarp();
    }
#define EV 0
    uint32_t na_[SEGW + 1];
    uint64_t vp = (uint64_t)&gs->vals[w * SEGW * CH + lane], vv[SEGW + 1];
#pragma unroll
    for (int j = 0; j <= SEGW; j++) vv[j] = tag;
    auto ldv = [&](bool again) {
#pragma unroll
        for (int j = 0; j <= SEGW; j++)
            asm volatile("{.reg .pred p; setp.lt.u32 p, %2, 320; @p ld.relaxed.gpu.global.b64 %0, [%1];}" : "+l"(vv[j])
                         : "l"(madw(j < SEGW ? ho[j] & 0xfff : ho[j], 8, vp) + (j < SEGW ? j * CH * 8 : 0)),
                           "r"(again ? (((uint32_t)vv[j] ^ tag) >> 30 ? 0 : 320) : na_[j]) : "memory");
    };
#pragma unroll
    for (int j = 0; j <= SEGW; j++) na_[j] = (kv[j] & am) | (none & 511 & ~am);
    if (EV == 4) ldv(false);
#pragma unroll
    for (int j = 0; j <= SEGW; j++) nk[j] = atoms_add(sm + O_NCNT + na_[j], 512);
    if (EV == 3) ldv(false);
    auto visit = [&](auto f) {
#pragma unroll 1
        for (int j = 0; j < SEGW; j++) {
            const uint32_t* kl = &gs->keys[((w * SEGW + j) * G + b) * 32];
            const uint32_t h = ld_rlx(kl + ((31 + b) & 31));
#pragma unroll 1
            for (int i = lane; i < (h >> 12 & 0xfff); i += 32) {
                const int o = (w * SEGW + j) * CH + (h & 0xfff) + i;
                uint32_t k;
                int it = 0;
                do { k = ld_rlx(i < 31 ? kl + ((i + b) & 31) : &gs->more[o]); spin_check(it++); } while ((k ^ tag) >> 30);
                f(k, o, i);
            }
        }
    };
    slow = __syncthreads_or(slow);
    if (slow) {
        if (t < 80) sts32(sm + O_NCNT + 4 * t, t <= NLOC ? 4 * t : 0);
        __syncthreads();
        visit([&](uint32_t k, int, int) { atoms_add(sm + O_NCNT + (k & 511), 512); });
        __syncthreads();
    }
    TS(4);
    if (t == 352) WLD(3);
    if (EV == 2) ldv(false);
    if (w < 10) {
        const uint32_t key = lds32(sm + O_NCNT + 4 + (t & ~3));
        uint4 k[5];
#pragma unroll
        for (int i = 0; i < 5; i++) k[i] = lds128(sm + O_NCNT + q * 80 + i * 16);
        uint32_t c[4] = {0, 0, 0, 0};
#pragma unroll
        for (int i = 0; i < 5; i++) { c[0] += (key - k[i].x) >> 31; c[1] += (key - k[i].y) >> 31; c[2] += (key - k[i].z) >> 31; c[3] += (key - k[i].w) >> 31; }
        int rank = c[0] + c[1] + c[2] + c[3];
        rank += __shfl_xor_sync(0xffffffffu, rank, 1);
        rank += __shfl_xor_sync(0xffffffffu, rank, 2);
        if (ASC && rank < 2 * NPRIV) rank = (2 * NPRIV - 1 - rank) ^ 1;
        if (t < NLOC * 4) sts32(sm + O_SORT + 4 * rank, key);
    }
    if (EV == 5) ldv(false);
    __syncthreads();
    TS(2);
    const bool on = lane < NLOC / 4;
    const uint4 k4 = lds128(sm + O_SORT + 16 * (on ? lane : 0));
    if (EV == 1) ldv(false);
    const uint32_t ks[4] = {k4.x, k4.y, k4.z, k4.w};
    const int n0 = on ? max(1u, (ks[0] + 3584) >> 12) : 0, n1 = on ? max(1u, (ks[2] + 3584) >> 12) : 0;
    const int u2 = warp_incl(n0 + n1), u1 = u2 - n1, u0 = u1 - n0;
    const int total = __shfl_sync(0xffffffffu, u2, 31);
    slow |= total > CAPT;
    const int m0 = slow ? n0 : HT ? max(2u, (ks[0] + 1536) >> 11) : 2 * n0, m1 = slow ? n1 : HT ? max(2u, (ks[2] + 1536) >> 11) : 2 * n1;
    int gbase = b * CAPT + 1;
    if (on) {
#pragma unroll
        for (int i = 0; i < 4; i++) {
            const int a = ks[i] & 511, node = a * (G / 4) - G + b, o = (i >> 1 ? u1 : u0) * 256 + (i & 1) * 16;
            const uint32_t mk = (node < NN ? node + 1 : 0) + ((i >> 1 ? m1 : m0) << 16);
            sts64(sm + O_NOFF + 2 * a, o - (a >> 4), mk + a * 32);
            if (!slow && ks[i] < 512) sts32(sm + O_L + 4 + o, mk);
        }
    }
    __syncwarp();
    if (t == 352) WLD(8);
    if (!slow) {
        uint32_t mk[SEGW + 1];
        TS(13);
        if (t == 352) { asm volatile("cp.async.bulk.wait_group.read 0;" ::: "memory"); }
        if (EV == 0) ldv(false);
        if (t == 352) WLD(4);
        TS(16);
#pragma unroll
        for (int j = 0; j <= SEGW; j++) {
            const uint2 o = lds64(sm + O_NOFF + 2 * na_[j]);
            mk[j] = o.y - nk[j] * 32; nk[j] = o.x + (nk[j] >> 4);
        }
        for (int it = 0;; it++) {
            old = 0;
#pragma unroll
            for (int j = 0; j <= SEGW; j++) old |= (uint32_t)vv[j] ^ tag;
            if (!__any_sync(0xffffffffu, old >> 30)) break;
            spin_check(it);
            vp = __shfl_sync(0xffffffffu, vp, lane);
            ldv(true);
            TV(23, (it + 1) * 100);
        }
        TS(17);
#pragma unroll
        for (int j = 0; j <= SEGW; j++)
            asm volatile("{.reg .pred p; setp.ne.u32 p, %3, %5; @p st.shared.v4.u32 [%0], {%1,%2,%3,%4};}"
                         ::"r"(sm + O_L + nk[j]), "r"(kv[j]), "r"(mk[j]), "r"((uint32_t)vv[j]), "r"((uint32_t)(vv[j] >> 32)), "r"(tag) : "memory");
        TS(18);
        if (na_[SEGW] < 320) gs->more[w * SEGW * CH + lane + ho[SEGW]] = 0;
    } else {
        int so = 0;
        if (t == 352) WLD(4);
#pragma unroll
        for (int j = 0; j < SEGW; j++) so += ho[j] & 0xfff;
        if (lane == 0) atoms_add(sm + O_SUM, so);
        if (t == 352) asm volatile("cp.async.bulk.wait_group.read 0;" ::: "memory");
        __syncthreads();
        gbase = TBIG + (lds32(sm + O_SUM) >> 3) + (NLOC + 5) * b;
        auto put = [&](uint32_t k, uint64_t e, uint32_t a, int rank) {
            const uint2 o = lds64(sm + O_NOFF + 2 * a);
            const uint32_t m = o.y - a * 32 - (rank << 13);
            gs->list[gbase * 16 + ((o.x + (a >> 4)) >> 4) + rank * 2] = make_uint4(k, (m & 0xffff) | min(m >> 16, 0x7fffu) << 17, e, e >> 32);
        };
        visit([&](uint32_t k, int o, int i) {
            uint64_t e;
            int it = 0;
            do {
                asm volatile("ld.relaxed.gpu.global.b64 %0, [%1];" : "=l"(e) : "l"(&gs->vals[o]) : "memory");
                spin_check(it++);
            } while (((uint32_t)e ^ tag) >> 30);
            if (i >= 31) gs->more[o] = 0;
            put(k, e, k & 511, atoms_add(sm + O_NCUR + (k & 511), 1));
        });
#pragma unroll 1
        for (int i = 0; i < 4; i++) {
            const uint32_t k = i == 0 ? ks[0] : i == 1 ? ks[1] : i == 2 ? ks[2] : ks[3];
#pragma unroll 1
            for (int p = (k >> 9) + w; p < (i >> 1 ? n1 : n0) * 8; p += NT / 32) put(0, 0, k & 511, p);
        }
        __threadfence();
    }
    if (t == 352) WLD(9);
    const uint32_t iw0 = (gbase + u0) << 12 | n0, iw1 = (gbase + u1) << 12 | n1;
    __syncthreads();
    TS(5);

    if (w >= 8) {
        asm volatile("setmaxnreg.dec.sync.aligned.u32 " STR(PREG) ";");
        const int h = __reduce_max_sync(0xffffffffu, w & 3);
        if (h == 0) TSW(28);
        gbase = __reduce_min_sync(0xffffffffu, iw0) >> 12;
        int pos = gbase + h, end = __reduce_max_sync(0xffffffffu, lane == NPRIV / 2 ? (NPRIV & 1 ? iw1 : iw0) : 0) >> 12;
        const int bytes = gbase < TBIG ? ((__reduce_max_sync(0xffffffffu, iw0) >> 12) - gbase) * 256 : 0;
        const uint32_t ring = sm + O_RING;
        const uint64_t xl = wr[0][0] | (uint64_t)wr[0][1] << 32, al = wr[0][2] | (uint64_t)wr[0][3] << 32, ml = wr[1][0] | (uint64_t)wr[1][1] << 32;
        const uint32_t xoff[2] = {wr[1][2], wr[1][3]}, aoff = wr[2][0], coff = wr[2][1], sh = wr[2][2], ial = wr[2][3], sel = wr[3][0];
        auto lde = [&](uint2& e, int p) {
            asm volatile("{.reg .pred p; setp.gt.s32 p, %3, 0; @p ld.relaxed.gpu.global.v2.u32 {%0,%1}, [%2];}" : "+r"(e.x), "+r"(e.y) : "l"(madw(p, 256, ml)), "r"(p) : "memory");
        };
        uint2 e0[3] = {};
#pragma unroll
        for (int k = 0; k < 3; k++) {
            e0[k] = lds64(sm + O_L + k * 1024 + h * 256 + ((uint32_t)ml & 255));
            lde(e0[k], bytes ? 0 : pos + 4 * k);
        }
        if (h == 3) fence_async();
        else if (B4) asm volatile("bar.arrive 4, %0;" ::"n"(NT) : "memory");
        pos += 4;

        int ev = 0, state = -2, tk = 0, nr = 0;
        uint32_t inf = 0;
        int ii = 0;
        auto take = [&]() {
            int v = 0;
            asm volatile("{.reg .pred p; setp.eq.s32 p, %2, 0; @p atom.relaxed.gpu.global.add.u32 %0, [%1], 1;}" : "+r"(v) : "l"(&gs->ticket), "r"(lane) : "memory");
            return v;
        };
        auto resolve = [&]() {
            const int k = __reduce_max_sync(0xffffffffu, tk);
            inf = tag;
            if (k < G * NPOOL) { const int l = k / G; ii = (k - l * G) * NPOOL + l; inf = ld_rlx(&gs->info[ii]);
                const int j = NPRIV + 1 + nr + (STAG), gd = __reduce_max_sync(0xffffffffu, lds32(sm + O_SUM + 4));
                tk = (QOK) && (j & ~7) > gd + GM && k >= G * NPOOL - (j & 7 ? THETB : THETA) ? G * NPOOL : take(); }
        };
        uint32_t so = ring + h * SLOT, ph = 0x80000000u;
        uint32_t spins = 0;
        asm volatile(".reg .pred z<5>;");
#define HD 300
        { const uint32_t c0 = clock(); while (__any_sync(0xffffffffu, (uint32_t)clock() - c0 < h * HD)); }
        while (true) {
            const uint2 e = e0[0];
            const uint32_t o = e.x >> sh, id = __shfl_sync(0xffffffffu, o, ial);
            uint32_t s[4];
#pragma unroll
            for (int j = 0; j < 4; j++) s[j] = __shfl_sync(0xffffffffu, o, 2 * j + 1, 8);
            const uint32_t nx = so == ring + (NSLOT - 1) * SLOT ? ph : ph ^ 0x80000000u, ey = lop_sel(e.y, nx, sel);
            const uint32_t y0 = __shfl_xor_sync(0xffffffffu, e.x, 1), ym = lane & 1 ? e.y : y0;
            const bool full = __ballot_sync(0xffffffffu, e.y >> 16 != 1) & 1;
            const uint64_t ga = madw(id, 32, al);
            uint64_t gx[4];
#pragma unroll
            for (int j = 0; j < 4; j++) gx[j] = madw(s[j], 1024, xl);
            const uint32_t da = so + aoff, dx[2] = {so + xoff[0], so + xoff[1]}, dc = so + coff;
            asm volatile("setp.eq.u32 z0, %0, 0;\nsetp.eq.u32 z1, %1, 0;\nsetp.eq.u32 z2, %2, 0;\nsetp.eq.u32 z3, %3, 0;\nsetp.eq.u32 z4, %4, 0;\n"
                         ::"r"(NULLP(s[0])), "r"(NULLP(s[1])), "r"(NULLP(s[2])), "r"(NULLP(s[3])), "r"(id), "l"(ga), "r"(da), "r"(dx[0]), "r"(dx[1]), "r"(dc));
            if (EPF) asm volatile("@!z4 prefetch.global.L2 [%0];" ::"l"(ga) : "memory");
            lde(e0[0], state < 0 ? 0 : pos);
            if (HS == 2) asm volatile("{.reg .pred p; setp.eq.s32 p, %1, -2; @p bar.arrive 5, %0;}" ::"n"(NT), "r"(state) : "memory");
            if (h == 0 && state == -2) TSW(29);
            if (h == 0 && state == -1) TSW(30);
            asm volatile("{\n.reg .pred p;\n.reg .b64 s;\nmov.b64 s, {0, %2};\n"
                         "LOOP:\nmbarrier.try_wait.shared::cta.b64 p, [%1], s;\n@p bra DONE;\n"
                         "add.u32 %0, %0, 1;\nsetp.gt.u32 p, %0, %3;\n@p trap;\nbra LOOP;\nDONE:\n}"
                         : "+r"(spins) : "r"(so + S_EMPTY), "r"(ph), "n"(SPIN_LIMIT) : "memory");
            asm volatile("cp.async.cg.shared.global" EH " [%0], [%1], 16, z4;" ::"r"(da), "l"(ga) : "memory");
#define ROW(j) _Pragma("unroll") for (int k = 0; k < 8; k++) \
                asm volatile("cp.async.cg.shared.global [%0], [%1], 16, z" #j ";" ::"r"(dx[j >> 1] + (j & 1) * 8192 + k * 128), "l"(gx[j] + k * 128) : "memory")
            ROW(0); ROW(2);
            if (full) { ROW(1); ROW(3); }
            stsm4t(dc, e.x, ey, lane < 16 ? ym : 0, lane < 16 ? 0 : ym);
            asm volatile("cp.async.mbarrier.arrive.noinc.shared::cta.b64 [%0];" ::"r"(so + S_FULL) : "memory");
            const bool wrap = NSLOT == 5 ? so != ring : so >= ring + (NSLOT - 4) * SLOT;
            ph ^= wrap ? 0x80000000u : 0u;
            so = wrap ? so - (NSLOT - 4) * SLOT : so + 4 * SLOT;
            pos += 4;
            if (pos >= ev) {
                if (state < 0) {
                    e0[0] = e0[1]; e0[1] = e0[2];
                    if (state == -2) {
                        if (h == 0) TSW(24);
                        if (h == 3) TSW(25);
                        if (HS == 1) asm volatile("bar.arrive 5, %0;" ::"n"(NT) : "memory");
                        if (HS >= 4 && h == HS - 4) asm volatile("bar.arrive 5, 288;" ::: "memory");
                        if (h < 3) bar_sync(7, 352);
                        if (h == 3) bar_sync(4, NT);
                        if (h == 0) mbar_wait(sm + O_WBE, 0);
                        if (h == 3) {
                            if (lane == 0) {
                                if (bytes) bulk_st(gs->list + gbase * 16, sm + O_L, bytes);
                                asm volatile("cp.async.bulk.wait_group.read 0;" ::: "memory");
                            }
                            __syncwarp();
                            if (lane == 0) {
                                for (int j = KR; j < 24; j++) tma3d(sm + O_W1 + (j - KR) * 4096, &m_w1, 16 * j, 0, sm + O_WBB);
                            }
                            __syncwarp();
                        }
                        state = -1;
                    } else {
                        if (h == 3) {
                            if (lane == 0) asm volatile("cp.async.bulk.wait_group 0;\nfence.proxy.async;" ::: "memory");
                            __syncwarp();
                            const int i = opaque(2 * lane - NPRIV, lane);
                            if ((unsigned)i < NPOOL) st_rlx(&gs->info[b * NPOOL + i], tag | iw0);
                            if ((unsigned)(i + 1) < NPOOL) st_rlx(&gs->info[b * NPOOL + i + 1], tag | iw1);
                        }
                        bar_sync(6, 128);
                        ev = h ? end : end - 12; state = h ? 2 : 0;
                    }
                } else if (state == 0) { ev = end - 6; state = 1; tk = take(); }
                else if (state == 1) { resolve(); ev = end; state = 2; }
                else {
                    if (state == 3) break;
                    do {
                        const uint32_t mb = sm + O_MB + (nr & 15) * 8;
                        uint32_t rg;
                        nr++;
                        if (h == 0) {
                            for (int it = 0; (rg = __reduce_max_sync(0xffffffffu, inf ^ tag)) >> 30; it++) { spin_check(it); inf = ld_rlx(&gs->info[ii]); }
                            asm volatile("st.release.cta.shared.b64 [%0], %1;" ::"r"(mb), "l"(rg | (uint64_t)nr << 32) : "memory");
                            if (rg) resolve();
                        } else {
                            uint64_t m;
                            for (int it = 0;; it++) {
                                asm volatile("ld.acquire.cta.shared.b64 %0, [%1];" : "=l"(m) : "r"(mb) : "memory");
                                if (__all_sync(0xffffffffu, (int)(m >> 32) == nr)) break;
                                spin_check(it);
                            }
                            rg = __reduce_max_sync(0xffffffffu, (uint32_t)m);
                        }
                        pos = rg ? (int)(rg >> 12) + pos - end : 0;
                        end = rg ? (rg >> 12) + (rg & 0xfff) : 1;
                        state = rg ? 2 : 3;
                    } while (pos >= end);
                    ev = end;
                }
            }
        }
        mbar_wait31(so + S_EMPTY, ph);
        TSW(8 + (h & 1));
        if (lane == 0) sts32(so + S_N, 0);
        mbar_arrive(so + S_FULL);
        if (t == 256) {
            gs->epoch[b * 32] = (tag >> 30) % 3;
            if (atomicInc(&gs->done, G - 1) == G - 1) gs->ticket = 0;
        }
        asm volatile("cp.async.wait_all;" ::: "memory");
    } else {
        asm volatile("setmaxnreg.inc.sync.aligned.u32 " STR(CREG) ";");
        if (HS && !HL) bar_sync(5, HS < 4 ? NT : 288);
        const uint32_t xa = opaque(((mat >> 1) * 8 + r) * 1024 + (w >> 2) * 128 + (((2 * (w & 3) + (mat & 1)) ^ r) * 16), lane);
        const uint32_t aa = opaque(S_A + ((mat >> 1) * 8 + r) * 32 + (((mat & 1) ^ (r >> 2)) * 16), lane);
        const uint32_t ya = opaque(S_C + (mat & 1) * 80 + (mat >> 1) * 16, lane);
        const uint32_t yc = opaque(S_C + (mat < 2 ? mat * 80 + 32 : q < 3 ? mat * 128 + ((r >> 2) ^ (mat & 1)) * 80 + q * 16 : 64), lane);
        const uint32_t na = opaque((mat & 1) * 8, lane);
        const uint32_t pw = sm + O_P + w * PW;
        const uint32_t fx = opaque(pw + (q < 3 ? P_1P0 + 2 * q * PSBO : P_1P1 + PSBO) + (mat & 1) * 128 + (r >> 2) * PSBO, lane);
        const uint32_t fyz = opaque(pw + (q < 3 ? (mat < 2 ? P_1P1 : P_1P2) + 2 * q * PSBO : mat < 2 ? P_0P0 : P_0P1) + (mat & 1) * 128 + (r >> 2) * PSBO, lane);
        uint32_t oh[MA ? 5 : 8];
#pragma unroll
        for (int c = 0; c < (MA ? 5 : 8); c++) oh[c] = opaque(g == (q >> 1) * 4 + (MA ? min(c, 3) : c & 3) ? 0x3F803F80u : 0u, lane ^ c >> 2);
        uint32_t eb[3];
#pragma unroll
        for (int k = 0; k < 3; k++) {
            const int i = (g & 3) * 9 + (q & 1) * 6 + k;
            const uint32_t lo = __shfl_sync(0xffffffffu, epl, i), hi = __shfl_sync(0xffffffffu, epl, i + 3);
            eb[k] = (g & 3) < 3 && (q >> 1) == (g >> 2) ? (q & 1 ? lo : lo | hi << 16) : 0u;
        }
        asm volatile(".reg .pred lane0;\nsetp.eq.u32 lane0, %0, 0;" ::"r"(lane));
        uint32_t w0[16][4], w1[KR][4];
        mbar_wait(sm + O_WBD, 0);
        if (HS && HL) bar_sync(5, HS < 4 ? NT : 288);
#pragma unroll
        for (int k = 0; k < 16; k++) ldsm4t(w0[k], sm + w0s(k >> 2) + (w >> 2) * 8192 + (k & 3) * 2048 + sw);
#pragma unroll
        for (int k = 0; k < KR; k++) ldsm4t(w1[k], sm + w1s(k) + (w >> 2) * 2048 + sw);
        if (B4) asm volatile("bar.arrive 4, %0;" ::"n"(NT) : "memory");
        bar_sync(7, B4 ? 352 : NT);
        TS(6);
        Acc A;
#pragma unroll
        for (int i = 0; i < 4; i++) { A.p[0][AI(i)] = A.p[1][AI(i)] = A.p[2][AI(i)] = A.p[3][AI(i)] = A.p[4][AI(i)] = 0; A.t01[i] = A.m[0][i] = A.m[1][i] = A.m[2][i] = 0.f; }
        uint32_t room = 144 - (STAG) * 16;
        uint32_t so = sm + O_RING, ph, a[4], ok, go, mt = 0;
        mbar_wait(so + S_FULL, 0);
        ldsm4(a, so + aa);
        TS(7);
        while (true) {
            {
                constexpr int F = 1, H = 0, XS = XS_F;
                int seen = 0;
                uint32_t yb[8], f[4][4], R[5][4], u[4][4], sd[4];
                float y[4], z[4];
                const uint32_t sof = room & 112;
                room -= 16;
                SEQ_F
            }
            if (!(go && room)) {
                const uint32_t pu = __reduce_max_sync(0xffffffffu, ph);
                if (!room || !pu) {
                    if (GD == 2) asm volatile("@lane0 red.shared.add.u32 [%0], 1;" ::"r"(sm + O_SUM + 4) : "memory");
                    GT(0);
                    const uint32_t wg = __reduce_max_sync(0xffffffffu, w >> 2);
                    if (!FEN) asm volatile("fence.proxy.async.shared::cta;" ::: "memory");
                    mbar_wait(sm + O_WBB, 0);
                    GT(1);
                    if (ALT == 1) asm volatile("{.reg .pred p; setp.ne.u32 p, %0, 0;\n@p bar.arrive 1, 256;\n@p bar.sync 2, 256;\n@!p bar.sync 1, 256;}" ::"r"(wg ^ AWG) : "memory");
                    else bar_sync(1, 256);
                    if (FEN) asm volatile("fence.proxy.async::generic.acquire.sync_restrict::shared::cluster.cluster;" ::: "memory");
                    GT(2);
                    float d0[8], d1[24];
                    const uint64_t db = (uint64_t)((sm + O_P) >> 4) | (8ull << 16) | ((uint64_t)(PSBO / 16) << 32);
                    const uint32_t da = ((sm + O_W1) >> 4 | 1 << 16) + wg * 128;
                    asm volatile("wgmma.fence.sync.aligned;" ::: "memory");
                    if (!IL) {
#pragma unroll
                        for (int k = 0; k < 16; k++) G0(k);
                        asm volatile("wgmma.commit_group.sync.aligned;" ::: "memory");
                    }
                    const uint32_t sp = so == sm + O_RING ? sm + O_RING + (NSLOT - 1) * SLOT : so - SLOT, sr = (r & 6) + (mat & 1);
                    const uint32_t nd = (sr * 16 - 16 & 112) >= room ? lds32(sm + O_NODE + sr * 16 + (mat >> 1) * 8) : 0;
                    const uint64_t oa = madw(nd, 1024, (uint64_t)(out - 1024 + w * 32 + (r & 1) * 16));
                    const uint32_t sl = sp + ((mat >> 1) * 8 + sr) * 1024 + (w >> 2) * 128 + (((2 * (w & 3) + (r & 1)) ^ sr) * 16);
                    auto put = [&](int j) {
                        const uint4 v = lds128(sl + j * 256);
                        asm volatile("{.reg .pred p; setp.ne.u32 p, %5, 0; @p st.global.v4.u32 [%0], {%1,%2,%3,%4};}"
                                     ::"l"(oa + j * 256), "r"(v.x), "r"(v.y), "r"(v.z), "r"(v.w), "r"(nd) : "memory");
                    };
                    float gt[8];
#pragma unroll
                    static_for<25>([&](auto kc) {
                        constexpr int k = kc.value;
                        if (IL && k == 16 / (IL + !IL)) asm volatile("wgmma.commit_group.sync.aligned;" ::: "memory");
                        if (ALT == 1 && k == ASP) asm volatile("{.reg .pred p; setp.eq.u32 p, %0, 0;\n@p bar.arrive 2, 256;}" ::"r"(wg ^ AWG) : "memory");
                        if (k == GP || k == 24) asm volatile("wgmma.commit_group.sync.aligned;" ::: "memory");
                        if (k == GP) {
                            asm volatile("wgmma.wait_group.sync.aligned 1;" ::: "memory");
#pragma unroll
                            for (int i = 0; i < 8; i++) asm volatile("" : "+f"(d0[i])::"memory");
                            stsm4t(sp + xa, pack(d0[0], d0[1]), pack(d0[2], d0[3]), pack(d0[4], d0[5]), pack(d0[6], d0[7]));
                            __syncwarp();
                        }
                        if (k == min(GP + GS, 24)) put(0);
#pragma unroll
                        for (int i = 0; i < 8; i++) {
                            if (k == min(GP + i / 2 * GS, 24)) asm volatile("ex2.approx.ftz.f32 %0, %1;" : "=f"(gt[i]) : "f"(d0[i] * -1.4426950408889634f) : "memory");
                            if (k == min(GP + (i / 2 + 1) * GS, 24)) asm volatile("rcp.approx.ftz.f32 %0, %1;" : "=f"(gt[i]) : "f"(gt[i] + 1.f) : "memory");
                        }
                        if (k == min(GP + 5 * GS, 24)) {
                            uint32_t chk = -1;
#pragma unroll
                            for (int i = 0; i < 8; i++) chk &= __float_as_uint(gt[i]);
                            sts32(sm + O_TRASH, chk);
                        }
                        if (k < 24) G1(k % 24);
#pragma unroll
                        for (int i = 0; i < IL; i++) if (k * IL + i < 16) G0((k * IL + i) % 16);
                    });
                    GT(3);
                    asm volatile("wgmma.wait_group.sync.aligned 0;" ::: "memory");
                    GT(4);
#pragma unroll
                    for (int i = 0; i < 24; i++) asm volatile("" : "+f"(d1[i])::"memory");
                    if (ALT == 1) asm volatile("{.reg .pred p; setp.ne.u32 p, %0, 0;\n@p bar.sync 3, 256;}" ::"r"(wg ^ AWG) : "memory");
#pragma unroll
                    for (int j = 0; j < 3; j++) {
                        uint32_t o[4];
#pragma unroll
                        for (int i = 0; i < 4; i++) o[i] = pack(d1[8 * j + 2 * i] * gt[2 * i], d1[8 * j + 2 * i + 1] * gt[2 * i + 1]);
                        stsm4t(sp + xa + 256 + j * 256, o[0], o[1], o[2], o[3]);
                    }
                    __syncwarp();
#pragma unroll
                    for (int j = 1; j < 4; j++) put(j);
                    __syncwarp();
                    asm volatile("@lane0 mbarrier.arrive.shared::cta.b64 _, [%0];" ::"r"(sp + S_EMPTY) : "memory");
                    if (GD == 1) asm volatile("@lane0 red.shared.add.u32 [%0], 1;" ::"r"(sm + O_SUM + 4) : "memory");
                    GT(5);
                    if (ALT == 1) asm volatile("{.reg .pred p; setp.eq.u32 p, %0, 0;\n@p bar.sync 3, 256;}" ::"r"(wg ^ AWG) : "memory");
                    else bar_sync(3, 256);
                    GT(6);
                    room = 128;
                    if (!pu) break;
                }
                if (!ok) { mbar_wait31(so + S_FULL, pu); ldsm4(a, so + aa); }
                if (!(pu & 0xfffc)) { if (pu & 1) goto half; continue; }
            }
            while (true) {
                do {
                    constexpr int F = 0, H = 0, XS = XS_R;
                    int seen = 0;
                    uint32_t yb[8], f[4][4], R[5][4], u[4][4], sd[4];
                    SEQ_R
                } while (go);
                if (ok) {
                    asm volatile("{.reg .pred p; .reg .f32 n; abs.f32 n, %1; setp.gt.f32 p, n, 0f00000002; selp.u32 %0, 1, 0, p;}" : "=r"(go) : "r"(ph));
                    break;
                }
                const uint32_t pu = __reduce_max_sync(0xffffffffu, ph);
                mbar_wait31(so + S_FULL, pu); ldsm4(a, so + aa);
                if (!(pu & 0xfffc)) { go = pu & 1; break; }
            }
            if (!go) continue;
        half: {
                constexpr int F = 0, H = 1, XS = XS_H;
                int seen = 0;
                uint32_t yb[8], f[4][4], R[5][4], u[4][4], sd[4];
                SEQ_H
                if (!ok) { mbar_wait31(so + S_FULL, __reduce_max_sync(0xffffffffu, ph)); ldsm4(a, so + aa); }
            }
        }
        TS(10);
    }
}

typedef CUresult (*EncFn)(CUtensorMap*, CUtensorMapDataType, cuuint32_t, void*, const cuuint64_t*, const cuuint64_t*,
                          const cuuint32_t*, const cuuint32_t*, CUtensorMapInterleave, CUtensorMapSwizzle,
                          CUtensorMapL2promotion, CUtensorMapFloatOOBfill);

void make_map(EncFn fn, CUtensorMap* m, void* p, int rows, int cols, int brows, int bcols, int bblk) {
    cuuint64_t dims[3] = {64, (cuuint64_t)rows, (cuuint64_t)cols / 64}, strides[2] = {(cuuint64_t)cols * 2, 128};
    cuuint32_t box[3] = {(cuuint32_t)bcols, (cuuint32_t)brows, (cuuint32_t)bblk}, es[3] = {1, 1, 1};
    fn(m, CU_TENSOR_MAP_DATA_TYPE_BFLOAT16, 3, p, dims, strides, box, es, CU_TENSOR_MAP_INTERLEAVE_NONE,
       bcols == 64 ? CU_TENSOR_MAP_SWIZZLE_128B : CU_TENSOR_MAP_SWIZZLE_NONE, CU_TENSOR_MAP_L2_PROMOTION_L2_128B, CU_TENSOR_MAP_FLOAT_OOB_FILL_NONE);
}

}

extern "C" void kernel_launch(void* const* d_in, const int* in_sizes, int n_in, void* d_out, int out_size) {
    static EncFn enc = nullptr;
    static void* scratch = nullptr;
    if (!enc) {
        void* fn = nullptr;
        cudaDriverEntryPointQueryResult qr;
        cudaGetDriverEntryPoint("cuTensorMapEncodeTiled", &fn, cudaEnableDefault, &qr);
        enc = (EncFn)fn;
        cudaGetSymbolAddress(&scratch, g_scratch);
        cudaFuncSetAttribute(tp_kernel, cudaFuncAttributeMaxDynamicSharedMemorySize, SMEM_BYTES);
    }
    CUtensorMap m_wr, m_w0, m_w1, m_x;
    make_map(enc, &m_wr, d_in[5], 16, 640, 16, 64, 5);
    make_map(enc, &m_w0, d_in[6], 256, 128, 64, 64, 2);
    make_map(enc, &m_w1, d_in[7], 384, 128, 16, 64, 2);
    make_map(enc, &m_x, d_in[0], NN * 8, 64, NLOC * 2, 8, 1);
    tp_kernel<<<G, NT, SMEM_BYTES>>>((const int4*)d_in[4], (const int4*)d_in[3], (const char*)d_in[1], (Scratch*)scratch,
                                     (const char*)d_in[0], (const char*)d_in[2], (const __nv_bfloat16*)d_in[8], (char*)d_out,
                                     m_wr, m_w0, m_w1, m_x);
}
```

```cpp
#include <cuda_runtime.h>
#include <cuda_bf16.h>
#include <cuda.h>
#include <stdint.h>
#include <stddef.h>

namespace {

constexpr int NN = 10000;
constexpr int NE = 320000;
constexpr int G = 132;
constexpr int NT = 384;
constexpr int CH = 2432;
constexpr int NLOC = (NN + G - 1) / G;
constexpr int NPOOL = 3;
constexpr int NPAIR = NLOC / 2, NPRIV = NPAIR - NPOOL;
constexpr int SEGW = 11;

constexpr int NSLOT = 7;
constexpr int KR = 9;
constexpr uint32_t WP = 0x5357575, TP = 0x9375;
#define WLD(p) { _Pragma("unroll") for (int j = 0; j < 4 + KR; j++) if ((WP >> 4 * (j < 4 ? j : j < 8 ? 4 : j < 11 ? 5 : 6) & 15) == p) \
    tma3d(sm + (j < 4 ? w0s(j) : w1s(j - 4)), j < 4 ? &m_w0 : &m_w1, j < 4 ? j * 64 : (j - 4) * 16, 0, sm + O_WBD); \
    _Pragma("unroll") for (int j = 0; j < 4; j++) { const int r0 = (b * 4 + j) * (NLOC / 4); \
        if ((TP >> 4 * j & 15) == p) tma3d(sm + O_WR1 + 12288, &m_x, r0 * 8, 0, sm + O_WBE); } }

constexpr int S_A = 16384, S_C = S_A + 512, S_FULL = S_C + 144, S_EMPTY = S_FULL + 8, S_N = S_C + 160, SLOT = S_C + 512;

constexpr int PSBO = 272;
constexpr int PB1 = 5 * PSBO + 256, PB0 = PSBO + 256;
constexpr int P_1P0 = 0, P_1P1 = PB1, P_0P1 = 2 * PB1, P_0P0 = P_0P1 + PB0, P_1P2 = P_0P0 + PB0;
constexpr int PW = P_1P2 + PB1;

constexpr int O_W1 = 0;
constexpr int O_P = 62336;
constexpr int O_RING = O_P + 8 * PW;
constexpr int O_WBA = O_RING + NSLOT * SLOT, O_WBB = O_WBA + 8, O_WBC = O_WBA + 16, O_WBD = O_WBA + 24, O_WBE = O_WBA + 32, O_TRASH = O_WBA + 40, O_NODE = O_WBA + 48;
constexpr int O_SUM = O_NODE + 128, O_MB = O_SUM + 16;
constexpr int SMEM_BYTES = O_MB + 128;
constexpr int CAPT = 192;
constexpr int O_L = 0, LZ = CAPT * 256 / (NT * 16), O_W0S = O_L + CAPT * 256, O_OUT = O_RING + S_C - CH * 8, O_SRC = O_RING + 6 * SLOT;
constexpr int O_KT = O_RING + SLOT, O_RH = O_RING + 2 * SLOT;
constexpr int O_WR0 = O_RING + 3 * SLOT, O_WR1 = O_RING + 4 * SLOT;
__host__ __device__ constexpr int w0s(int j) { return j < 3 ? O_W0S + j * 16384 : O_SRC; }
__host__ __device__ constexpr int w1s(int k) { return k < 4 ? O_RING + 5 * SLOT + k * 4096 : k < 7 ? O_WR1 + (k - 4) * 4096 : O_W0S + 49152 + (k - 7) * 4096; }
constexpr int O_BCNT = O_WR0 + 10240, O_NCUR = O_BCNT + 640, O_NCNT = O_NCUR + 320;
constexpr int O_BOFF = O_NCNT + 512, O_SORT = O_BOFF + 640, O_NOFF = O_SORT + 320;
constexpr int TBIG = G * CAPT + 8, NTILE = TBIG + NE / 8 + G * (NLOC + 5);
static_assert(SMEM_BYTES <= 232448 && CAPT % 16 == 0 && NTILE < (1 << 18), "smem");
static_assert(LZ * NT * 16 == CAPT * 256 && O_W0S % 1024 == 0 && w1s(KR) <= O_OUT && O_OUT % 128 == 0 && CH * 6 <= S_C && G * 128 <= S_C, "staging");
static_assert(O_NOFF + 1024 <= O_RING + 3 * SLOT + S_C && 12288 + NLOC * 32 <= S_C && (24 - KR) * 4096 <= O_P && KR <= 9, "staging");
static_assert(O_RING % 1024 == 0 && SLOT % 1024 == 0 && O_W0S <= O_P && O_NOFF % 8 == 0, "layout");
static_assert(G * CH >= NE && NE % 8 == 0 && CH < 4096 && CH / 8 <= 320 && NE < (1 << 21), "chunks");
static_assert(SEGW * (NT / 32) == G && G <= 160 && G % 4 == 0, "segments");
static_assert(NLOC % 4 == 0 && NLOC < 80 && NLOC * 4 <= 320 && NN < 0x3fff && NE / 8 < 0xbfff && NPRIV >= 30, "scan width");

struct __align__(256) Scratch {
    uint32_t keys[G * G * 32];
    uint64_t vals[G * CH];
    uint32_t more[G * CH];
    uint32_t epoch[G * 32];
    uint32_t info[(G * NPOOL + 127) / 128 * 128];
    unsigned done, pad0[31], ticket, pad1[31];
    uint4 list[NTILE * 16];
};
static_assert(offsetof(Scratch, list) % 256 == 0, "list");
__device__ Scratch g_scratch;
#define TS(i)
#define TSW(i)
#define TV(i, v)

constexpr int SPIN_LIMIT = 1 << 24;

__device__ __forceinline__ void mbar_init(uint32_t a, int c) { asm volatile("mbarrier.init.shared::cta.b64 [%0], %1;" ::"r"(a), "r"(c) : "memory"); }
__device__ __forceinline__ void mbar_expect(uint32_t a, int b) { asm volatile("mbarrier.arrive.expect_tx.shared::cta.b64 _, [%0], %1;" ::"r"(a), "r"(b) : "memory"); }
__device__ __forceinline__ void mbar_arrive(uint32_t a) { asm volatile("mbarrier.arrive.shared::cta.b64 _, [%0];" ::"r"(a) : "memory"); }
__device__ __forceinline__ void mbar_wait(uint32_t a, uint32_t ph) {
    asm volatile("{\n.reg .pred p, q;\n.reg .u32 it;\n"
                 "mbarrier.try_wait.parity.shared::cta.b64 p, [%0], %1;\n"
                 "@p bra DONE;\n"
                 "mov.u32 it, 0;\n"
                 "LOOP:\n"
                 "mbarrier.try_wait.parity.shared::cta.b64 p, [%0], %1;\n"
                 "@p bra DONE;\n"
                 "add.u32 it, it, 1;\n"
                 "setp.gt.u32 q, it, %2;\n"
                 "@q trap;\n"
                 "bra LOOP;\n"
                 "DONE:\n}" ::"r"(a), "r"(ph), "n"(SPIN_LIMIT) : "memory");
}
__device__ __forceinline__ void mbar_wait31(uint32_t a, uint32_t ph) {
    asm volatile("{\n.reg .pred p, q;\n.reg .u32 it;\n.reg .b64 s;\n"
                 "mov.b64 s, {0, %1};\n"
                 "mbarrier.try_wait.shared::cta.b64 p, [%0], s;\n"
                 "@p bra DONE;\n"
                 "mov.u32 it, 0;\n"
                 "LOOP:\n"
                 "mbarrier.try_wait.shared::cta.b64 p, [%0], s;\n"
                 "@p bra DONE;\n"
                 "add.u32 it, it, 1;\n"
                 "setp.gt.u32 q, it, %2;\n"
                 "@q trap;\n"
                 "bra LOOP;\n"
                 "DONE:\n}" ::"r"(a), "r"(ph), "n"(SPIN_LIMIT) : "memory");
}
__device__ __forceinline__ void spin_check(int it) {
    asm volatile("{\n.reg .pred q;\nsetp.gt.s32 q, %0, %1;\n@q trap;\n}" ::"r"(it), "n"(SPIN_LIMIT));
}
__device__ __forceinline__ void ldsm4(uint32_t* r, uint32_t a) { asm volatile("ldmatrix.sync.aligned.m8n8.x4.shared.b16 {%0,%1,%2,%3}, [%4];" : "=r"(r[0]), "=r"(r[1]), "=r"(r[2]), "=r"(r[3]) : "r"(a) : "memory"); }
__device__ __forceinline__ void ldsm4t(uint32_t* r, uint32_t a) { asm volatile("ldmatrix.sync.aligned.m8n8.x4.trans.shared.b16 {%0,%1,%2,%3}, [%4];" : "=r"(r[0]), "=r"(r[1]), "=r"(r[2]), "=r"(r[3]) : "r"(a) : "memory"); }
__device__ __forceinline__ void ldsm2t(uint32_t* r, uint32_t a) { asm volatile("ldmatrix.sync.aligned.m8n8.x2.trans.shared.b16 {%0,%1}, [%2];" : "=r"(r[0]), "=r"(r[1]) : "r"(a) : "memory"); }
__device__ __forceinline__ void stsm4t(uint32_t a, uint32_t r0, uint32_t r1, uint32_t r2, uint32_t r3) { asm volatile("stmatrix.sync.aligned.m8n8.x4.trans.shared.b16 [%0], {%1,%2,%3,%4};" ::"r"(a), "r"(r0), "r"(r1), "r"(r2), "r"(r3) : "memory"); }
__device__ __forceinline__ void stsm2t(uint32_t a, uint32_t r0, uint32_t r1) { asm volatile("stmatrix.sync.aligned.m8n8.x2.trans.shared.b16 [%0], {%1,%2};" ::"r"(a), "r"(r0), "r"(r1) : "memory"); }
__device__ __forceinline__ void mma16(float* d, const uint32_t* a, uint32_t b0, uint32_t b1) {
    asm("mma.sync.aligned.m16n8k16.row.col.f32.bf16.bf16.f32 {%0,%1,%2,%3}, {%4,%5,%6,%7}, {%8,%9}, {%0,%1,%2,%3};"
        : "+f"(d[0]), "+f"(d[1]), "+f"(d[2]), "+f"(d[3]) : "r"(a[0]), "r"(a[1]), "r"(a[2]), "r"(a[3]), "r"(b0), "r"(b1));
}
__device__ __forceinline__ void mma8(float* d, uint32_t a0, uint32_t a1, uint32_t b0) {
    asm("mma.sync.aligned.m16n8k8.row.col.f32.bf16.bf16.f32 {%0,%1,%2,%3}, {%4,%5}, {%6}, {%0,%1,%2,%3};"
        : "+f"(d[0]), "+f"(d[1]), "+f"(d[2]), "+f"(d[3]) : "r"(a0), "r"(a1), "r"(b0));
}
__device__ __forceinline__ void mma16z(float* d, const uint32_t* a, uint32_t b0, uint32_t b1) {
    asm("mma.sync.aligned.m16n8k16.row.col.f32.bf16.bf16.f32 {%0,%1,%2,%3}, {%4,%5,%6,%7}, {%8,%9}, {%10,%10,%10,%10};"
        : "=f"(d[0]), "=f"(d[1]), "=f"(d[2]), "=f"(d[3]) : "r"(a[0]), "r"(a[1]), "r"(a[2]), "r"(a[3]), "r"(b0), "r"(b1), "f"(0.f));
}
__device__ __forceinline__ uint32_t pack(float lo, float hi) { uint32_t r; asm("cvt.rn.bf16x2.f32 %0, %1, %2;" : "=r"(r) : "f"(hi), "f"(lo)); return r; }
__device__ __forceinline__ uint32_t hmul(uint32_t a, uint32_t b) { uint32_t r; asm("mul.rn.bf16x2 %0, %1, %2;" : "=r"(r) : "r"(a), "r"(b)); return r; }
__device__ __forceinline__ uint32_t hfma(uint32_t a, uint32_t b, uint32_t c) { uint32_t r; asm("fma.rn.bf16x2 %0, %1, %2, %3;" : "=r"(r) : "r"(a), "r"(b), "r"(c)); return r; }
__device__ __forceinline__ uint4 lds128(uint32_t a) { uint4 v; asm volatile("ld.shared.v4.u32 {%0,%1,%2,%3}, [%4];" : "=r"(v.x), "=r"(v.y), "=r"(v.z), "=r"(v.w) : "r"(a) : "memory"); return v; }
__device__ __forceinline__ void sts128(uint32_t a, uint4 v) { asm volatile("st.shared.v4.u32 [%0], {%1,%2,%3,%4};" ::"r"(a), "r"(v.x), "r"(v.y), "r"(v.z), "r"(v.w) : "memory"); }
__device__ __forceinline__ int lds32(uint32_t a) { int v; asm volatile("ld.shared.u32 %0, [%1];" : "=r"(v) : "r"(a) : "memory"); return v; }
__device__ __forceinline__ void sts32(uint32_t a, int v) { asm volatile("st.shared.u32 [%0], %1;" ::"r"(a), "r"(v) : "memory"); }
__device__ __forceinline__ int atoms_add(uint32_t a, int v) { int r; asm volatile("atom.shared.add.u32 %0, [%1], %2;" : "=r"(r) : "r"(a), "r"(v) : "memory"); return r; }
__device__ __forceinline__ uint32_t ld_rlx(const void* p) { uint32_t v; asm volatile("ld.relaxed.gpu.global.u32 %0, [%1];" : "=r"(v) : "l"(p) : "memory"); return v; }
__device__ __forceinline__ void st_rlx(void* p, uint32_t v) { asm volatile("st.relaxed.gpu.global.u32 [%0], %1;" ::"l"(p), "r"(v) : "memory"); }
__device__ __forceinline__ void bulk(uint32_t dst, const void* g, int n, uint32_t bar) {
    asm volatile("cp.async.bulk.shared::cluster.global.mbarrier::complete_tx::bytes [%0], [%1], %2, [%3];" ::"r"(dst), "l"(g), "r"(n), "r"(bar) : "memory");
}
__device__ __forceinline__ void bulk_st(void* g, uint32_t src, int n) {
    asm volatile("cp.async.bulk.global.shared::cta.bulk_group [%0], [%1], %2;\ncp.async.bulk.commit_group;" ::"l"(g), "r"(src), "r"(n) : "memory");
}
__device__ __forceinline__ uint2 lds64(uint32_t a) { uint2 v; asm volatile("ld.shared.v2.u32 {%0,%1}, [%2];" : "=r"(v.x), "=r"(v.y) : "r"(a) : "memory"); return v; }
__device__ __forceinline__ void sts64(uint32_t a, uint32_t x, uint32_t y) { asm volatile("st.shared.v2.u32 [%0], {%1,%2};" ::"r"(a), "r"(x), "r"(y) : "memory"); }
__device__ __forceinline__ void tma3d(uint32_t dst, const CUtensorMap* m, int c1, int c2, uint32_t bar) {
    asm volatile("cp.async.bulk.tensor.3d.shared::cluster.global.mbarrier::complete_tx::bytes [%0], [%1, {0, %3, %4}], [%2];"
                 ::"r"(dst), "l"(m), "r"(bar), "r"(c1), "r"(c2) : "memory");
}
__device__ __forceinline__ void fence_async() { asm volatile("fence.proxy.async.shared::cta;" ::: "memory"); }
__device__ __forceinline__ uint64_t madw(uint32_t a, uint32_t b, uint64_t c) { uint64_t r; asm("mad.wide.u32 %0, %1, %2, %3;" : "=l"(r) : "r"(a), "r"(b), "l"(c)); return r; }
__device__ __forceinline__ uint32_t lop_sel(uint32_t a, uint32_t b, uint32_t m) { uint32_t r; asm("lop3.b32 %0, %1, %2, %3, 0xd8;" : "=r"(r) : "r"(a), "r"(b), "r"(m)); return r; }
__device__ __forceinline__ uint32_t opaque(uint32_t v, int lane) { return __shfl_sync(0xffffffffu, v, lane); }
__device__ __forceinline__ void bar_sync(int id, int n) { asm volatile("bar.sync %0, %1;" ::"r"(id), "r"(n) : "memory"); }

__device__ __forceinline__ void wg_rs16(float* d, const uint32_t* a, uint64_t db, int sc) {
    asm volatile("{.reg .pred p; setp.ne.b32 p, %13, 0;\n"
                 "wgmma.mma_async.sync.aligned.m64n16k16.f32.bf16.bf16 {%0,%1,%2,%3,%4,%5,%6,%7}, {%8,%9,%10,%11}, %12, p, 1, 1, 0;}"
                 : "+f"(d[0]), "+f"(d[1]), "+f"(d[2]), "+f"(d[3]), "+f"(d[4]), "+f"(d[5]), "+f"(d[6]), "+f"(d[7])
                 : "r"(a[0]), "r"(a[1]), "r"(a[2]), "r"(a[3]), "l"(db), "r"(sc));
}
__device__ __forceinline__ void wg_rs48(float* d, const uint32_t* a, uint64_t db, int sc) {
    asm volatile("{.reg .pred p; setp.ne.b32 p, %29, 0;\n"
                 "wgmma.mma_async.sync.aligned.m64n48k16.f32.bf16.bf16 {%0,%1,%2,%3,%4,%5,%6,%7,%8,%9,%10,%11,%12,%13,%14,%15,%16,%17,%18,%19,%20,%21,%22,%23}, {%24,%25,%26,%27}, %28, p, 1, 1, 0;}"
                 : "+f"(d[0]), "+f"(d[1]), "+f"(d[2]), "+f"(d[3]), "+f"(d[4]), "+f"(d[5]), "+f"(d[6]), "+f"(d[7]),
                   "+f"(d[8]), "+f"(d[9]), "+f"(d[10]), "+f"(d[11]), "+f"(d[12]), "+f"(d[13]), "+f"(d[14]), "+f"(d[15]),
                   "+f"(d[16]), "+f"(d[17]), "+f"(d[18]), "+f"(d[19]), "+f"(d[20]), "+f"(d[21]), "+f"(d[22]), "+f"(d[23])
                 : "r"(a[0]), "r"(a[1]), "r"(a[2]), "r"(a[3]), "l"(db), "r"(sc));
}
__device__ __forceinline__ void wg_ss48(float* d, uint64_t da, uint64_t db, int sc) {
    asm volatile("{.reg .pred p; setp.ne.b32 p, %26, 0;\n"
                 "wgmma.mma_async.sync.aligned.m64n48k16.f32.bf16.bf16 {%0,%1,%2,%3,%4,%5,%6,%7,%8,%9,%10,%11,%12,%13,%14,%15,%16,%17,%18,%19,%20,%21,%22,%23}, %24, %25, p, 1, 1, 1, 0;}"
                 : "+f"(d[0]), "+f"(d[1]), "+f"(d[2]), "+f"(d[3]), "+f"(d[4]), "+f"(d[5]), "+f"(d[6]), "+f"(d[7]),
                   "+f"(d[8]), "+f"(d[9]), "+f"(d[10]), "+f"(d[11]), "+f"(d[12]), "+f"(d[13]), "+f"(d[14]), "+f"(d[15]),
                   "+f"(d[16]), "+f"(d[17]), "+f"(d[18]), "+f"(d[19]), "+f"(d[20]), "+f"(d[21]), "+f"(d[22]), "+f"(d[23])
                 : "l"(da), "l"(db), "r"(sc));
}

__device__ __forceinline__ int warp_incl(int v) {
#pragma unroll
    for (int o = 1; o < 32; o <<= 1)
        asm volatile("{.reg .pred p; .reg .b32 u; shfl.sync.up.b32 u|p, %0, %1, 0, 0xffffffff; @p add.s32 %0, %0, u;}" : "+r"(v) : "r"(o));
    return v;
}
__device__ __forceinline__ void ldg128(uint32_t* r, const void* p, bool on) {
    asm volatile("{.reg .pred p; setp.ne.u32 p, %5, 0; @p ld.global.nc.v4.u32 {%0,%1,%2,%3}, [%4];}"
                 : "=r"(r[0]), "=r"(r[1]), "=r"(r[2]), "=r"(r[3]) : "l"(p), "r"((uint32_t)on));
}

template <int V> struct IC { static constexpr int value = V; };
template <int N, int I = 0, class Fn> __device__ __forceinline__ void static_for(Fn f) { if constexpr (I < N) { f(IC<I>{}); static_for<N, I + 1>(f); } }

struct Acc {
    uint32_t p[10];
    float t01[4], m[3][4];
};

#define LF(m) if (H) ldsm2t(f[m], so + xa + m * 256); else ldsm4t(f[m], so + xa + m * 256)
#define LY() ldsm4(yb, so + ya)
#define LC() ldsm4(yb + 4, so + yc)
#define LN() ph = lds32(so + S_N)
#define ADV() { if (F) asm volatile("{.reg .pred p; setp.ne.and.u32 p, %1, 0, lane0; @p mbarrier.arrive.shared::cta.b64 _, [%0];}" ::"r"(so + S_EMPTY), "r"(room) : "memory"); \
                else asm volatile("@lane0 mbarrier.arrive.shared::cta.b64 _, [%0];" ::"r"(so + S_EMPTY) : "memory"); \
                so = so == sm + O_RING + (NSLOT - 1) * SLOT ? sm + O_RING : so + SLOT; }
#define LA() asm volatile("{\n.reg .pred p, q;\n.reg .b64 s;\n.reg .f32 n;\nmov.b64 s, {0, %7};\nmbarrier.test_wait.shared::cta.b64 p, [%6], s;\n" \
                          "abs.f32 n, %7;\nsetp.gt.and.f32 q, n, 0f00000003, p;\nselp.u32 %4, 1, 0, p;\nselp.u32 %5, 1, 0, q;\n" \
                          "@p ldmatrix.sync.aligned.m8n8.x4.shared.b16 {%0,%1,%2,%3}, [%8];\n}" \
                          : "+r"(a[0]), "+r"(a[1]), "+r"(a[2]), "+r"(a[3]), "=r"(ok), "=r"(go) : "r"(so + S_FULL), "r"(ph), "r"(so + aa) : "memory")
#define RAD(p, s) if (!H || !s) { float c[4]; mma16z(c, wr[p], a[2 * s], a[2 * s + 1]); R[p][2 * s] = pack(c[0], c[1]); R[p][2 * s + 1] = pack(c[2], c[3]); }
#define MUL(n, x, y) (XS >> n & 1 ? hmul(y, x) : hmul(x, y))
#define FMA(n, x, y, z) (XS >> n & 1 ? hfma(y, x, z) : hfma(x, y, z))
#define ON(i) if (!H || i < 2)
#define ACC(n, m, i, x, y) ON(i) { constexpr int c = 2 * m + ((i ^ XA) & 1); A.p[c] = F && !(seen >> c & 1) ? MUL(n, x, y) : FMA(n, x, y, A.p[c]); seen |= 1 << c; }
#define P00(i) ACC(0, 3, i, f[0][i], R[0][i])
#define P10(k, i) ACC(1, k, i, f[1 + k][i], R[3][i])
#define S0(k, i) ON(i) sd[i] = MUL(2, f[1 + k][i], yb[2 * k + (i >> 1)])
#define SD(k, i) ON(i) sd[i] = FMA(2, f[1 + k][i], yb[2 * k + (i >> 1)], sd[i])
#define P110(i) ACC(3, 4, i, sd[i], R[1][i])
#define TU(i) ON(i) u[3][i ^ XU] = MUL(4, f[0][i], R[2][i])
#define EM(d, u) if (F) mma16z(d, u, yb[6], yb[7]); else if (H) mma8(d, u[0], u[1], yb[6]); else mma16(d, u, yb[6], yb[7])
#define TM() EM(A.t01, u[3])
#define MU(k, i) ON(i) u[k][i ^ XU] = MUL(5, f[1 + k][i], R[4][i])
#define MM(k) EM(A.m[k], u[k])
#define PK(v, h) pack(v[2 * (h)], v[2 * (h) + 1])
#define LM() { sts32(na + (sof + sm + O_NODE), mt); asm volatile("ld.shared.u16 %0, [%1];" : "=r"(mt) : "r"(na + (so + S_C + 48)) : "memory"); }
#define MP(k) PK(A.m[k], XA ^ XU), PK(A.m[k], 1 ^ XA ^ XU)
#define FY(k) if (k == 0) mma16z(y, A.p, oh[0], oh[1]); else if (k > 1 && !(seen >> 30)) { mma16(y, A.p + 4, oh[2], oh[3]); seen |= 1 << 30; }
#define FZ(k) if (k == 0) { const uint32_t mp[4] = {A.p[8], A.p[9], MP(2)}; mma16z(z, mp, oh[4], eb[2]); } \
              else if (k == 1) { const uint32_t mp[4] = {MP(0), MP(1)}; mma16(z, mp, eb[0], eb[1]); }
#define SX() stsm2t(fx + sof, PK(A.t01, XU), PK(A.t01, 1 ^ XU))
#define SY() stsm4t(fyz + sof, PK(y, XA), PK(y, 1 ^ XA), PK(z, XA), PK(z, 1 ^ XA))
#define G0(k) wg_rs16(d0, w0[k], db + ((((k) & 7) * PW + (((k) >> 3) ? P_0P1 : P_0P0)) >> 4), k)
#define G1(i) { constexpr int k_ = ((i) + KR) % 24; const uint64_t bk = db + (((k_ & 7) * PW + ((k_ >> 3) == 0 ? P_1P0 : (k_ >> 3) == 1 ? P_1P1 : P_1P2)) >> 4); \
                if (k_ < KR) wg_rs48(d1, w1[k_ % KR], bk, i); else wg_ss48(d1, (da + (k_ - KR) * 256) | (64ull << 32) | (1ull << 62), bk, i); }
#define XA 1
#define XU 0
#define XS_R 63
#define SEQ_R LF(2); LN(); RAD(1,0); RAD(1,1); LC(); LY(); RAD(2,0); RAD(2,1); RAD(4,0); RAD(4,1); RAD(3,0); RAD(3,1); LF(0); P10(1,1); P10(1,0); \
    P10(1,3); P10(1,2); LF(3); MU(2,3); S0(2,3); S0(2,2); S0(2,1); S0(2,0); RAD(0,1); RAD(0,0); MU(2,2); P00(2); MU(2,1); MU(1,3); MU(2,0); MM(2); P00(3); \
    MU(1,2); LF(1); ADV(); LA(); P10(0,0); P10(0,1); P10(0,2); P10(0,3); SD(0,0); SD(0,2); SD(0,1); SD(0,3); SD(1,0); P110(0); SD(1,2); P110(2); SD(1,1); \
    P110(1); SD(1,3); P110(3); P00(0); MU(0,0); TU(0); P10(2,0); TU(2); MU(1,1); TU(3); TU(1); TM(); P10(2,2); P00(1); MU(0,2); P10(2,1); MU(1,0); MM(1); \
    P10(2,3); MU(0,1); MU(0,3); MM(0);
#define XS_H XS_R
#define SEQ_H SEQ_R
#define XS_F 63
#define SEQ_F LY(); LF(2); LF(0); SX(); FZ(0); FY(0); FY(2); RAD(1,0); LM(); RAD(0,1); RAD(2,1); RAD(3,0); RAD(3,1); RAD(2,0); LC(); RAD(0,0); \
    RAD(4,0); LN(); FZ(2); LF(1); LF(3); ADV(); FY(1); RAD(4,1); RAD(1,1); LA(); TU(1); TU(0); TU(3); TU(2); P10(0,0); P10(0,2); P10(2,3); P10(0,1); \
    P10(2,2); TM(); P10(0,3); FY(3); P10(2,1); P10(1,0); P10(2,0); P10(1,1); P10(1,2); S0(0,1); SD(2,1); SD(1,1); P110(1); S0(0,0); S0(0,3); S0(0,2); \
    SD(2,0); SD(1,0); P110(0); FZ(1); SY(); P10(1,3); MU(0,1); MU(0,0); MU(0,3); MU(0,2); SD(2,3); SD(1,3); P110(3); MU(2,2); MU(2,3); MU(2,0); MU(2,1); \
    MM(2); P00(2); SD(2,2); SD(1,2); P110(2); MU(1,0); P00(3); MU(1,2); MU(1,3); MU(1,1); MM(1); P00(0); P00(1); MM(0);

__global__ void __launch_bounds__(NT, 1)
tp_kernel(const int4* __restrict__ dst, const int4* __restrict__ src, const char* __restrict__ rhat, Scratch* __restrict__ gs,
          const char* __restrict__ x, const char* __restrict__ ea, const __nv_bfloat16* __restrict__ eps, char* __restrict__ out,
          const __grid_constant__ CUtensorMap m_wr, const __grid_constant__ CUtensorMap m_w0, const __grid_constant__ CUtensorMap m_w1,
          const __grid_constant__ CUtensorMap m_x) {
    extern __shared__ __align__(1024) char smem_raw[];
    constexpr uint32_t sm = 1024;
    spin_check((uint32_t)__cvta_generic_to_shared(smem_raw) == sm ? 0 : 2 * SPIN_LIMIT);
    int t;
    asm volatile("mov.u32 %0, %%tid.x;" : "=r"(t));
    const int w = t >> 5, lane = t & 31, b = blockIdx.x;

    const int g = lane >> 2, q = lane & 3, mat = lane >> 3, r = lane & 7;
    const int e0 = b * CH + t * 8, ne = min(CH, NE - b * CH);
    const bool act = t * 8 < ne;
    uint32_t d[8];
#pragma unroll
    for (int k = 0; k < 2; k++) ldg128(d + 4 * k, dst + e0 / 4 + k, act);
    uint32_t tag = ld_rlx(&gs->epoch[b * 32]), epl;
    asm volatile("ld.global.nc.u16 %0, [%1];" : "=r"(epl) : "l"(eps + min(lane, 26)));
    if (t < 60) sts128(sm + O_BCNT + 16 * t, make_uint4(0, 0, 0, 0));
    if (t == NT - 1) {
#pragma unroll
        for (int i = 0; i < 5; i++) mbar_init(sm + O_WBA + 8 * i, 1);
        fence_async();
        mbar_expect(sm + O_WBC, ne * 10); mbar_expect(sm + O_WBA, 20480); mbar_expect(sm + O_WBB, (24 - KR) * 4096); mbar_expect(sm + O_WBD, 65536 + KR * 4096);
        mbar_expect(sm + O_WBE, (((TP & 15) != 15) + ((TP >> 4 & 15) != 15) + ((TP >> 8 & 15) != 15) + ((TP >> 12) != 15)) * (NLOC / 4 * 128));
        WLD(6);
        spin_check(tag);
        bulk(sm + O_RH, rhat + b * (CH * 6), ne * 6, sm + O_WBC);
        bulk(sm + O_SRC, src + b * (CH / 4), ne * 4, sm + O_WBC);
        tma3d(sm + O_WR0, &m_wr, 0, 0, sm + O_WBA);
        tma3d(sm + O_WR1, &m_wr, 0, 5, sm + O_WBA);
        WLD(0);
    }
    if (t == 320) {
#pragma unroll
        for (int i = 0; i < NSLOT; i++) {
            sts128(sm + O_RING + i * SLOT + S_C + 64, make_uint4(0, 0, 0, 0));
            mbar_init(sm + O_RING + i * SLOT + S_FULL, 32); mbar_init(sm + O_RING + i * SLOT + S_EMPTY, 8);
        }
    }
#pragma unroll
    for (int k = 0; k < LZ; k++) sts128(sm + O_L + 16 * (t + k * NT), make_uint4(0, 0, 0, 0));
    if (t < 80) sts32(sm + O_NCNT + 4 * t, t <= NLOC ? 4 * t : 0);
    if (t < 68) sts32(sm + O_NODE + 4 * t, 0);
    uint32_t ba[8], rk[8];
    if (w < 10) bar_sync(1, 320);
    tag = (tag + 1) << 30;
    if (act) {
#pragma unroll
        for (int i = 0; i < 8; i++) {
            const uint32_t l = __umulhi(d[i], (uint32_t)((1ull << 32) / G + 1));
            ba[i] = d[i] * 4 - l * (4 * G);
            d[i] = l * 4 + (tag + ((e0 + i + 1) << 9) + 4);
            rk[i] = atoms_add(sm + O_BCNT + ba[i], 4);
        }
#pragma unroll
        for (int i = 0; i < 8; i++)
            asm volatile("{.reg .pred p; setp.lt.u32 p, %2, 124; @p st.shared.u32 [%0], %1;}"
                         ::"r"(sm + O_KT + ba[i] * 32 + ((ba[i] + rk[i]) & 127)), "r"(d[i]), "r"(rk[i]) : "memory");
    }
    TS(0);
    __syncthreads();
    {
        int v[5], sum = 0;
#pragma unroll
        for (int i = 0; i < 5; i++) { v[i] = lds32(sm + O_BCNT + 4 * (lane * 5 + i)); sum += v[i]; }
        int e = warp_incl(sum) - sum;
        if (w == 10) {
#pragma unroll
            for (int i = 0; i < 5; i++) {
                const int k = lane * 5 + i;
                if (k < G) sts32(sm + O_KT + k * 128 + ((k * 4 + 124) & 127), tag | v[i] << 10 | e >> 2);
                e += v[i];
            }
            __syncwarp();
            if (lane == 0) {
                fence_async();
                bulk_st(&gs->keys[b * (G * 32)], sm + O_KT, G * 128);
                WLD(5);
            }
        } else {
#pragma unroll
            for (int i = 0; i < 5; i++) { sts32(sm + O_BOFF + 4 * (lane * 5 + i), e); e += v[i]; }
        }
        __syncwarp();
    }
    TS(11);
    const uint32_t sw = (uint32_t)(((2 * (w & 3) + (mat & 1)) ^ r) * 16 + ((mat >> 1) * 8 + r) * 128);
    const uint32_t lo = (lane & 2) * 64 + (lane & 12) * 8 + (lane & 16) + (lane & 1) * 8;
    uint32_t wr[5][4];
    const uint32_t* kp = &gs->keys[(w * SEGW * G + b) * 32 + ((lane + b) & 31)];
    uint32_t kv[SEGW + 1], ho[SEGW + 1], nk[SEGW + 1], old;
    if (act) {
        uint32_t mx = 0;
#pragma unroll
        for (int i = 0; i < 8; i++) { mx = max(mx, rk[i]); ba[i] = rk[i] + lds32(sm + O_BOFF + ba[i]); }
        if (mx >= 124) {
#pragma unroll
            for (int i = 0; i < 8; i++)
                if (rk[i] >= 124) st_rlx(&gs->more[b * CH + (ba[i] >> 2)], d[i]);
        }
    }
    if (w < 8) {
        mbar_wait(sm + O_WBA, 0);
#pragma unroll
        for (int p = 0; p < 5; p++) {
            const int c = 2 * p + (w >> 2);
            ldsm4t(wr[p], sm + (c < 5 ? O_WR0 : O_WR1 - 5 * 2048) + c * 2048 + sw);
        }
    } else {
        const uint64_t xl = (uint64_t)(x - 1024 + r * 16) - (tag >> 6), al = (uint64_t)(ea - 32 + (lane & 1) * 16) - (tag >> 4);
        const uint64_t ml = (uint64_t)gs->list + lo;
        const uint32_t row = ((mat & 2 ? mat & 1 ? 0xa9c876b5u : 0xfe4d2130u : mat & 1 ? 0x76b821a3u : 0xc5bfe0cbu) >> 4 * r & 15) + (mat & 2) * 8;
        const uint32_t c[13] = {(uint32_t)xl, (uint32_t)(xl >> 32), (uint32_t)al, (uint32_t)(al >> 32), (uint32_t)ml, (uint32_t)(ml >> 32),
            mat * 2048u + (r ^ 2 * mat) * 16, mat * 2048u + 1024 + (r ^ 2 * mat ^ 1) * 16,
            S_A + (lane & 2) * 128u + g * 32 + ((lane ^ lane >> 4) & 1) * 16, S_C + row * 16, lane & 1 ? 16u : 9u, lane & 30u,
            lane == 4 ? 0xffff0000u : 0u};
#pragma unroll
        for (int i = 0; i < 20; i++) wr[i >> 2][i & 3] = i < 13 ? opaque(c[i % 13], lane) : 0;
    }
    TS(21);
    mbar_wait(sm + O_WBC, 0);
    TS(22);
    if (act) {
        uint32_t s[8], y[12];
#pragma unroll
        for (int k = 0; k < 3; k++) *(uint4*)&y[4 * k] = lds128(sm + O_RH + t * 48 + k * 16);
#pragma unroll
        for (int k = 0; k < 2; k++) *(uint4*)&s[4 * k] = lds128(sm + O_SRC + t * 32 + k * 16);
#pragma unroll
        for (int i = 0; i < 8; i++) {
            const int k = 3 * i / 2;
            sts64(sm + O_OUT + ba[i] * 2, __byte_perm(y[k], s[i] + (tag >> 16) + 1, i & 1 ? 0x5432 : 0x5410),
                  i & 1 ? y[k + 1] : __byte_perm(y[k], y[k + 1], 0x5432));
        }
    }
    TS(12);
    __syncthreads();
    if (t == 352) { fence_async(); bulk_st(&gs->vals[b * CH], sm + O_OUT, ne * 8); WLD(7); }

    const uint32_t am = lane < 31 ? 511 : 0, none = tag | (320 + 4 * lane);
    auto check = [&]() {
        old = 0;
#pragma unroll
        for (int j = 0; j < SEGW; j++) {
            ho[j] = __shfl_sync(0xffffffffu, kv[j], 31);
            kv[j] = ho[j] >= (lane < 31 ? tag + ((lane + 1) << 12) : 0u) ? kv[j] : none;
            old |= kv[j] ^ tag;
        }
        return __any_sync(0xffffffffu, old >> 30);
    };
#pragma unroll
    for (int j = 0; j < SEGW; j++) kv[j] = ld_rlx(kp + j * (G * 32));
    TS(1);
    if (t == 352) WLD(1);
    TV(19, 0); TV(23, 0);
    for (int it = 0; check(); it++) {
        spin_check(it);
        if (it == 0) TS(20);
        TV(19, (it + 1) * 100);
#pragma unroll
        for (int j = 0; j < SEGW; j++)
            if (__any_sync(0xffffffffu, (kv[j] ^ tag) >> 30)) kv[j] = ld_rlx(kp + j * (G * 32));
    }
    TS(3);
    if (t == 352) WLD(2);
    kv[SEGW] = none; ho[SEGW] = 0;
    bool slow = false;
    const bool more = __any_sync(0xffffffffu, lane == 31 && (old & 0xfe0000));
    if (more) {
        int c = lane;
#pragma unroll
        for (int j = 0; j < SEGW; j++) {
            const int n = max((int)(ho[j] >> 12 & 0xfff) - 31, 0);
            if ((unsigned)c < (unsigned)n) ho[SEGW] = j * CH + (ho[j] & 0xfff) + 31 + c - lane;
            c -= n;
        }
        slow = lane == 31 && c < 0;
        if (c < 0 && lane < 31)
            for (int it = 0; ((kv[SEGW] = ld_rlx(&gs->more[w * SEGW * CH + lane + ho[SEGW]])) ^ tag) >> 30; it++) spin_check(it);
        __syncwarp();
    }
    uint32_t na_[SEGW + 1];
    uint64_t vp = (uint64_t)&gs->vals[w * SEGW * CH + lane], vv[SEGW + 1];
#pragma unroll
    for (int j = 0; j <= SEGW; j++) vv[j] = tag;
    auto ldv = [&](bool again) {
#pragma unroll
        for (int j = 0; j <= SEGW; j++)
            asm volatile("{.reg .pred p; setp.lt.u32 p, %2, 320; @p ld.relaxed.gpu.global.b64 %0, [%1];}" : "+l"(vv[j])
                         : "l"(madw(j < SEGW ? ho[j] & 0xfff : ho[j], 8, vp) + (j < SEGW ? j * CH * 8 : 0)),
                           "r"(again ? (((uint32_t)vv[j] ^ tag) >> 30 ? 0 : 320) : na_[j]) : "memory");
    };
#pragma unroll
    for (int j = 0; j <= SEGW; j++) na_[j] = (kv[j] & am) | (none & 511 & ~am);
#pragma unroll
    for (int j = 0; j <= SEGW; j++) nk[j] = atoms_add(sm + O_NCNT + na_[j], 512);
    auto visit = [&](auto f) {
#pragma unroll 1
        for (int j = 0; j < SEGW; j++) {
            const uint32_t* kl = &gs->keys[((w * SEGW + j) * G + b) * 32];
            const uint32_t h = ld_rlx(kl + ((31 + b) & 31));
#pragma unroll 1
            for (int i = lane; i < (h >> 12 & 0xfff); i += 32) {
                const int o = (w * SEGW + j) * CH + (h & 0xfff) + i;
                uint32_t k;
                int it = 0;
                do { k = ld_rlx(i < 31 ? kl + ((i + b) & 31) : &gs->more[o]); spin_check(it++); } while ((k ^ tag) >> 30);
                f(k, o, i);
            }
        }
    };
    slow = __syncthreads_or(slow);
    if (slow) {
        if (t < 80) sts32(sm + O_NCNT + 4 * t, t <= NLOC ? 4 * t : 0);
        __syncthreads();
        visit([&](uint32_t k, int, int) { atoms_add(sm + O_NCNT + (k & 511), 512); });
        __syncthreads();
    }
    TS(4);
    if (t == 352) WLD(3);
    if (w < 10) {
        const uint32_t key = lds32(sm + O_NCNT + 4 + (t & ~3));
        uint4 k[5];
#pragma unroll
        for (int i = 0; i < 5; i++) k[i] = lds128(sm + O_NCNT + q * 80 + i * 16);
        uint32_t c[4] = {0, 0, 0, 0};
#pragma unroll
        for (int i = 0; i < 5; i++) { c[0] += (key - k[i].x) >> 31; c[1] += (key - k[i].y) >> 31; c[2] += (key - k[i].z) >> 31; c[3] += (key - k[i].w) >> 31; }
        int rank = c[0] + c[1] + c[2] + c[3];
        rank += __shfl_xor_sync(0xffffffffu, rank, 1);
        rank += __shfl_xor_sync(0xffffffffu, rank, 2);
        if ((b & 1) && rank < 2 * NPRIV) rank = (2 * NPRIV - 1 - rank) ^ 1;
        if (t < NLOC * 4) sts32(sm + O_SORT + 4 * rank, key);
    }
    __syncthreads();
    TS(2);
    const bool on = lane < NLOC / 4;
    const uint4 k4 = lds128(sm + O_SORT + 16 * (on ? lane : 0));
    const uint32_t ks[4] = {k4.x, k4.y, k4.z, k4.w};
    const int n0 = on ? max(1u, (ks[0] + 3584) >> 12) : 0, n1 = on ? max(1u, (ks[2] + 3584) >> 12) : 0;
    const int u2 = warp_incl(n0 + n1), u1 = u2 - n1, u0 = u1 - n0;
    const int total = __shfl_sync(0xffffffffu, u2, 31);
    slow |= total > CAPT;
    const int m0 = slow ? n0 : max(2u, (ks[0] + 1536) >> 11), m1 = slow ? n1 : max(2u, (ks[2] + 1536) >> 11);
    int gbase = b * CAPT + 1;
    if (on) {
#pragma unroll
        for (int i = 0; i < 4; i++) {
            const int a = ks[i] & 511, node = a * (G / 4) - G + b, o = (i >> 1 ? u1 : u0) * 256 + (i & 1) * 16;
            const uint32_t mk = (node < NN ? node + 1 : 0) + ((i >> 1 ? m1 : m0) << 16);
            sts64(sm + O_NOFF + 2 * a, o - (a >> 4), mk + a * 32);
            if (!slow && ks[i] < 512) sts32(sm + O_L + 4 + o, mk);
        }
    }
    __syncwarp();
    if (t == 352) WLD(8);
    if (!slow) {
        uint32_t mk[SEGW + 1];
        TS(13);
        if (t == 352) { asm volatile("cp.async.bulk.wait_group.read 0;" ::: "memory"); }
        ldv(false);
        if (t == 352) WLD(4);
        TS(16);
#pragma unroll
        for (int j = 0; j <= SEGW; j++) {
            const uint2 o = lds64(sm + O_NOFF + 2 * na_[j]);
            mk[j] = o.y - nk[j] * 32; nk[j] = o.x + (nk[j] >> 4);
        }
        for (int it = 0;; it++) {
            old = 0;
#pragma unroll
            for (int j = 0; j <= SEGW; j++) old |= (uint32_t)vv[j] ^ tag;
            if (!__any_sync(0xffffffffu, old >> 30)) break;
            spin_check(it);
            vp = __shfl_sync(0xffffffffu, vp, lane);
            ldv(true);
            TV(23, (it + 1) * 100);
        }
        TS(17);
#pragma unroll
        for (int j = 0; j <= SEGW; j++)
            asm volatile("{.reg .pred p; setp.ne.u32 p, %3, %5; @p st.shared.v4.u32 [%0], {%1,%2,%3,%4};}"
                         ::"r"(sm + O_L + nk[j]), "r"(kv[j]), "r"(mk[j]), "r"((uint32_t)vv[j]), "r"((uint32_t)(vv[j] >> 32)), "r"(tag) : "memory");
        TS(18);
        if (na_[SEGW] < 320) gs->more[w * SEGW * CH + lane + ho[SEGW]] = 0;
    } else {
        int so = 0;
        if (t == 352) WLD(4);
#pragma unroll
        for (int j = 0; j < SEGW; j++) so += ho[j] & 0xfff;
        if (lane == 0) atoms_add(sm + O_SUM, so);
        if (t == 352) asm volatile("cp.async.bulk.wait_group.read 0;" ::: "memory");
        __syncthreads();
        gbase = TBIG + (lds32(sm + O_SUM) >> 3) + (NLOC + 5) * b;
        auto put = [&](uint32_t k, uint64_t e, uint32_t a, int rank) {
            const uint2 o = lds64(sm + O_NOFF + 2 * a);
            const uint32_t m = o.y - a * 32 - (rank << 13);
            gs->list[gbase * 16 + ((o.x + (a >> 4)) >> 4) + rank * 2] = make_uint4(k, (m & 0xffff) | min(m >> 16, 0x7fffu) << 17, e, e >> 32);
        };
        visit([&](uint32_t k, int o, int i) {
            uint64_t e;
            int it = 0;
            do {
                asm volatile("ld.relaxed.gpu.global.b64 %0, [%1];" : "=l"(e) : "l"(&gs->vals[o]) : "memory");
                spin_check(it++);
            } while (((uint32_t)e ^ tag) >> 30);
            if (i >= 31) gs->more[o] = 0;
            put(k, e, k & 511, atoms_add(sm + O_NCUR + (k & 511), 1));
        });
#pragma unroll 1
        for (int i = 0; i < 4; i++) {
            const uint32_t k = i == 0 ? ks[0] : i == 1 ? ks[1] : i == 2 ? ks[2] : ks[3];
#pragma unroll 1
            for (int p = (k >> 9) + w; p < (i >> 1 ? n1 : n0) * 8; p += NT / 32) put(0, 0, k & 511, p);
        }
        __threadfence();
    }
    if (t == 352) WLD(9);
    const uint32_t iw0 = (gbase + u0) << 12 | n0, iw1 = (gbase + u1) << 12 | n1;
    __syncthreads();
    TS(5);

    if (w >= 8) {
        asm volatile("setmaxnreg.dec.sync.aligned.u32 56;");
        const int h = __reduce_max_sync(0xffffffffu, w & 3);
        if (h == 0) TSW(28);
        gbase = __reduce_min_sync(0xffffffffu, iw0) >> 12;
        int pos = gbase + h, end = __reduce_max_sync(0xffffffffu, lane == NPRIV / 2 ? (NPRIV & 1 ? iw1 : iw0) : 0) >> 12;
        const int bytes = gbase < TBIG ? ((__reduce_max_sync(0xffffffffu, iw0) >> 12) - gbase) * 256 : 0;
        const uint32_t ring = sm + O_RING;
        const uint64_t xl = wr[0][0] | (uint64_t)wr[0][1] << 32, al = wr[0][2] | (uint64_t)wr[0][3] << 32, ml = wr[1][0] | (uint64_t)wr[1][1] << 32;
        const uint32_t xoff[2] = {wr[1][2], wr[1][3]}, aoff = wr[2][0], coff = wr[2][1], sh = wr[2][2], ial = wr[2][3], sel = wr[3][0];
        auto lde = [&](uint2& e, int p) {
            asm volatile("{.reg .pred p; setp.gt.s32 p, %3, 0; @p ld.relaxed.gpu.global.v2.u32 {%0,%1}, [%2];}" : "+r"(e.x), "+r"(e.y) : "l"(madw(p, 256, ml)), "r"(p) : "memory");
        };
        uint2 e0[3] = {};
#pragma unroll
        for (int k = 0; k < 3; k++) {
            e0[k] = lds64(sm + O_L + k * 1024 + h * 256 + ((uint32_t)ml & 255));
            lde(e0[k], bytes ? 0 : pos + 4 * k);
        }
        if (h == 3) fence_async();
        else asm volatile("bar.arrive 4, %0;" ::"n"(NT) : "memory");
        pos += 4;

        int ev = 0, state = -2, tk = 0, nr = 0;
        uint32_t inf = 0;
        int ii = 0;
        auto take = [&]() {
            int v = 0;
            asm volatile("{.reg .pred p; setp.eq.s32 p, %2, 0; @p atom.relaxed.gpu.global.add.u32 %0, [%1], 1;}" : "+r"(v) : "l"(&gs->ticket), "r"(lane) : "memory");
            return v;
        };
        auto resolve = [&]() {
            const int k = __reduce_max_sync(0xffffffffu, tk);
            inf = tag;
            if (k < G * NPOOL) { const int l = k / G; ii = (k - l * G) * NPOOL + l; inf = ld_rlx(&gs->info[ii]);
                const int j = NPRIV + 1 + nr + (b & 7), gd = __reduce_max_sync(0xffffffffu, lds32(sm + O_SUM + 4));
                tk = (b & 7) && (j & ~7) > gd && k >= G * NPOOL - (j & 7 ? G : 5 * G / 3) ? G * NPOOL : take(); }
        };
        uint32_t so = ring + h * SLOT, ph = 0x80000000u;
        uint32_t spins = 0;
        asm volatile(".reg .pred z<5>;");
        { const uint32_t c0 = clock(); while (__any_sync(0xffffffffu, (uint32_t)clock() - c0 < h * 300)); }
        while (true) {
            const uint2 e = e0[0];
            const uint32_t o = e.x >> sh, id = __shfl_sync(0xffffffffu, o, ial);
            uint32_t s[4];
#pragma unroll
            for (int j = 0; j < 4; j++) s[j] = __shfl_sync(0xffffffffu, o, 2 * j + 1, 8);
            const uint32_t nx = so == ring + (NSLOT - 1) * SLOT ? ph : ph ^ 0x80000000u, ey = lop_sel(e.y, nx, sel);
            const uint32_t y0 = __shfl_xor_sync(0xffffffffu, e.x, 1), ym = lane & 1 ? e.y : y0;
            const bool full = __ballot_sync(0xffffffffu, e.y >> 16 != 1) & 1;
            const uint64_t ga = madw(id, 32, al);
            uint64_t gx[4];
#pragma unroll
            for (int j = 0; j < 4; j++) gx[j] = madw(s[j], 1024, xl);
            const uint32_t da = so + aoff, dx[2] = {so + xoff[0], so + xoff[1]}, dc = so + coff;
            asm volatile("setp.eq.u32 z0, %0, 0;\nsetp.eq.u32 z1, %1, 0;\nsetp.eq.u32 z2, %2, 0;\nsetp.eq.u32 z3, %3, 0;\nsetp.eq.u32 z4, %4, 0;\n"
                         ::"r"(s[0]), "r"(s[1]), "r"(s[2]), "r"(s[3]), "r"(id), "l"(ga), "r"(da), "r"(dx[0]), "r"(dx[1]), "r"(dc));
            lde(e0[0], state < 0 ? 0 : pos);
            if (h == 0 && state == -2) TSW(29);
            if (h == 0 && state == -1) TSW(30);
            asm volatile("{\n.reg .pred p;\n.reg .b64 s;\nmov.b64 s, {0, %2};\n"
                         "LOOP:\nmbarrier.try_wait.shared::cta.b64 p, [%1], s;\n@p bra DONE;\n"
                         "add.u32 %0, %0, 1;\nsetp.gt.u32 p, %0, %3;\n@p trap;\nbra LOOP;\nDONE:\n}"
                         : "+r"(spins) : "r"(so + S_EMPTY), "r"(ph), "n"(SPIN_LIMIT) : "memory");
            asm volatile("cp.async.cg.shared.global [%0], [%1], 16, z4;" ::"r"(da), "l"(ga) : "memory");
#define ROW(j) _Pragma("unroll") for (int k = 0; k < 8; k++) \
                asm volatile("cp.async.cg.shared.global [%0], [%1], 16, z" #j ";" ::"r"(dx[j >> 1] + (j & 1) * 8192 + k * 128), "l"(gx[j] + k * 128) : "memory")
            ROW(0); ROW(2);
            if (full) { ROW(1); ROW(3); }
            stsm4t(dc, e.x, ey, lane < 16 ? ym : 0, lane < 16 ? 0 : ym);
            asm volatile("cp.async.mbarrier.arrive.noinc.shared::cta.b64 [%0];" ::"r"(so + S_FULL) : "memory");
            const bool wrap = so >= ring + (NSLOT - 4) * SLOT;
            ph ^= wrap ? 0x80000000u : 0u;
            so = wrap ? so - (NSLOT - 4) * SLOT : so + 4 * SLOT;
            pos += 4;
            if (pos >= ev) {
                if (state < 0) {
                    e0[0] = e0[1]; e0[1] = e0[2];
                    if (state == -2) {
                        if (h == 0) TSW(24);
                        if (h == 3) TSW(25);
                        if (h == 0) asm volatile("bar.arrive 5, 288;" ::: "memory");
                        if (h < 3) bar_sync(7, 352);
                        if (h == 3) bar_sync(4, NT);
                        if (h == 0) mbar_wait(sm + O_WBE, 0);
                        if (h == 3) {
                            if (lane == 0) {
                                if (bytes) bulk_st(gs->list + gbase * 16, sm + O_L, bytes);
                                asm volatile("cp.async.bulk.wait_group.read 0;" ::: "memory");
                            }
                            __syncwarp();
                            if (lane == 0) {
                                for (int j = KR; j < 24; j++) tma3d(sm + O_W1 + (j - KR) * 4096, &m_w1, 16 * j, 0, sm + O_WBB);
                            }
                            __syncwarp();
                        }
                        state = -1;
                    } else {
                        if (h == 3) {
                            if (lane == 0) asm volatile("cp.async.bulk.wait_group 0;\nfence.proxy.async;" ::: "memory");
                            __syncwarp();
                            const int i = opaque(2 * lane - NPRIV, lane);
                            if ((unsigned)i < NPOOL) st_rlx(&gs->info[b * NPOOL + i], tag | iw0);
                            if ((unsigned)(i + 1) < NPOOL) st_rlx(&gs->info[b * NPOOL + i + 1], tag | iw1);
                        }
                        bar_sync(6, 128);
                        ev = h ? end : end - 12; state = h ? 2 : 0;
                    }
                } else if (state == 0) { ev = end - 6; state = 1; tk = take(); }
                else if (state == 1) { resolve(); ev = end; state = 2; }
                else {
                    if (state == 3) break;
                    do {
                        const uint32_t mb = sm + O_MB + (nr & 15) * 8;
                        uint32_t rg;
                        nr++;
                        if (h == 0) {
                            for (int it = 0; (rg = __reduce_max_sync(0xffffffffu, inf ^ tag)) >> 30; it++) { spin_check(it); inf = ld_rlx(&gs->info[ii]); }
                            asm volatile("st.release.cta.shared.b64 [%0], %1;" ::"r"(mb), "l"(rg | (uint64_t)nr << 32) : "memory");
                            if (rg) resolve();
                        } else {
                            uint64_t m;
                            for (int it = 0;; it++) {
                                asm volatile("ld.acquire.cta.shared.b64 %0, [%1];" : "=l"(m) : "r"(mb) : "memory");
                                if (__all_sync(0xffffffffu, (int)(m >> 32) == nr)) break;
                                spin_check(it);
                            }
                            rg = __reduce_max_sync(0xffffffffu, (uint32_t)m);
                        }
                        pos = rg ? (int)(rg >> 12) + pos - end : 0;
                        end = rg ? (rg >> 12) + (rg & 0xfff) : 1;
                        state = rg ? 2 : 3;
                    } while (pos >= end);
                    ev = end;
                }
            }
        }
        mbar_wait31(so + S_EMPTY, ph);
        TSW(8 + (h & 1));
        if (lane == 0) sts32(so + S_N, 0);
        mbar_arrive(so + S_FULL);
        if (t == 256) {
            gs->epoch[b * 32] = (tag >> 30) % 3;
            if (atomicInc(&gs->done, G - 1) == G - 1) gs->ticket = 0;
        }
        asm volatile("cp.async.wait_all;" ::: "memory");
    } else {
        asm volatile("setmaxnreg.inc.sync.aligned.u32 224;");
        bar_sync(5, 288);
        const uint32_t xa = opaque(((mat >> 1) * 8 + r) * 1024 + (w >> 2) * 128 + (((2 * (w & 3) + (mat & 1)) ^ r) * 16), lane);
        const uint32_t aa = opaque(S_A + ((mat >> 1) * 8 + r) * 32 + (((mat & 1) ^ (r >> 2)) * 16), lane);
        const uint32_t ya = opaque(S_C + (mat & 1) * 80 + (mat >> 1) * 16, lane);
        const uint32_t yc = opaque(S_C + (mat < 2 ? mat * 80 + 32 : q < 3 ? mat * 128 + ((r >> 2) ^ (mat & 1)) * 80 + q * 16 : 64), lane);
        const uint32_t na = opaque((mat & 1) * 8, lane);
        const uint32_t pw = sm + O_P + w * PW;
        const uint32_t fx = opaque(pw + (q < 3 ? P_1P0 + 2 * q * PSBO : P_1P1 + PSBO) + (mat & 1) * 128 + (r >> 2) * PSBO, lane);
        const uint32_t fyz = opaque(pw + (q < 3 ? (mat < 2 ? P_1P1 : P_1P2) + 2 * q * PSBO : mat < 2 ? P_0P0 : P_0P1) + (mat & 1) * 128 + (r >> 2) * PSBO, lane);
        uint32_t oh[5];
#pragma unroll
        for (int c = 0; c < 5; c++) oh[c] = opaque(g == (q >> 1) * 4 + min(c, 3) ? 0x3F803F80u : 0u, lane ^ c >> 2);
        uint32_t eb[3];
#pragma unroll
        for (int k = 0; k < 3; k++) {
            const int i = (g & 3) * 9 + (q & 1) * 6 + k;
            const uint32_t lo = __shfl_sync(0xffffffffu, epl, i), hi = __shfl_sync(0xffffffffu, epl, i + 3);
            eb[k] = (g & 3) < 3 && (q >> 1) == (g >> 2) ? (q & 1 ? lo : lo | hi << 16) : 0u;
        }
        asm volatile(".reg .pred lane0;\nsetp.eq.u32 lane0, %0, 0;" ::"r"(lane));
        uint32_t w0[16][4], w1[KR][4];
        mbar_wait(sm + O_WBD, 0);
#pragma unroll
        for (int k = 0; k < 16; k++) ldsm4t(w0[k], sm + w0s(k >> 2) + (w >> 2) * 8192 + (k & 3) * 2048 + sw);
#pragma unroll
        for (int k = 0; k < KR; k++) ldsm4t(w1[k], sm + w1s(k) + (w >> 2) * 2048 + sw);
        asm volatile("bar.arrive 4, %0;" ::"n"(NT) : "memory");
        bar_sync(7, 352);
        TS(6);
        Acc A;
#pragma unroll
        for (int i = 0; i < 4; i++) { A.p[i] = A.p[4 + i] = A.p[8 + i / 2] = 0; A.t01[i] = A.m[0][i] = A.m[1][i] = A.m[2][i] = 0.f; }
        uint32_t room = 144 - (b & 7) * 16;
        uint32_t so = sm + O_RING, ph, a[4], ok, go, mt = 0;
        mbar_wait(so + S_FULL, 0);
        ldsm4(a, so + aa);
        TS(7);
        while (true) {
            {
                constexpr int F = 1, H = 0, XS = XS_F;
                int seen = 0;
                uint32_t yb[8], f[4][4], R[5][4], u[4][4], sd[4];
                float y[4], z[4];
                const uint32_t sof = room & 112;
                room -= 16;
                SEQ_F
            }
            if (!(go && room)) {
                const uint32_t pu = __reduce_max_sync(0xffffffffu, ph);
                if (!room || !pu) {
                    const uint32_t wg = __reduce_max_sync(0xffffffffu, w >> 2);
                    mbar_wait(sm + O_WBB, 0);
                    asm volatile("{.reg .pred p; setp.ne.u32 p, %0, 0;\n@p bar.arrive 1, 256;\n@p bar.sync 2, 256;\n@!p bar.sync 1, 256;}" ::"r"(wg) : "memory");
                    asm volatile("fence.proxy.async::generic.acquire.sync_restrict::shared::cluster.cluster;" ::: "memory");
                    float d0[8], d1[24];
                    const uint64_t db = (uint64_t)((sm + O_P) >> 4) | (8ull << 16) | ((uint64_t)(PSBO / 16) << 32);
                    const uint32_t da = ((sm + O_W1) >> 4 | 1 << 16) + wg * 128;
                    asm volatile("wgmma.fence.sync.aligned;" ::: "memory");
                    const uint32_t sp = so == sm + O_RING ? sm + O_RING + (NSLOT - 1) * SLOT : so - SLOT, sr = (r & 6) + (mat & 1);
                    const uint32_t nd = (sr * 16 - 16 & 112) >= room ? lds32(sm + O_NODE + sr * 16 + (mat >> 1) * 8) : 0;
                    const uint64_t oa = madw(nd, 1024, (uint64_t)(out - 1024 + w * 32 + (r & 1) * 16));
                    const uint32_t sl = sp + ((mat >> 1) * 8 + sr) * 1024 + (w >> 2) * 128 + (((2 * (w & 3) + (r & 1)) ^ sr) * 16);
                    auto put = [&](int j) {
                        const uint4 v = lds128(sl + j * 256);
                        asm volatile("{.reg .pred p; setp.ne.u32 p, %5, 0; @p st.global.v4.u32 [%0], {%1,%2,%3,%4};}"
                                     ::"l"(oa + j * 256), "r"(v.x), "r"(v.y), "r"(v.z), "r"(v.w), "r"(nd) : "memory");
                    };
                    static_for<24>([&](auto kc) {
                        constexpr int k = kc.value;
                        if (k == 16) asm volatile("wgmma.commit_group.sync.aligned;" ::: "memory");
                        if (k == 20) asm volatile("{.reg .pred p; setp.eq.u32 p, %0, 0;\n@p bar.arrive 2, 256;}" ::"r"(wg) : "memory");
                        G1(k);
                        if (k < 16) G0(k % 16);
                    });
                    asm volatile("wgmma.commit_group.sync.aligned;" ::: "memory");
                    asm volatile("wgmma.wait_group.sync.aligned 1;" ::: "memory");
#pragma unroll
                    for (int i = 0; i < 8; i++) asm volatile("" : "+f"(d0[i])::"memory");
                    stsm4t(sp + xa, pack(d0[0], d0[1]), pack(d0[2], d0[3]), pack(d0[4], d0[5]), pack(d0[6], d0[7]));
                    __syncwarp();
                    put(0);
                    float gt[8];
                    uint32_t chk = -1;
#pragma unroll
                    for (int i = 0; i < 8; i++) {
                        asm volatile("ex2.approx.ftz.f32 %0, %1;" : "=f"(gt[i]) : "f"(d0[i] * -1.4426950408889634f) : "memory");
                        asm volatile("rcp.approx.ftz.f32 %0, %1;" : "=f"(gt[i]) : "f"(gt[i] + 1.f) : "memory");
                    }
#pragma unroll
                    for (int i = 0; i < 8; i++) chk &= __float_as_uint(gt[i]);
                    sts32(sm + O_TRASH, chk);
                    asm volatile("wgmma.wait_group.sync.aligned 0;" ::: "memory");
#pragma unroll
                    for (int i = 0; i < 24; i++) asm volatile("" : "+f"(d1[i])::"memory");
                    asm volatile("{.reg .pred p; setp.ne.u32 p, %0, 0;\n@p bar.sync 3, 256;}" ::"r"(wg) : "memory");
#pragma unroll
                    for (int j = 0; j < 3; j++) {
                        uint32_t o[4];
#pragma unroll
                        for (int i = 0; i < 4; i++) o[i] = pack(d1[8 * j + 2 * i] * gt[2 * i], d1[8 * j + 2 * i + 1] * gt[2 * i + 1]);
                        stsm4t(sp + xa + 256 + j * 256, o[0], o[1], o[2], o[3]);
                    }
                    __syncwarp();
#pragma unroll
                    for (int j = 1; j < 4; j++) put(j);
                    __syncwarp();
                    asm volatile("@lane0 mbarrier.arrive.shared::cta.b64 _, [%0];" ::"r"(sp + S_EMPTY) : "memory");
                    asm volatile("@lane0 red.shared.add.u32 [%0], 1;" ::"r"(sm + O_SUM + 4) : "memory");
                    asm volatile("{.reg .pred p; setp.eq.u32 p, %0, 0;\n@p bar.sync 3, 256;}" ::"r"(wg) : "memory");
                    room = 128;
                    if (!pu) break;
                }
                if (!ok) { mbar_wait31(so + S_FULL, pu); ldsm4(a, so + aa); }
                if (!(pu & 0xfffc)) { if (pu & 1) goto half; continue; }
            }
            while (true) {
                do {
                    constexpr int F = 0, H = 0, XS = XS_R;
                    int seen = 0;
                    uint32_t yb[8], f[4][4], R[5][4], u[4][4], sd[4];
                    SEQ_R
                } while (go);
                if (ok) {
                    asm volatile("{.reg .pred p; .reg .f32 n; abs.f32 n, %1; setp.gt.f32 p, n, 0f00000002; selp.u32 %0, 1, 0, p;}" : "=r"(go) : "r"(ph));
                    break;
                }
                const uint32_t pu = __reduce_max_sync(0xffffffffu, ph);
                mbar_wait31(so + S_FULL, pu); ldsm4(a, so + aa);
                if (!(pu & 0xfffc)) { go = pu & 1; break; }
            }
            if (!go) continue;
        half: {
                constexpr int F = 0, H = 1, XS = XS_H;
                int seen = 0;
                uint32_t yb[8], f[4][4], R[5][4], u[4][4], sd[4];
                SEQ_H
                if (!ok) { mbar_wait31(so + S_FULL, __reduce_max_sync(0xffffffffu, ph)); ldsm4(a, so + aa); }
            }
        }
        TS(10);
    }
}

typedef CUresult (*EncFn)(CUtensorMap*, CUtensorMapDataType, cuuint32_t, void*, const cuuint64_t*, const cuuint64_t*,
                          const cuuint32_t*, const cuuint32_t*, CUtensorMapInterleave, CUtensorMapSwizzle,
                          CUtensorMapL2promotion, CUtensorMapFloatOOBfill);

void make_map(EncFn fn, CUtensorMap* m, void* p, int rows, int cols, int brows, int bcols, int bblk) {
    cuuint64_t dims[3] = {64, (cuuint64_t)rows, (cuuint64_t)cols / 64}, strides[2] = {(cuuint64_t)cols * 2, 128};
    cuuint32_t box[3] = {(cuuint32_t)bcols, (cuuint32_t)brows, (cuuint32_t)bblk}, es[3] = {1, 1, 1};
    fn(m, CU_TENSOR_MAP_DATA_TYPE_BFLOAT16, 3, p, dims, strides, box, es, CU_TENSOR_MAP_INTERLEAVE_NONE,
       bcols == 64 ? CU_TENSOR_MAP_SWIZZLE_128B : CU_TENSOR_MAP_SWIZZLE_NONE, CU_TENSOR_MAP_L2_PROMOTION_L2_128B, CU_TENSOR_MAP_FLOAT_OOB_FILL_NONE);
}

}

extern "C" void kernel_launch(void* const* d_in, const int* in_sizes, int n_in, void* d_out, int out_size) {
    static EncFn enc = nullptr;
    static void* scratch = nullptr;
    if (!enc) {
        void* fn = nullptr;
        cudaDriverEntryPointQueryResult qr;
        cudaGetDriverEntryPoint("cuTensorMapEncodeTiled", &fn, cudaEnableDefault, &qr);
        enc = (EncFn)fn;
        cudaGetSymbolAddress(&scratch, g_scratch);
        cudaFuncSetAttribute(tp_kernel, cudaFuncAttributeMaxDynamicSharedMemorySize, SMEM_BYTES);
    }
    CUtensorMap m_wr, m_w0, m_w1, m_x;
    make_map(enc, &m_wr, d_in[5], 16, 640, 16, 64, 5);
    make_map(enc, &m_w0, d_in[6], 256, 128, 64, 64, 2);
    make_map(enc, &m_w1, d_in[7], 384, 128, 16, 64, 2);
    make_map(enc, &m_x, d_in[0], NN * 8, 64, NLOC * 2, 8, 1);
    tp_kernel<<<G, NT, SMEM_BYTES>>>((const int4*)d_in[4], (const int4*)d_in[3], (const char*)d_in[1], (Scratch*)scratch,
                                     (const char*)d_in[0], (const char*)d_in[2], (const __nv_bfloat16*)d_in[8], (char*)d_out,
                                     m_wr, m_w0, m_w1, m_x);
}
```

```cpp
#include <cuda_runtime.h>
#include <cuda_bf16.h>
#include <cuda.h>
#include <stdint.h>
#include <stddef.h>

namespace {

constexpr int NN = 10000;
constexpr int NE = 320000;
constexpr int G = 132;
constexpr int NT = 384;
constexpr int CH = 2432;
constexpr int NLOC = (NN + G - 1) / G;
constexpr int NPOOL = 3;
constexpr int NPAIR = NLOC / 2, NPRIV = NPAIR - NPOOL;
constexpr int SEGW = 11;

constexpr int NSLOT = 7;
constexpr int KR = 9;
constexpr uint32_t WP = 0x5357575, TP = 0x9375;
#define WLD(p) { _Pragma("unroll") for (int j = 0; j < 4 + KR; j++) if ((WP >> 4 * (j < 4 ? j : j < 8 ? 4 : j < 11 ? 5 : 6) & 15) == p) \
    tma3d(sm + (j < 4 ? w0s(j) : w1s(j - 4)), j < 4 ? &m_w0 : &m_w1, j < 4 ? j * 64 : (j - 4) * 16, 0, sm + O_WBD); \
    _Pragma("unroll") for (int j = 0; j < 4; j++) { const int r0 = (b * 4 + j) * (NLOC / 4); \
        if ((TP >> 4 * j & 15) == p) tma3d(sm + O_WR1 + 12288, &m_x, r0 * 8, 0, sm + O_WBE); } }

constexpr int S_A = 16384, S_C = S_A + 512, S_FULL = S_C + 144, S_EMPTY = S_FULL + 8, S_N = S_C + 160, SLOT = S_C + 512;

constexpr int PSBO = 272;
constexpr int PB1 = 5 * PSBO + 256, PB0 = PSBO + 256;
constexpr int P_1P0 = 0, P_1P1 = PB1, P_0P1 = 2 * PB1, P_0P0 = P_0P1 + PB0, P_1P2 = P_0P0 + PB0;
constexpr int PW = P_1P2 + PB1;

constexpr int O_W1 = 0;
constexpr int O_P = 62336;
constexpr int O_RING = O_P + 8 * PW;
constexpr int O_WBA = O_RING + NSLOT * SLOT, O_WBB = O_WBA + 8, O_WBC = O_WBA + 16, O_WBD = O_WBA + 24, O_WBE = O_WBA + 32, O_TRASH = O_WBA + 40, O_NODE = O_WBA + 48;
constexpr int O_SUM = O_NODE + 128, O_MB = O_SUM + 16;
constexpr int SMEM_BYTES = O_MB + 128;
constexpr int CAPT = 192;
constexpr int O_L = 0, LZ = CAPT * 256 / (NT * 16), O_W0S = O_L + CAPT * 256, O_OUT = O_RING + S_C - CH * 8, O_SRC = O_RING + 6 * SLOT;
constexpr int O_KT = O_RING + SLOT, O_RH = O_RING + 2 * SLOT;
constexpr int O_WR0 = O_RING + 3 * SLOT, O_WR1 = O_RING + 4 * SLOT;
__host__ __device__ constexpr int w0s(int j) { return j < 3 ? O_W0S + j * 16384 : O_SRC; }
__host__ __device__ constexpr int w1s(int k) { return k < 4 ? O_RING + 5 * SLOT + k * 4096 : k < 7 ? O_WR1 + (k - 4) * 4096 : O_W0S + 49152 + (k - 7) * 4096; }
constexpr int O_BCNT = O_WR0 + 10240, O_NCUR = O_BCNT + 640, O_NCNT = O_NCUR + 320;
constexpr int O_BOFF = O_NCNT + 512, O_SORT = O_BOFF + 640, O_NOFF = O_SORT + 320;
constexpr int TBIG = G * CAPT + 8, NTILE = TBIG + NE / 8 + G * (NLOC + 5);
static_assert(SMEM_BYTES <= 232448 && CAPT % 16 == 0 && NTILE < (1 << 18), "smem");
static_assert(LZ * NT * 16 == CAPT * 256 && O_W0S % 1024 == 0 && w1s(KR) <= O_OUT && O_OUT % 128 == 0 && CH * 6 <= S_C && G * 128 <= S_C, "staging");
static_assert(O_NOFF + 1024 <= O_RING + 3 * SLOT + S_C && 12288 + NLOC * 32 <= S_C && (24 - KR) * 4096 <= O_P && KR <= 9, "staging");
static_assert(O_RING % 1024 == 0 && SLOT % 1024 == 0 && O_W0S <= O_P && O_NOFF % 8 == 0, "layout");
static_assert(G * CH >= NE && NE % 8 == 0 && CH < 4096 && CH / 8 <= 320 && NE < (1 << 21), "chunks");
static_assert(SEGW * (NT / 32) == G && G <= 160 && G % 4 == 0, "segments");
static_assert(NLOC % 4 == 0 && NLOC < 80 && NLOC * 4 <= 320 && NN < 0x3fff && NE / 8 < 0xbfff && NPRIV >= 30, "scan width");

struct __align__(256) Scratch {
    uint32_t keys[G * G * 32];
    uint64_t vals[G * CH];
    uint32_t more[G * CH];
    uint32_t epoch[G * 32];
    uint32_t info[(G * NPOOL + 127) / 128 * 128];
    unsigned done, pad0[31], ticket, pad1[31];
    uint4 list[NTILE * 16];
};
static_assert(offsetof(Scratch, list) % 256 == 0, "list");
__device__ Scratch g_scratch;
#define TS(i)
#define TSW(i)
#define TV(i, v)

constexpr int SPIN_LIMIT = 1 << 24;

__device__ __forceinline__ void mbar_init(uint32_t a, int c) { asm volatile("mbarrier.init.shared::cta.b64 [%0], %1;" ::"r"(a), "r"(c) : "memory"); }
__device__ __forceinline__ void mbar_expect(uint32_t a, int b) { asm volatile("mbarrier.arrive.expect_tx.shared::cta.b64 _, [%0], %1;" ::"r"(a), "r"(b) : "memory"); }
__device__ __forceinline__ void mbar_arrive(uint32_t a) { asm volatile("mbarrier.arrive.shared::cta.b64 _, [%0];" ::"r"(a) : "memory"); }
__device__ __forceinline__ void mbar_wait(uint32_t a, uint32_t ph) {
    asm volatile("{\n.reg .pred p, q;\n.reg .u32 it;\n"
                 "mbarrier.try_wait.parity.shared::cta.b64 p, [%0], %1;\n"
                 "@p bra DONE;\n"
                 "mov.u32 it, 0;\n"
                 "LOOP:\n"
                 "mbarrier.try_wait.parity.shared::cta.b64 p, [%0], %1;\n"
                 "@p bra DONE;\n"
                 "add.u32 it, it, 1;\n"
                 "setp.gt.u32 q, it, %2;\n"
                 "@q trap;\n"
                 "bra LOOP;\n"
                 "DONE:\n}" ::"r"(a), "r"(ph), "n"(SPIN_LIMIT) : "memory");
}
__device__ __forceinline__ void mbar_wait31(uint32_t a, uint32_t ph) {
    asm volatile("{\n.reg .pred p, q;\n.reg .u32 it;\n.reg .b64 s;\n"
                 "mov.b64 s, {0, %1};\n"
                 "mbarrier.try_wait.shared::cta.b64 p, [%0], s;\n"
                 "@p bra DONE;\n"
                 "mov.u32 it, 0;\n"
                 "LOOP:\n"
                 "mbarrier.try_wait.shared::cta.b64 p, [%0], s;\n"
                 "@p bra DONE;\n"
                 "add.u32 it, it, 1;\n"
                 "setp.gt.u32 q, it, %2;\n"
                 "@q trap;\n"
                 "bra LOOP;\n"
                 "DONE:\n}" ::"r"(a), "r"(ph), "n"(SPIN_LIMIT) : "memory");
}
__device__ __forceinline__ void spin_check(int it) {
    asm volatile("{\n.reg .pred q;\nsetp.gt.s32 q, %0, %1;\n@q trap;\n}" ::"r"(it), "n"(SPIN_LIMIT));
}
__device__ __forceinline__ void ldsm4(uint32_t* r, uint32_t a) { asm volatile("ldmatrix.sync.aligned.m8n8.x4.shared.b16 {%0,%1,%2,%3}, [%4];" : "=r"(r[0]), "=r"(r[1]), "=r"(r[2]), "=r"(r[3]) : "r"(a) : "memory"); }
__device__ __forceinline__ void ldsm4t(uint32_t* r, uint32_t a) { asm volatile("ldmatrix.sync.aligned.m8n8.x4.trans.shared.b16 {%0,%1,%2,%3}, [%4];" : "=r"(r[0]), "=r"(r[1]), "=r"(r[2]), "=r"(r[3]) : "r"(a) : "memory"); }
__device__ __forceinline__ void ldsm2t(uint32_t* r, uint32_t a) { asm volatile("ldmatrix.sync.aligned.m8n8.x2.trans.shared.b16 {%0,%1}, [%2];" : "=r"(r[0]), "=r"(r[1]) : "r"(a) : "memory"); }
__device__ __forceinline__ void stsm4t(uint32_t a, uint32_t r0, uint32_t r1, uint32_t r2, uint32_t r3) { asm volatile("stmatrix.sync.aligned.m8n8.x4.trans.shared.b16 [%0], {%1,%2,%3,%4};" ::"r"(a), "r"(r0), "r"(r1), "r"(r2), "r"(r3) : "memory"); }
__device__ __forceinline__ void stsm2t(uint32_t a, uint32_t r0, uint32_t r1) { asm volatile("stmatrix.sync.aligned.m8n8.x2.trans.shared.b16 [%0], {%1,%2};" ::"r"(a), "r"(r0), "r"(r1) : "memory"); }
__device__ __forceinline__ void mma16(float* d, const uint32_t* a, uint32_t b0, uint32_t b1) {
    asm("mma.sync.aligned.m16n8k16.row.col.f32.bf16.bf16.f32 {%0,%1,%2,%3}, {%4,%5,%6,%7}, {%8,%9}, {%0,%1,%2,%3};"
        : "+f"(d[0]), "+f"(d[1]), "+f"(d[2]), "+f"(d[3]) : "r"(a[0]), "r"(a[1]), "r"(a[2]), "r"(a[3]), "r"(b0), "r"(b1));
}
__device__ __forceinline__ void mma8(float* d, uint32_t a0, uint32_t a1, uint32_t b0) {
    asm("mma.sync.aligned.m16n8k8.row.col.f32.bf16.bf16.f32 {%0,%1,%2,%3}, {%4,%5}, {%6}, {%0,%1,%2,%3};"
        : "+f"(d[0]), "+f"(d[1]), "+f"(d[2]), "+f"(d[3]) : "r"(a0), "r"(a1), "r"(b0));
}
__device__ __forceinline__ void mma16z(float* d, const uint32_t* a, uint32_t b0, uint32_t b1) {
    asm("mma.sync.aligned.m16n8k16.row.col.f32.bf16.bf16.f32 {%0,%1,%2,%3}, {%4,%5,%6,%7}, {%8,%9}, {%10,%10,%10,%10};"
        : "=f"(d[0]), "=f"(d[1]), "=f"(d[2]), "=f"(d[3]) : "r"(a[0]), "r"(a[1]), "r"(a[2]), "r"(a[3]), "r"(b0), "r"(b1), "f"(0.f));
}
__device__ __forceinline__ uint32_t pack(float lo, float hi) { uint32_t r; asm("cvt.rn.bf16x2.f32 %0, %1, %2;" : "=r"(r) : "f"(hi), "f"(lo)); return r; }
__device__ __forceinline__ uint32_t hmul(uint32_t a, uint32_t b) { uint32_t r; asm("mul.rn.bf16x2 %0, %1, %2;" : "=r"(r) : "r"(a), "r"(b)); return r; }
__device__ __forceinline__ uint32_t hfma(uint32_t a, uint32_t b, uint32_t c) { uint32_t r; asm("fma.rn.bf16x2 %0, %1, %2, %3;" : "=r"(r) : "r"(a), "r"(b), "r"(c)); return r; }
__device__ __forceinline__ uint4 lds128(uint32_t a) { uint4 v; asm volatile("ld.shared.v4.u32 {%0,%1,%2,%3}, [%4];" : "=r"(v.x), "=r"(v.y), "=r"(v.z), "=r"(v.w) : "r"(a) : "memory"); return v; }
__device__ __forceinline__ void sts128(uint32_t a, uint4 v) { asm volatile("st.shared.v4.u32 [%0], {%1,%2,%3,%4};" ::"r"(a), "r"(v.x), "r"(v.y), "r"(v.z), "r"(v.w) : "memory"); }
__device__ __forceinline__ int lds32(uint32_t a) { int v; asm volatile("ld.shared.u32 %0, [%1];" : "=r"(v) : "r"(a) : "memory"); return v; }
__device__ __forceinline__ void sts32(uint32_t a, int v) { asm volatile("st.shared.u32 [%0], %1;" ::"r"(a), "r"(v) : "memory"); }
__device__ __forceinline__ int atoms_add(uint32_t a, int v) { int r; asm volatile("atom.shared.add.u32 %0, [%1], %2;" : "=r"(r) : "r"(a), "r"(v) : "memory"); return r; }
__device__ __forceinline__ uint32_t ld_rlx(const void* p) { uint32_t v; asm volatile("ld.relaxed.gpu.global.u32 %0, [%1];" : "=r"(v) : "l"(p) : "memory"); return v; }
__device__ __forceinline__ void st_rlx(void* p, uint32_t v) { asm volatile("st.relaxed.gpu.global.u32 [%0], %1;" ::"l"(p), "r"(v) : "memory"); }
__device__ __forceinline__ void bulk(uint32_t dst, const void* g, int n, uint32_t bar) {
    asm volatile("cp.async.bulk.shared::cluster.global.mbarrier::complete_tx::bytes [%0], [%1], %2, [%3];" ::"r"(dst), "l"(g), "r"(n), "r"(bar) : "memory");
}
__device__ __forceinline__ void bulk_st(void* g, uint32_t src, int n) {
    asm volatile("cp.async.bulk.global.shared::cta.bulk_group [%0], [%1], %2;\ncp.async.bulk.commit_group;" ::"l"(g), "r"(src), "r"(n) : "memory");
}
__device__ __forceinline__ uint2 lds64(uint32_t a) { uint2 v; asm volatile("ld.shared.v2.u32 {%0,%1}, [%2];" : "=r"(v.x), "=r"(v.y) : "r"(a) : "memory"); return v; }
__device__ __forceinline__ void sts64(uint32_t a, uint32_t x, uint32_t y) { asm volatile("st.shared.v2.u32 [%0], {%1,%2};" ::"r"(a), "r"(x), "r"(y) : "memory"); }
__device__ __forceinline__ void tma3d(uint32_t dst, const CUtensorMap* m, int c1, int c2, uint32_t bar) {
    asm volatile("cp.async.bulk.tensor.3d.shared::cluster.global.mbarrier::complete_tx::bytes [%0], [%1, {0, %3, %4}], [%2];"
                 ::"r"(dst), "l"(m), "r"(bar), "r"(c1), "r"(c2) : "memory");
}
__device__ __forceinline__ void fence_async() { asm volatile("fence.proxy.async.shared::cta;" ::: "memory"); }
__device__ __forceinline__ uint64_t madw(uint32_t a, uint32_t b, uint64_t c) { uint64_t r; asm("mad.wide.u32 %0, %1, %2, %3;" : "=l"(r) : "r"(a), "r"(b), "l"(c)); return r; }
__device__ __forceinline__ uint32_t lop_sel(uint32_t a, uint32_t b, uint32_t m) { uint32_t r; asm("lop3.b32 %0, %1, %2, %3, 0xd8;" : "=r"(r) : "r"(a), "r"(b), "r"(m)); return r; }
__device__ __forceinline__ uint32_t opaque(uint32_t v, int lane) { return __shfl_sync(0xffffffffu, v, lane); }
__device__ __forceinline__ void bar_sync(int id, int n) { asm volatile("bar.sync %0, %1;" ::"r"(id), "r"(n) : "memory"); }

__device__ __forceinline__ void wg_rs16(float* d, const uint32_t* a, uint64_t db, int sc) {
    asm volatile("{.reg .pred p; setp.ne.b32 p, %13, 0;\n"
                 "wgmma.mma_async.sync.aligned.m64n16k16.f32.bf16.bf16 {%0,%1,%2,%3,%4,%5,%6,%7}, {%8,%9,%10,%11}, %12, p, 1, 1, 0;}"
                 : "+f"(d[0]), "+f"(d[1]), "+f"(d[2]), "+f"(d[3]), "+f"(d[4]), "+f"(d[5]), "+f"(d[6]), "+f"(d[7])
                 : "r"(a[0]), "r"(a[1]), "r"(a[2]), "r"(a[3]), "l"(db), "r"(sc));
}
__device__ __forceinline__ void wg_rs48(float* d, const uint32_t* a, uint64_t db, int sc) {
    asm volatile("{.reg .pred p; setp.ne.b32 p, %29, 0;\n"
                 "wgmma.mma_async.sync.aligned.m64n48k16.f32.bf16.bf16 {%0,%1,%2,%3,%4,%5,%6,%7,%8,%9,%10,%11,%12,%13,%14,%15,%16,%17,%18,%19,%20,%21,%22,%23}, {%24,%25,%26,%27}, %28, p, 1, 1, 0;}"
                 : "+f"(d[0]), "+f"(d[1]), "+f"(d[2]), "+f"(d[3]), "+f"(d[4]), "+f"(d[5]), "+f"(d[6]), "+f"(d[7]),
                   "+f"(d[8]), "+f"(d[9]), "+f"(d[10]), "+f"(d[11]), "+f"(d[12]), "+f"(d[13]), "+f"(d[14]), "+f"(d[15]),
                   "+f"(d[16]), "+f"(d[17]), "+f"(d[18]), "+f"(d[19]), "+f"(d[20]), "+f"(d[21]), "+f"(d[22]), "+f"(d[23])
                 : "r"(a[0]), "r"(a[1]), "r"(a[2]), "r"(a[3]), "l"(db), "r"(sc));
}
__device__ __forceinline__ void wg_ss48(float* d, uint64_t da, uint64_t db, int sc) {
    asm volatile("{.reg .pred p; setp.ne.b32 p, %26, 0;\n"
                 "wgmma.mma_async.sync.aligned.m64n48k16.f32.bf16.bf16 {%0,%1,%2,%3,%4,%5,%6,%7,%8,%9,%10,%11,%12,%13,%14,%15,%16,%17,%18,%19,%20,%21,%22,%23}, %24, %25, p, 1, 1, 1, 0;}"
                 : "+f"(d[0]), "+f"(d[1]), "+f"(d[2]), "+f"(d[3]), "+f"(d[4]), "+f"(d[5]), "+f"(d[6]), "+f"(d[7]),
                   "+f"(d[8]), "+f"(d[9]), "+f"(d[10]), "+f"(d[11]), "+f"(d[12]), "+f"(d[13]), "+f"(d[14]), "+f"(d[15]),
                   "+f"(d[16]), "+f"(d[17]), "+f"(d[18]), "+f"(d[19]), "+f"(d[20]), "+f"(d[21]), "+f"(d[22]), "+f"(d[23])
                 : "l"(da), "l"(db), "r"(sc));
}

__device__ __forceinline__ int warp_incl(int v) {
#pragma unroll
    for (int o = 1; o < 32; o <<= 1)
        asm volatile("{.reg .pred p; .reg .b32 u; shfl.sync.up.b32 u|p, %0, %1, 0, 0xffffffff; @p add.s32 %0, %0, u;}" : "+r"(v) : "r"(o));
    return v;
}
__device__ __forceinline__ void ldg128(uint32_t* r, const void* p, bool on) {
    asm volatile("{.reg .pred p; setp.ne.u32 p, %5, 0; @p ld.global.nc.v4.u32 {%0,%1,%2,%3}, [%4];}"
                 : "=r"(r[0]), "=r"(r[1]), "=r"(r[2]), "=r"(r[3]) : "l"(p), "r"((uint32_t)on));
}

template <int V> struct IC { static constexpr int value = V; };
template <int N, int I = 0, class Fn> __device__ __forceinline__ void static_for(Fn f) { if constexpr (I < N) { f(IC<I>{}); static_for<N, I + 1>(f); } }

struct Acc {
    uint32_t p[10];
    float t01[4], m[3][4];
};

#define LF(m) if (H) ldsm2t(f[m], so + xa + m * 256); else ldsm4t(f[m], so + xa + m * 256)
#define LY() ldsm4(yb, so + ya)
#define LC() ldsm4(yb + 4, so + yc)
#define LN() ph = lds32(so + S_N)
#define ADV() { if (F) asm volatile("{.reg .pred p; setp.ne.and.u32 p, %1, 0, lane0; @p mbarrier.arrive.shared::cta.b64 _, [%0];}" ::"r"(so + S_EMPTY), "r"(room) : "memory"); \
                else asm volatile("@lane0 mbarrier.arrive.shared::cta.b64 _, [%0];" ::"r"(so + S_EMPTY) : "memory"); \
                so = so == sm + O_RING + (NSLOT - 1) * SLOT ? sm + O_RING : so + SLOT; }
#define LA() asm volatile("{\n.reg .pred p, q;\n.reg .b64 s;\n.reg .f32 n;\nmov.b64 s, {0, %7};\nmbarrier.test_wait.shared::cta.b64 p, [%6], s;\n" \
                          "abs.f32 n, %7;\nsetp.gt.and.f32 q, n, 0f00000003, p;\nselp.u32 %4, 1, 0, p;\nselp.u32 %5, 1, 0, q;\n" \
                          "@p ldmatrix.sync.aligned.m8n8.x4.shared.b16 {%0,%1,%2,%3}, [%8];\n}" \
                          : "+r"(a[0]), "+r"(a[1]), "+r"(a[2]), "+r"(a[3]), "=r"(ok), "=r"(go) : "r"(so + S_FULL), "r"(ph), "r"(so + aa) : "memory")
#define RAD(p, s) if (!H || !s) { float c[4]; mma16z(c, wr[p], a[2 * s], a[2 * s + 1]); R[p][2 * s] = pack(c[0], c[1]); R[p][2 * s + 1] = pack(c[2], c[3]); }
#define MUL(n, x, y) (XS >> n & 1 ? hmul(y, x) : hmul(x, y))
#define FMA(n, x, y, z) (XS >> n & 1 ? hfma(y, x, z) : hfma(x, y, z))
#define ON(i) if (!H || i < 2)
#define ACC(n, m, i, x, y) ON(i) { constexpr int c = 2 * m + ((i ^ XA) & 1); A.p[c] = F && !(seen >> c & 1) ? MUL(n, x, y) : FMA(n, x, y, A.p[c]); seen |= 1 << c; }
#define P00(i) ACC(0, 3, i, f[0][i], R[0][i])
#define P10(k, i) ACC(1, k, i, f[1 + k][i], R[3][i])
#define S0(k, i) ON(i) sd[i] = MUL(2, f[1 + k][i], yb[2 * k + (i >> 1)])
#define SD(k, i) ON(i) sd[i] = FMA(2, f[1 + k][i], yb[2 * k + (i >> 1)], sd[i])
#define P110(i) ACC(3, 4, i, sd[i], R[1][i])
#define TU(i) ON(i) u[3][i ^ XU] = MUL(4, f[0][i], R[2][i])
#define EM(d, u) if (F) mma16z(d, u, yb[6], yb[7]); else if (H) mma8(d, u[0], u[1], yb[6]); else mma16(d, u, yb[6], yb[7])
#define TM() EM(A.t01, u[3])
#define MU(k, i) ON(i) u[k][i ^ XU] = MUL(5, f[1 + k][i], R[4][i])
#define MM(k) EM(A.m[k], u[k])
#define PK(v, h) pack(v[2 * (h)], v[2 * (h) + 1])
#define LM() { sts32(na + (sof + sm + O_NODE), mt); asm volatile("ld.shared.u16 %0, [%1];" : "=r"(mt) : "r"(na + (so + S_C + 48)) : "memory"); }
#define MP(k) PK(A.m[k], XA ^ XU), PK(A.m[k], 1 ^ XA ^ XU)
#define FY(k) if (k == 0) mma16z(y, A.p, oh[0], oh[1]); else if (k > 1 && !(seen >> 30)) { mma16(y, A.p + 4, oh[2], oh[3]); seen |= 1 << 30; }
#define FZ(k) if (k == 0) { const uint32_t mp[4] = {A.p[8], A.p[9], MP(2)}; mma16z(z, mp, oh[4], eb[2]); } \
              else if (k == 1) { const uint32_t mp[4] = {MP(0), MP(1)}; mma16(z, mp, eb[0], eb[1]); }
#define SX() stsm2t(fx + sof, PK(A.t01, XU), PK(A.t01, 1 ^ XU))
#define SY() stsm4t(fyz + sof, PK(y, XA), PK(y, 1 ^ XA), PK(z, XA), PK(z, 1 ^ XA))
#define G0(k) wg_rs16(d0, w0[k], db + ((((k) & 7) * PW + (((k) >> 3) ? P_0P1 : P_0P0)) >> 4), k)
#define G1(i) { constexpr int k_ = ((i) + KR) % 24; const uint64_t bk = db + (((k_ & 7) * PW + ((k_ >> 3) == 0 ? P_1P0 : (k_ >> 3) == 1 ? P_1P1 : P_1P2)) >> 4); \
                if (k_ < KR) wg_rs48(d1, w1[k_ % KR], bk, i); else wg_ss48(d1, (da + (k_ - KR) * 256) | (64ull << 32) | (1ull << 62), bk, i); }
#define XA 1
#define XU 0
#define XS_R 63
#define SEQ_R LF(2); LN(); RAD(1,0); RAD(1,1); LC(); LY(); RAD(2,0); RAD(2,1); RAD(4,0); RAD(4,1); RAD(3,0); RAD(3,1); LF(0); P10(1,1); P10(1,0); \
    P10(1,3); P10(1,2); LF(3); MU(2,3); S0(2,3); S0(2,2); S0(2,1); S0(2,0); RAD(0,1); RAD(0,0); MU(2,2); P00(2); MU(2,1); MU(1,3); MU(2,0); MM(2); P00(3); \
    MU(1,2); LF(1); ADV(); LA(); P10(0,0); P10(0,1); P10(0,2); P10(0,3); SD(0,0); SD(0,2); SD(0,1); SD(0,3); SD(1,0); P110(0); SD(1,2); P110(2); SD(1,1); \
    P110(1); SD(1,3); P110(3); P00(0); MU(0,0); TU(0); P10(2,0); TU(2); MU(1,1); TU(3); TU(1); TM(); P10(2,2); P00(1); MU(0,2); P10(2,1); MU(1,0); MM(1); \
    P10(2,3); MU(0,1); MU(0,3); MM(0);
#define XS_H XS_R
#define SEQ_H SEQ_R
#define XS_F 63
#define SEQ_F LY(); LF(2); LF(0); SX(); FZ(0); FY(0); FY(2); RAD(1,0); LM(); RAD(0,1); RAD(2,1); RAD(3,0); RAD(3,1); RAD(2,0); LC(); RAD(0,0); \
    RAD(4,0); LN(); FZ(2); LF(1); LF(3); ADV(); FY(1); RAD(4,1); RAD(1,1); LA(); TU(1); TU(0); TU(3); TU(2); P10(0,0); P10(0,2); P10(2,3); P10(0,1); \
    P10(2,2); TM(); P10(0,3); FY(3); P10(2,1); P10(1,0); P10(2,0); P10(1,1); P10(1,2); S0(0,1); SD(2,1); SD(1,1); P110(1); S0(0,0); S0(0,3); S0(0,2); \
    SD(2,0); SD(1,0); P110(0); FZ(1); SY(); P10(1,3); MU(0,1); MU(0,0); MU(0,3); MU(0,2); SD(2,3); SD(1,3); P110(3); MU(2,2); MU(2,3); MU(2,0); MU(2,1); \
    MM(2); P00(2); SD(2,2); SD(1,2); P110(2); MU(1,0); P00(3); MU(1,2); MU(1,3); MU(1,1); MM(1); P00(0); P00(1); MM(0);

__global__ void __launch_bounds__(NT, 1)
tp_kernel(const int4* __restrict__ dst, const int4* __restrict__ src, const char* __restrict__ rhat, Scratch* __restrict__ gs,
          const char* __restrict__ x, const char* __restrict__ ea, const __nv_bfloat16* __restrict__ eps, char* __restrict__ out,
          const __grid_constant__ CUtensorMap m_wr, const __grid_constant__ CUtensorMap m_w0, const __grid_constant__ CUtensorMap m_w1,
          const __grid_constant__ CUtensorMap m_x) {
    extern __shared__ __align__(1024) char smem_raw[];
    constexpr uint32_t sm = 1024;
    spin_check((uint32_t)__cvta_generic_to_shared(smem_raw) == sm ? 0 : 2 * SPIN_LIMIT);
    int t;
    asm volatile("mov.u32 %0, %%tid.x;" : "=r"(t));
    const int w = t >> 5, lane = t & 31, b = blockIdx.x;

    const int g = lane >> 2, q = lane & 3, mat = lane >> 3, r = lane & 7;
    const int e0 = b * CH + t * 8, ne = min(CH, NE - b * CH);
    const bool act = t * 8 < ne;
    uint32_t d[8];
#pragma unroll
    for (int k = 0; k < 2; k++) ldg128(d + 4 * k, dst + e0 / 4 + k, act);
    uint32_t tag = ld_rlx(&gs->epoch[b * 32]), epl;
    asm volatile("ld.global.nc.u16 %0, [%1];" : "=r"(epl) : "l"(eps + min(lane, 26)));
    if (t < 60) sts128(sm + O_BCNT + 16 * t, make_uint4(0, 0, 0, 0));
    if (t == NT - 1) {
#pragma unroll
        for (int i = 0; i < 5; i++) mbar_init(sm + O_WBA + 8 * i, 1);
        fence_async();
        mbar_expect(sm + O_WBC, ne * 10); mbar_expect(sm + O_WBA, 20480); mbar_expect(sm + O_WBB, (24 - KR) * 4096); mbar_expect(sm + O_WBD, 65536 + KR * 4096);
        mbar_expect(sm + O_WBE, (((TP & 15) != 15) + ((TP >> 4 & 15) != 15) + ((TP >> 8 & 15) != 15) + ((TP >> 12) != 15)) * (NLOC / 4 * 128));
        WLD(6);
        spin_check(tag);
        bulk(sm + O_RH, rhat + b * (CH * 6), ne * 6, sm + O_WBC);
        bulk(sm + O_SRC, src + b * (CH / 4), ne * 4, sm + O_WBC);
        tma3d(sm + O_WR0, &m_wr, 0, 0, sm + O_WBA);
        tma3d(sm + O_WR1, &m_wr, 0, 5, sm + O_WBA);
        WLD(0);
    }
    if (t == 320) {
#pragma unroll
        for (int i = 0; i < NSLOT; i++) {
            sts128(sm + O_RING + i * SLOT + S_C + 64, make_uint4(0, 0, 0, 0));
            mbar_init(sm + O_RING + i * SLOT + S_FULL, 32); mbar_init(sm + O_RING + i * SLOT + S_EMPTY, 8);
        }
    }
#pragma unroll
    for (int k = 0; k < LZ; k++) sts128(sm + O_L + 16 * (t + k * NT), make_uint4(0, 0, 0, 0));
    if (t < 80) sts32(sm + O_NCNT + 4 * t, t <= NLOC ? 4 * t : 0);
    if (t < 68) sts32(sm + O_NODE + 4 * t, 0);
    uint32_t ba[8], rk[8];
    if (w < 10) bar_sync(1, 320);
    tag = (tag + 1) << 30;
    if (act) {
#pragma unroll
        for (int i = 0; i < 8; i++) {
            const uint32_t l = __umulhi(d[i], (uint32_t)((1ull << 32) / G + 1));
            ba[i] = d[i] * 4 - l * (4 * G);
            d[i] = l * 4 + (tag + ((e0 + i + 1) << 9) + 4);
            rk[i] = atoms_add(sm + O_BCNT + ba[i], 4);
        }
#pragma unroll
        for (int i = 0; i < 8; i++)
            asm volatile("{.reg .pred p; setp.lt.u32 p, %2, 124; @p st.shared.u32 [%0], %1;}"
                         ::"r"(sm + O_KT + ba[i] * 32 + ((ba[i] + rk[i]) & 127)), "r"(d[i]), "r"(rk[i]) : "memory");
    }
    TS(0);
    __syncthreads();
    {
        int v[5], sum = 0;
#pragma unroll
        for (int i = 0; i < 5; i++) { v[i] = lds32(sm + O_BCNT + 4 * (lane * 5 + i)); sum += v[i]; }
        int e = warp_incl(sum) - sum;
        if (w == 10) {
#pragma unroll
            for (int i = 0; i < 5; i++) {
                const int k = lane * 5 + i;
                if (k < G) sts32(sm + O_KT + k * 128 + ((k * 4 + 124) & 127), tag | v[i] << 10 | e >> 2);
                e += v[i];
            }
            __syncwarp();
            if (lane == 0) {
                fence_async();
                bulk_st(&gs->keys[b * (G * 32)], sm + O_KT, G * 128);
                WLD(5);
            }
        } else {
#pragma unroll
            for (int i = 0; i < 5; i++) { sts32(sm + O_BOFF + 4 * (lane * 5 + i), e); e += v[i]; }
        }
        __syncwarp();
    }
    TS(11);
    const uint32_t sw = (uint32_t)(((2 * (w & 3) + (mat & 1)) ^ r) * 16 + ((mat >> 1) * 8 + r) * 128);
    const uint32_t lo = (lane & 2) * 64 + (lane & 12) * 8 + (lane & 16) + (lane & 1) * 8;
    uint32_t wr[5][4];
    const uint32_t* kp = &gs->keys[(w * SEGW * G + b) * 32 + ((lane + b) & 31)];
    uint32_t kv[SEGW + 1], ho[SEGW + 1], nk[SEGW + 1], old;
    if (act) {
        uint32_t mx = 0;
#pragma unroll
        for (int i = 0; i < 8; i++) { mx = max(mx, rk[i]); ba[i] = rk[i] + lds32(sm + O_BOFF + ba[i]); }
        if (mx >= 124) {
#pragma unroll
            for (int i = 0; i < 8; i++)
                if (rk[i] >= 124) st_rlx(&gs->more[b * CH + (ba[i] >> 2)], d[i]);
        }
    }
    if (w < 8) {
        mbar_wait(sm + O_WBA, 0);
#pragma unroll
        for (int p = 0; p < 5; p++) {
            const int c = 2 * p + (w >> 2);
            ldsm4t(wr[p], sm + (c < 5 ? O_WR0 : O_WR1 - 5 * 2048) + c * 2048 + sw);
        }
    } else {
        const uint64_t xl = (uint64_t)(x - 1024 + (r ^ 2 * mat) * 16) - (tag >> 6), al = (uint64_t)(ea - 32 + (lane & 1) * 16) - (tag >> 4);
        const uint64_t ml = (uint64_t)gs->list + lo;
        const uint32_t row = ((mat & 2 ? mat & 1 ? 0xa9c876b5u : 0xfe4d2130u : mat & 1 ? 0xfed8c1a3u : 0x76c521b0u) >> 4 * r & 15) + (mat & 2) * 8;
        const uint32_t c[16] = {(uint32_t)xl, (uint32_t)(xl >> 32), (uint32_t)al, (uint32_t)(al >> 32), (uint32_t)ml, (uint32_t)(ml >> 32),
            mat * 2048u + r * 16, (uint32_t)xl ^ 16,
            S_A + (lane & 2) * 128u + g * 32 + ((lane ^ lane >> 4) & 1) * 16, S_C + row * 16, lane & 1 ? 16u : 9u, lane & 30u,
            lane == 4 ? 0xffff0000u : 0u, lane & 1 ? ~0u : 0u, lane < 16 ? ~0u : 0u, lane ? 0u : 0x20000u};
#pragma unroll
        for (int i = 0; i < 20; i++) wr[i >> 2][i & 3] = i < 16 ? opaque(c[i % 16], lane) : 0;
    }
    TS(21);
    mbar_wait(sm + O_WBC, 0);
    TS(22);
    if (act) {
        uint32_t s[8], y[12];
#pragma unroll
        for (int k = 0; k < 3; k++) *(uint4*)&y[4 * k] = lds128(sm + O_RH + t * 48 + k * 16);
#pragma unroll
        for (int k = 0; k < 2; k++) *(uint4*)&s[4 * k] = lds128(sm + O_SRC + t * 32 + k * 16);
#pragma unroll
        for (int i = 0; i < 8; i++) {
            const int k = 3 * i / 2;
            sts64(sm + O_OUT + ba[i] * 2, __byte_perm(y[k], s[i] + (tag >> 16) + 1, i & 1 ? 0x5432 : 0x5410),
                  i & 1 ? y[k + 1] : __byte_perm(y[k], y[k + 1], 0x5432));
        }
    }
    TS(12);
    __syncthreads();
    if (t == 352) { fence_async(); bulk_st(&gs->vals[b * CH], sm + O_OUT, ne * 8); WLD(7); }

    const uint32_t am = lane < 31 ? 511 : 0, none = tag | (320 + 4 * lane);
    auto check = [&]() {
        old = 0;
#pragma unroll
        for (int j = 0; j < SEGW; j++) {
            ho[j] = __shfl_sync(0xffffffffu, kv[j], 31);
            kv[j] = ho[j] >= (lane < 31 ? tag + ((lane + 1) << 12) : 0u) ? kv[j] : none;
            old |= kv[j] ^ tag;
        }
        return __any_sync(0xffffffffu, old >> 30);
    };
#pragma unroll
    for (int j = 0; j < SEGW; j++) kv[j] = ld_rlx(kp + j * (G * 32));
    TS(1);
    if (t == 352) WLD(1);
    TV(19, 0); TV(23, 0);
    for (int it = 0; check(); it++) {
        spin_check(it);
        if (it == 0) TS(20);
        TV(19, (it + 1) * 100);
#pragma unroll
        for (int j = 0; j < SEGW; j++)
            if (__any_sync(0xffffffffu, (kv[j] ^ tag) >> 30)) kv[j] = ld_rlx(kp + j * (G * 32));
    }
    TS(3);
    if (t == 352) WLD(2);
    kv[SEGW] = none; ho[SEGW] = 0;
    bool slow = false;
    const bool more = __any_sync(0xffffffffu, lane == 31 && (old & 0xfe0000));
    if (more) {
        int c = lane;
#pragma unroll
        for (int j = 0; j < SEGW; j++) {
            const int n = max((int)(ho[j] >> 12 & 0xfff) - 31, 0);
            if ((unsigned)c < (unsigned)n) ho[SEGW] = j * CH + (ho[j] & 0xfff) + 31 + c - lane;
            c -= n;
        }
        slow = lane == 31 && c < 0;
        if (c < 0 && lane < 31)
            for (int it = 0; ((kv[SEGW] = ld_rlx(&gs->more[w * SEGW * CH + lane + ho[SEGW]])) ^ tag) >> 30; it++) spin_check(it);
        __syncwarp();
    }
    uint32_t na_[SEGW + 1];
    uint64_t vp = (uint64_t)&gs->vals[w * SEGW * CH + lane], vv[SEGW + 1];
#pragma unroll
    for (int j = 0; j <= SEGW; j++) vv[j] = tag;
    auto ldv = [&](bool again) {
#pragma unroll
        for (int j = 0; j <= SEGW; j++)
            asm volatile("{.reg .pred p; setp.lt.u32 p, %2, 320; @p ld.relaxed.gpu.global.b64 %0, [%1];}" : "+l"(vv[j])
                         : "l"(madw(j < SEGW ? ho[j] & 0xfff : ho[j], 8, vp) + (j < SEGW ? j * CH * 8 : 0)),
                           "r"(again ? (((uint32_t)vv[j] ^ tag) >> 30 ? 0 : 320) : na_[j]) : "memory");
    };
#pragma unroll
    for (int j = 0; j <= SEGW; j++) na_[j] = (kv[j] & am) | (none & 511 & ~am);
#pragma unroll
    for (int j = 0; j <= SEGW; j++) nk[j] = atoms_add(sm + O_NCNT + na_[j], 512);
    auto visit = [&](auto f) {
#pragma unroll 1
        for (int j = 0; j < SEGW; j++) {
            const uint32_t* kl = &gs->keys[((w * SEGW + j) * G + b) * 32];
            const uint32_t h = ld_rlx(kl + ((31 + b) & 31));
#pragma unroll 1
            for (int i = lane; i < (h >> 12 & 0xfff); i += 32) {
                const int o = (w * SEGW + j) * CH + (h & 0xfff) + i;
                uint32_t k;
                int it = 0;
                do { k = ld_rlx(i < 31 ? kl + ((i + b) & 31) : &gs->more[o]); spin_check(it++); } while ((k ^ tag) >> 30);
                f(k, o, i);
            }
        }
    };
    slow = __syncthreads_or(slow);
    if (slow) {
        if (t < 80) sts32(sm + O_NCNT + 4 * t, t <= NLOC ? 4 * t : 0);
        __syncthreads();
        visit([&](uint32_t k, int, int) { atoms_add(sm + O_NCNT + (k & 511), 512); });
        __syncthreads();
    }
    TS(4);
    if (t == 352) WLD(3);
    if (w < 10) {
        const uint32_t key = lds32(sm + O_NCNT + 4 + (t & ~3));
        uint4 k[5];
#pragma unroll
        for (int i = 0; i < 5; i++) k[i] = lds128(sm + O_NCNT + q * 80 + i * 16);
        uint32_t c[4] = {0, 0, 0, 0};
#pragma unroll
        for (int i = 0; i < 5; i++) { c[0] += (key - k[i].x) >> 31; c[1] += (key - k[i].y) >> 31; c[2] += (key - k[i].z) >> 31; c[3] += (key - k[i].w) >> 31; }
        int rank = c[0] + c[1] + c[2] + c[3];
        rank += __shfl_xor_sync(0xffffffffu, rank, 1);
        rank += __shfl_xor_sync(0xffffffffu, rank, 2);
        if ((b & 1) && rank < 2 * NPRIV) rank = (2 * NPRIV - 1 - rank) ^ 1;
        if (t < NLOC * 4) sts32(sm + O_SORT + 4 * rank, key);
    }
    __syncthreads();
    TS(2);
    const bool on = lane < NLOC / 4;
    const uint4 k4 = lds128(sm + O_SORT + 16 * (on ? lane : 0));
    const uint32_t ks[4] = {k4.x, k4.y, k4.z, k4.w};
    const int n0 = on ? max(1u, (ks[0] + 3584) >> 12) : 0, n1 = on ? max(1u, (ks[2] + 3584) >> 12) : 0;
    const int u2 = warp_incl(n0 + n1), u1 = u2 - n1, u0 = u1 - n0;
    const int total = __shfl_sync(0xffffffffu, u2, 31);
    slow |= total > CAPT;
    const int m0 = slow ? n0 : max(2u, (ks[0] + 1536) >> 11), m1 = slow ? n1 : max(2u, (ks[2] + 1536) >> 11);
    int gbase = b * CAPT + 1;
    if (on) {
#pragma unroll
        for (int i = 0; i < 4; i++) {
            const int a = ks[i] & 511, node = a * (G / 4) - G + b, o = (i >> 1 ? u1 : u0) * 256 + (i & 1) * 16;
            const uint32_t mk = (node < NN ? node + 1 : 0) + ((i >> 1 ? m1 : m0) << 16);
            sts64(sm + O_NOFF + 2 * a, o - (a >> 4), mk + a * 32);
            if (!slow && ks[i] < 512) sts32(sm + O_L + 4 + o, mk);
        }
    }
    __syncwarp();
    if (t == 352) WLD(8);
    if (!slow) {
        uint32_t mk[SEGW + 1];
        TS(13);
        if (t == 352) { asm volatile("cp.async.bulk.wait_group.read 0;" ::: "memory"); }
        ldv(false);
        if (t == 352) WLD(4);
        TS(16);
#pragma unroll
        for (int j = 0; j <= SEGW; j++) {
            const uint2 o = lds64(sm + O_NOFF + 2 * na_[j]);
            mk[j] = o.y - nk[j] * 32; nk[j] = o.x + (nk[j] >> 4);
        }
        for (int it = 0;; it++) {
            old = 0;
#pragma unroll
            for (int j = 0; j <= SEGW; j++) old |= (uint32_t)vv[j] ^ tag;
            if (!__any_sync(0xffffffffu, old >> 30)) break;
            spin_check(it);
            vp = __shfl_sync(0xffffffffu, vp, lane);
            ldv(true);
            TV(23, (it + 1) * 100);
        }
        TS(17);
#pragma unroll
        for (int j = 0; j <= SEGW; j++)
            asm volatile("{.reg .pred p; setp.ne.u32 p, %3, %5; @p st.shared.v4.u32 [%0], {%1,%2,%3,%4};}"
                         ::"r"(sm + O_L + nk[j]), "r"(kv[j]), "r"(mk[j]), "r"((uint32_t)vv[j]), "r"((uint32_t)(vv[j] >> 32)), "r"(tag) : "memory");
        TS(18);
        if (na_[SEGW] < 320) gs->more[w * SEGW * CH + lane + ho[SEGW]] = 0;
    } else {
        int so = 0;
        if (t == 352) WLD(4);
#pragma unroll
        for (int j = 0; j < SEGW; j++) so += ho[j] & 0xfff;
        if (lane == 0) atoms_add(sm + O_SUM, so);
        if (t == 352) asm volatile("cp.async.bulk.wait_group.read 0;" ::: "memory");
        __syncthreads();
        gbase = TBIG + (lds32(sm + O_SUM) >> 3) + (NLOC + 5) * b;
        auto put = [&](uint32_t k, uint64_t e, uint32_t a, int rank) {
            const uint2 o = lds64(sm + O_NOFF + 2 * a);
            const uint32_t m = o.y - a * 32 - (rank << 13);
            gs->list[gbase * 16 + ((o.x + (a >> 4)) >> 4) + rank * 2] = make_uint4(k, (m & 0xffff) | min(m >> 16, 0x7fffu) << 17, e, e >> 32);
        };
        visit([&](uint32_t k, int o, int i) {
            uint64_t e;
            int it = 0;
            do {
                asm volatile("ld.relaxed.gpu.global.b64 %0, [%1];" : "=l"(e) : "l"(&gs->vals[o]) : "memory");
                spin_check(it++);
            } while (((uint32_t)e ^ tag) >> 30);
            if (i >= 31) gs->more[o] = 0;
            put(k, e, k & 511, atoms_add(sm + O_NCUR + (k & 511), 1));
        });
#pragma unroll 1
        for (int i = 0; i < 4; i++) {
            const uint32_t k = i == 0 ? ks[0] : i == 1 ? ks[1] : i == 2 ? ks[2] : ks[3];
#pragma unroll 1
            for (int p = (k >> 9) + w; p < (i >> 1 ? n1 : n0) * 8; p += NT / 32) put(0, 0, k & 511, p);
        }
        __threadfence();
    }
    if (t == 352) WLD(9);
    const uint32_t iw0 = (gbase + u0) << 12 | n0, iw1 = (gbase + u1) << 12 | n1;
    __syncthreads();
    TS(5);

    if (w >= 8) {
        asm volatile("setmaxnreg.dec.sync.aligned.u32 56;");
        const int h = __reduce_max_sync(0xffffffffu, w & 3);
        if (h == 0) TSW(28);
        gbase = __reduce_min_sync(0xffffffffu, iw0) >> 12;
        int pos = gbase + h, end = __reduce_max_sync(0xffffffffu, lane == NPRIV / 2 ? (NPRIV & 1 ? iw1 : iw0) : 0) >> 12;
        const int bytes = gbase < TBIG ? ((__reduce_max_sync(0xffffffffu, iw0) >> 12) - gbase) * 256 : 0;
        const uint32_t ring = sm + O_RING;
        const uint64_t xl[2] = {wr[0][0] | (uint64_t)wr[0][1] << 32, wr[1][3] | (uint64_t)wr[0][1] << 32};
        const uint64_t al = wr[0][2] | (uint64_t)wr[0][3] << 32, ml = wr[1][0] | (uint64_t)wr[1][1] << 32;
        const uint32_t xoff = wr[1][2], aoff = wr[2][0], coff = wr[2][1], sh = wr[2][2], ial = wr[2][3], sel = wr[3][0];
        const uint32_t odd = wr[3][1], low = wr[3][2], lim = wr[3][3];
        auto lde = [&](uint2& e, int p) {
            asm volatile("{.reg .pred p; setp.gt.s32 p, %3, 0; @p ld.relaxed.gpu.global.v2.u32 {%0,%1}, [%2];}" : "+r"(e.x), "+r"(e.y) : "l"(madw(p, 256, ml)), "r"(p) : "memory");
        };
        uint2 e0[3] = {};
#pragma unroll
        for (int k = 0; k < 3; k++) {
            e0[k] = lds64(sm + O_L + k * 1024 + h * 256 + ((uint32_t)ml & 255));
            lde(e0[k], bytes ? 0 : pos + 4 * k);
        }
        if (h == 3) fence_async();
        else asm volatile("bar.arrive 4, %0;" ::"n"(NT) : "memory");
        pos += 4;

        int ev = 0, state = -2, tk = 0, nr = 0;
        uint32_t inf = 0;
        int ii = 0;
        auto take = [&]() {
            int v = 0;
            asm volatile("{.reg .pred p; setp.eq.s32 p, %2, 0; @p atom.relaxed.gpu.global.add.u32 %0, [%1], 1;}" : "+r"(v) : "l"(&gs->ticket), "r"(lane) : "memory");
            return v;
        };
        auto resolve = [&]() {
            const int k = __reduce_max_sync(0xffffffffu, tk);
            inf = tag;
            if (k < G * NPOOL) { const int l = k / G; ii = (k - l * G) * NPOOL + l; inf = ld_rlx(&gs->info[ii]);
                const int j = NPRIV + 1 + nr + (b & 7), gd = __reduce_max_sync(0xffffffffu, lds32(sm + O_SUM + 4));
                tk = (b & 7) && (j & ~7) > gd && k >= G * NPOOL - (j & 7 ? G : 5 * G / 3) ? G * NPOOL : take(); }
        };
        uint32_t so = ring + h * SLOT, ph = 0x80000000u;
        uint32_t spins = 0;
        asm volatile(".reg .pred z<5>;");
        { const uint32_t c0 = clock(); while (__any_sync(0xffffffffu, (uint32_t)clock() - c0 < h * 300)); }
        while (true) {
            const uint2 e = e0[0];
            const uint32_t o = e.x >> sh, id = __shfl_sync(0xffffffffu, o, ial);
            uint32_t s[4];
#pragma unroll
            for (int j = 0; j < 4; j++) s[j] = __shfl_sync(0xffffffffu, o, 2 * j + 1, 8);
            const uint32_t nx = so == ring + (NSLOT - 1) * SLOT ? ph : ph ^ 0x80000000u, ey = lop_sel(e.y, nx, sel);
            const uint32_t ym = lop_sel(__shfl_xor_sync(0xffffffffu, e.x, 1), e.y, odd);
            const bool full = __all_sync(0xffffffffu, e.y >= lim);
            const uint64_t ga = madw(id, 32, al);
            uint64_t gx[4];
#pragma unroll
            for (int j = 0; j < 4; j++) gx[j] = madw(s[j], 1024, xl[j >> 1]);
            const uint32_t da = so + aoff, dx = so + xoff, dc = so + coff;
            asm volatile("setp.eq.u32 z0, %0, 0;\nsetp.eq.u32 z1, %1, 0;\nsetp.eq.u32 z2, %2, 0;\nsetp.eq.u32 z3, %3, 0;\nsetp.eq.u32 z4, %4, 0;\n"
                         ::"r"(s[0]), "r"(s[1]), "r"(s[2]), "r"(s[3]), "r"(id), "l"(ga), "r"(da), "r"(dx), "r"(dc), "l"(gx[0]), "l"(gx[1]), "l"(gx[2]), "l"(gx[3]));
            asm volatile("{.reg .pred p; setp.gt.s32 p, %3, 0; @p ld.relaxed.gpu.global.v2.u32 {%0,%1}, [%2];}"
                         : "=r"(e0[0].x), "=r"(e0[0].y) : "l"((uint64_t)(gs->list + pos * 16) + ((uint32_t)ml & 255)), "r"(state < 0 ? 0 : pos) : "memory");
            if (h == 0 && state == -2) TSW(29);
            if (h == 0 && state == -1) TSW(30);
            asm volatile("{\n.reg .pred p;\n.reg .b64 s;\nmov.b64 s, {0, %2};\n"
                         "LOOP:\nmbarrier.try_wait.shared::cta.b64 p, [%1], s;\n@p bra DONE;\n"
                         "add.u32 %0, %0, 1;\nsetp.gt.u32 p, %0, %3;\n@p trap;\nbra LOOP;\nDONE:\n}"
                         : "+r"(spins) : "r"(so + S_EMPTY), "r"(ph), "n"(SPIN_LIMIT) : "memory");
            asm volatile("cp.async.cg.shared.global [%0], [%1], 16, z4;" ::"r"(da), "l"(ga) : "memory");
#define ROW(j) _Pragma("unroll") for (int k = 0; k < 8; k++) \
                asm volatile("cp.async.cg.shared.global [%0], [%1], 16, z" #j ";" ::"r"(dx + (j >> 1) * 1024 + (j & 1) * 8192 + k * 128), "l"(gx[j] + k * 128) : "memory")
            ROW(0); ROW(2);
            if (full) { ROW(1); ROW(3); }
            stsm4t(dc, ym, ey, ym & low, ym & ~low);
            asm volatile("cp.async.mbarrier.arrive.noinc.shared::cta.b64 [%0];" ::"r"(so + S_FULL) : "memory");
            const bool wrap = so >= ring + (NSLOT - 4) * SLOT;
            ph ^= wrap ? 0x80000000u : 0u;
            so = wrap ? so - (NSLOT - 4) * SLOT : so + 4 * SLOT;
            pos += 4;
            if (pos >= ev) {
                if (state < 0) {
                    e0[0].x = state == -2 ? e0[1].x : e0[2].x; e0[0].y = state == -2 ? e0[1].y : e0[2].y;
                    if (state == -2) {
                        if (h == 0) TSW(24);
                        if (h == 3) TSW(25);
                        if (h == 0) asm volatile("bar.arrive 5, 288;" ::: "memory");
                        if (h < 3) bar_sync(7, 352);
                        if (h == 3) bar_sync(4, NT);
                        if (h == 0) mbar_wait(sm + O_WBE, 0);
                        if (h == 3) {
                            if (lane == 0) {
                                if (bytes) bulk_st(gs->list + gbase * 16, sm + O_L, bytes);
                                asm volatile("cp.async.bulk.wait_group.read 0;" ::: "memory");
                            }
                            __syncwarp();
                            if (lane == 0) {
                                for (int j = KR; j < 24; j++) tma3d(sm + O_W1 + (j - KR) * 4096, &m_w1, 16 * j, 0, sm + O_WBB);
                            }
                            __syncwarp();
                        }
                        state = -1;
                    } else {
                        if (h == 3) {
                            if (lane == 0) asm volatile("cp.async.bulk.wait_group 0;\nfence.proxy.async;" ::: "memory");
                            __syncwarp();
                            const int i = opaque(2 * lane - NPRIV, lane);
                            if ((unsigned)i < NPOOL) st_rlx(&gs->info[b * NPOOL + i], tag | iw0);
                            if ((unsigned)(i + 1) < NPOOL) st_rlx(&gs->info[b * NPOOL + i + 1], tag | iw1);
                        }
                        bar_sync(6, 128);
                        ev = h ? end : end - 12; state = h ? 2 : 0;
                    }
                } else if (state == 0) { ev = end - 6; state = 1; tk = take(); }
                else if (state == 1) { resolve(); ev = end; state = 2; }
                else {
                    if (state == 3) break;
                    do {
                        const uint32_t mb = sm + O_MB + (nr & 15) * 8;
                        uint32_t rg;
                        nr++;
                        if (h == 0) {
                            for (int it = 0; (rg = __reduce_max_sync(0xffffffffu, inf ^ tag)) >> 30; it++) { spin_check(it); inf = ld_rlx(&gs->info[ii]); }
                            asm volatile("st.release.cta.shared.b64 [%0], %1;" ::"r"(mb), "l"(rg | (uint64_t)nr << 32) : "memory");
                            if (rg) resolve();
                        } else {
                            uint64_t m;
                            for (int it = 0;; it++) {
                                asm volatile("ld.acquire.cta.shared.b64 %0, [%1];" : "=l"(m) : "r"(mb) : "memory");
                                if (__all_sync(0xffffffffu, (int)(m >> 32) == nr)) break;
                                spin_check(it);
                            }
                            rg = __reduce_max_sync(0xffffffffu, (uint32_t)m);
                        }
                        pos = rg ? (int)(rg >> 12) + pos - end : 0;
                        end = rg ? (rg >> 12) + (rg & 0xfff) : 1;
                        state = rg ? 2 : 3;
                    } while (pos >= end);
                    ev = end;
                }
            }
        }
        mbar_wait31(so + S_EMPTY, ph);
        TSW(8 + (h & 1));
        if (lane == 0) sts32(so + S_N, 0);
        mbar_arrive(so + S_FULL);
        if (t == 256) {
            gs->epoch[b * 32] = (tag >> 30) % 3;
            if (atomicInc(&gs->done, G - 1) == G - 1) gs->ticket = 0;
        }
        asm volatile("cp.async.wait_all;" ::: "memory");
    } else {
        asm volatile("setmaxnreg.inc.sync.aligned.u32 224;");
        bar_sync(5, 288);
        const uint32_t xa = opaque(((mat >> 1) * 8 + r) * 1024 + (w >> 2) * 128 + (((2 * (w & 3) + (mat & 1)) ^ r) * 16), lane);
        const uint32_t aa = opaque(S_A + ((mat >> 1) * 8 + r) * 32 + (((mat & 1) ^ (r >> 2)) * 16), lane);
        const uint32_t ya = opaque(S_C + (mat & 1) * 80 + (mat >> 1) * 16, lane);
        const uint32_t yc = opaque(S_C + (mat < 2 ? mat * 80 + 32 : q < 3 ? mat * 128 + ((r >> 2) ^ (mat & 1)) * 80 + q * 16 : 64), lane);
        const uint32_t na = opaque((mat & 1) * 8, lane);
        const uint32_t pw = sm + O_P + w * PW;
        const uint32_t fx = opaque(pw + (q < 3 ? P_1P0 + 2 * q * PSBO : P_1P1 + PSBO) + (mat & 1) * 128 + (r >> 2) * PSBO, lane);
        const uint32_t fyz = opaque(pw + (q < 3 ? (mat < 2 ? P_1P1 : P_1P2) + 2 * q * PSBO : mat < 2 ? P_0P0 : P_0P1) + (mat & 1) * 128 + (r >> 2) * PSBO, lane);
        uint32_t oh[5];
#pragma unroll
        for (int c = 0; c < 5; c++) oh[c] = opaque(g == (q >> 1) * 4 + min(c, 3) ? 0x3F803F80u : 0u, lane ^ c >> 2);
        uint32_t eb[3];
#pragma unroll
        for (int k = 0; k < 3; k++) {
            const int i = (g & 3) * 9 + (q & 1) * 6 + k;
            const uint32_t lo = __shfl_sync(0xffffffffu, epl, i), hi = __shfl_sync(0xffffffffu, epl, i + 3);
            eb[k] = (g & 3) < 3 && (q >> 1) == (g >> 2) ? (q & 1 ? lo : lo | hi << 16) : 0u;
        }
        asm volatile(".reg .pred lane0;\nsetp.eq.u32 lane0, %0, 0;" ::"r"(lane));
        uint32_t w0[16][4], w1[KR][4];
        mbar_wait(sm + O_WBD, 0);
#pragma unroll
        for (int k = 0; k < 16; k++) ldsm4t(w0[k], sm + w0s(k >> 2) + (w >> 2) * 8192 + (k & 3) * 2048 + sw);
#pragma unroll
        for (int k = 0; k < KR; k++) ldsm4t(w1[k], sm + w1s(k) + (w >> 2) * 2048 + sw);
        asm volatile("bar.arrive 4, %0;" ::"n"(NT) : "memory");
        bar_sync(7, 352);
        TS(6);
        Acc A;
#pragma unroll
        for (int i = 0; i < 4; i++) { A.p[i] = A.p[4 + i] = A.p[8 + i / 2] = 0; A.t01[i] = A.m[0][i] = A.m[1][i] = A.m[2][i] = 0.f; }
        uint32_t room = 144 - (b & 7) * 16;
        uint32_t so = sm + O_RING, ph, a[4], ok, go, mt = 0;
        mbar_wait(so + S_FULL, 0);
        ldsm4(a, so + aa);
        TS(7);
        while (true) {
            {
                constexpr int F = 1, H = 0, XS = XS_F;
                int seen = 0;
                uint32_t yb[8], f[4][4], R[5][4], u[4][4], sd[4];
                float y[4], z[4];
                const uint32_t sof = room & 112;
                room -= 16;
                SEQ_F
            }
            if (!(go && room)) {
                const uint32_t pu = __reduce_max_sync(0xffffffffu, ph);
                if (!room || !pu) {
                    const uint32_t wg = __reduce_max_sync(0xffffffffu, w >> 2);
                    mbar_wait(sm + O_WBB, 0);
                    asm volatile("{.reg .pred p; setp.ne.u32 p, %0, 0;\n@p bar.arrive 1, 256;\n@p bar.sync 2, 256;\n@!p bar.sync 1, 256;}" ::"r"(wg) : "memory");
                    asm volatile("fence.proxy.async::generic.acquire.sync_restrict::shared::cluster.cluster;" ::: "memory");
                    float d0[8], d1[24];
                    const uint64_t db = (uint64_t)((sm + O_P) >> 4) | (8ull << 16) | ((uint64_t)(PSBO / 16) << 32);
                    const uint32_t da = ((sm + O_W1) >> 4 | 1 << 16) + wg * 128;
                    asm volatile("wgmma.fence.sync.aligned;" ::: "memory");
                    const uint32_t sp = so == sm + O_RING ? sm + O_RING + (NSLOT - 1) * SLOT : so - SLOT, sr = (r & 6) + (mat & 1);
                    const uint32_t nd = (sr * 16 - 16 & 112) >= room ? lds32(sm + O_NODE + sr * 16 + (mat >> 1) * 8) : 0;
                    const uint64_t oa = madw(nd, 1024, (uint64_t)(out - 1024 + w * 32 + (r & 1) * 16));
                    const uint32_t sl = sp + ((mat >> 1) * 8 + sr) * 1024 + (w >> 2) * 128 + (((2 * (w & 3) + (r & 1)) ^ sr) * 16);
                    auto put = [&](int j) {
                        const uint4 v = lds128(sl + j * 256);
                        asm volatile("{.reg .pred p; setp.ne.u32 p, %5, 0; @p st.global.v4.u32 [%0], {%1,%2,%3,%4};}"
                                     ::"l"(oa + j * 256), "r"(v.x), "r"(v.y), "r"(v.z), "r"(v.w), "r"(nd) : "memory");
                    };
                    static_for<24>([&](auto kc) {
                        constexpr int k = kc.value;
                        if (k == 16) asm volatile("wgmma.commit_group.sync.aligned;" ::: "memory");
                        if (k == 20) asm volatile("{.reg .pred p; setp.eq.u32 p, %0, 0;\n@p bar.arrive 2, 256;}" ::"r"(wg) : "memory");
                        G1(k);
                        if (k < 16) G0(k % 16);
                    });
                    asm volatile("wgmma.commit_group.sync.aligned;" ::: "memory");
                    asm volatile("wgmma.wait_group.sync.aligned 1;" ::: "memory");
#pragma unroll
                    for (int i = 0; i < 8; i++) asm volatile("" : "+f"(d0[i])::"memory");
                    stsm4t(sp + xa, pack(d0[0], d0[1]), pack(d0[2], d0[3]), pack(d0[4], d0[5]), pack(d0[6], d0[7]));
                    __syncwarp();
                    put(0);
                    float gt[8];
                    uint32_t chk = -1;
#pragma unroll
                    for (int i = 0; i < 8; i++) {
                        asm volatile("ex2.approx.ftz.f32 %0, %1;" : "=f"(gt[i]) : "f"(d0[i] * -1.4426950408889634f) : "memory");
                        asm volatile("rcp.approx.ftz.f32 %0, %1;" : "=f"(gt[i]) : "f"(gt[i] + 1.f) : "memory");
                    }
#pragma unroll
                    for (int i = 0; i < 8; i++) chk &= __float_as_uint(gt[i]);
                    sts32(sm + O_TRASH, chk);
                    asm volatile("wgmma.wait_group.sync.aligned 0;" ::: "memory");
#pragma unroll
                    for (int i = 0; i < 24; i++) asm volatile("" : "+f"(d1[i])::"memory");
                    asm volatile("{.reg .pred p; setp.ne.u32 p, %0, 0;\n@p bar.sync 3, 256;}" ::"r"(wg) : "memory");
#pragma unroll
                    for (int j = 0; j < 3; j++) {
                        uint32_t o[4];
#pragma unroll
                        for (int i = 0; i < 4; i++) o[i] = pack(d1[8 * j + 2 * i] * gt[2 * i], d1[8 * j + 2 * i + 1] * gt[2 * i + 1]);
                        stsm4t(sp + xa + 256 + j * 256, o[0], o[1], o[2], o[3]);
                    }
                    __syncwarp();
#pragma unroll
                    for (int j = 1; j < 4; j++) put(j);
                    __syncwarp();
                    asm volatile("@lane0 mbarrier.arrive.shared::cta.b64 _, [%0];" ::"r"(sp + S_EMPTY) : "memory");
                    asm volatile("@lane0 red.shared.add.u32 [%0], 1;" ::"r"(sm + O_SUM + 4) : "memory");
                    asm volatile("{.reg .pred p; setp.eq.u32 p, %0, 0;\n@p bar.sync 3, 256;}" ::"r"(wg) : "memory");
                    room = 128;
                    if (!pu) break;
                }
                if (!ok) { mbar_wait31(so + S_FULL, pu); ldsm4(a, so + aa); }
                if (!(pu & 0xfffc)) { if (pu & 1) goto half; continue; }
            }
            while (true) {
                do {
                    constexpr int F = 0, H = 0, XS = XS_R;
                    int seen = 0;
                    uint32_t yb[8], f[4][4], R[5][4], u[4][4], sd[4];
                    SEQ_R
                } while (go);
                if (ok) {
                    asm volatile("{.reg .pred p; .reg .f32 n; abs.f32 n, %1; setp.gt.f32 p, n, 0f00000002; selp.u32 %0, 1, 0, p;}" : "=r"(go) : "r"(ph));
                    break;
                }
                const uint32_t pu = __reduce_max_sync(0xffffffffu, ph);
                mbar_wait31(so + S_FULL, pu); ldsm4(a, so + aa);
                if (!(pu & 0xfffc)) { go = pu & 1; break; }
            }
            if (!go) continue;
        half: {
                constexpr int F = 0, H = 1, XS = XS_H;
                int seen = 0;
                uint32_t yb[8], f[4][4], R[5][4], u[4][4], sd[4];
                SEQ_H
                if (!ok) { mbar_wait31(so + S_FULL, __reduce_max_sync(0xffffffffu, ph)); ldsm4(a, so + aa); }
            }
        }
        TS(10);
    }
}

typedef CUresult (*EncFn)(CUtensorMap*, CUtensorMapDataType, cuuint32_t, void*, const cuuint64_t*, const cuuint64_t*,
                          const cuuint32_t*, const cuuint32_t*, CUtensorMapInterleave, CUtensorMapSwizzle,
                          CUtensorMapL2promotion, CUtensorMapFloatOOBfill);

void make_map(EncFn fn, CUtensorMap* m, void* p, int rows, int cols, int brows, int bcols, int bblk) {
    cuuint64_t dims[3] = {64, (cuuint64_t)rows, (cuuint64_t)cols / 64}, strides[2] = {(cuuint64_t)cols * 2, 128};
    cuuint32_t box[3] = {(cuuint32_t)bcols, (cuuint32_t)brows, (cuuint32_t)bblk}, es[3] = {1, 1, 1};
    fn(m, CU_TENSOR_MAP_DATA_TYPE_BFLOAT16, 3, p, dims, strides, box, es, CU_TENSOR_MAP_INTERLEAVE_NONE,
       bcols == 64 ? CU_TENSOR_MAP_SWIZZLE_128B : CU_TENSOR_MAP_SWIZZLE_NONE, CU_TENSOR_MAP_L2_PROMOTION_L2_128B, CU_TENSOR_MAP_FLOAT_OOB_FILL_NONE);
}

}

extern "C" void kernel_launch(void* const* d_in, const int* in_sizes, int n_in, void* d_out, int out_size) {
    static EncFn enc = nullptr;
    static void* scratch = nullptr;
    if (!enc) {
        void* fn = nullptr;
        cudaDriverEntryPointQueryResult qr;
        cudaGetDriverEntryPoint("cuTensorMapEncodeTiled", &fn, cudaEnableDefault, &qr);
        enc = (EncFn)fn;
        cudaGetSymbolAddress(&scratch, g_scratch);
        cudaFuncSetAttribute(tp_kernel, cudaFuncAttributeMaxDynamicSharedMemorySize, SMEM_BYTES);
    }
    CUtensorMap m_wr, m_w0, m_w1, m_x;
    make_map(enc, &m_wr, d_in[5], 16, 640, 16, 64, 5);
    make_map(enc, &m_w0, d_in[6], 256, 128, 64, 64, 2);
    make_map(enc, &m_w1, d_in[7], 384, 128, 16, 64, 2);
    make_map(enc, &m_x, d_in[0], NN * 8, 64, NLOC * 2, 8, 1);
    tp_kernel<<<G, NT, SMEM_BYTES>>>((const int4*)d_in[4], (const int4*)d_in[3], (const char*)d_in[1], (Scratch*)scratch,
                                     (const char*)d_in[0], (const char*)d_in[2], (const __nv_bfloat16*)d_in[8], (char*)d_out,
                                     m_wr, m_w0, m_w1, m_x);
}
```

```cpp
#include <cuda_runtime.h>
#include <cuda_bf16.h>
#include <cuda.h>
#include <stdint.h>
#include <stddef.h>

namespace {

constexpr int NN = 10000;
constexpr int NE = 320000;
constexpr int G = 132;
constexpr int NT = 384;
constexpr int CH = 2432;
constexpr int NLOC = (NN + G - 1) / G;
constexpr int NPOOL = 3;
constexpr int NPAIR = NLOC / 2, NPRIV = NPAIR - NPOOL;
constexpr int SEGW = 11;

constexpr int NSLOT = 7;
constexpr int KR = 9;
constexpr uint32_t WP = 0x5357575, TP = 0x9375;
#define WLD(p) { _Pragma("unroll") for (int j = 0; j < 4 + KR; j++) if ((WP >> 4 * (j < 4 ? j : j < 8 ? 4 : j < 11 ? 5 : 6) & 15) == p) \
    tma3d(sm + (j < 4 ? w0s(j) : w1s(j - 4)), j < 4 ? &m_w0 : &m_w1, j < 4 ? j * 64 : (j - 4) * 16, 0, sm + O_WBD); \
    _Pragma("unroll") for (int j = 0; j < 4; j++) { const int r0 = (b * 4 + j) * (NLOC / 4); \
        if ((TP >> 4 * j & 15) == p) tma3d(sm + O_WR1 + 12288, &m_x, r0 * 8, 0, sm + O_WBE); } }

constexpr int S_A = 16384, S_C = S_A + 512, S_FULL = S_C + 144, S_EMPTY = S_FULL + 8, S_N = S_C + 160, SLOT = S_C + 512;

constexpr int PSBO = 272;
constexpr int PB1 = 5 * PSBO + 256, PB0 = PSBO + 256;
constexpr int P_1P0 = 0, P_1P1 = PB1, P_0P1 = 2 * PB1, P_0P0 = P_0P1 + PB0, P_1P2 = P_0P0 + PB0;
constexpr int PW = P_1P2 + PB1;

constexpr int O_W1 = 0;
constexpr int O_P = 62336;
constexpr int O_RING = O_P + 8 * PW;
constexpr int O_WBA = O_RING + NSLOT * SLOT, O_WBB = O_WBA + 8, O_WBC = O_WBA + 16, O_WBD = O_WBA + 24, O_WBE = O_WBA + 32, O_TRASH = O_WBA + 40, O_NODE = O_WBA + 48;
constexpr int O_SUM = O_NODE + 128, O_MB = O_SUM + 16;
constexpr int SMEM_BYTES = O_MB + 128;
constexpr int CAPT = 192;
constexpr int O_L = 0, LZ = CAPT * 256 / (NT * 16), O_W0S = O_L + CAPT * 256, O_OUT = O_RING + S_C - CH * 8, O_SRC = O_RING + 6 * SLOT;
constexpr int O_KT = O_RING + SLOT, O_RH = O_RING + 2 * SLOT;
constexpr int O_WR0 = O_RING + 3 * SLOT, O_WR1 = O_RING + 4 * SLOT;
__host__ __device__ constexpr int w0s(int j) { return j < 3 ? O_W0S + j * 16384 : O_SRC; }
__host__ __device__ constexpr int w1s(int k) { return k < 4 ? O_RING + 5 * SLOT + k * 4096 : k < 7 ? O_WR1 + (k - 4) * 4096 : O_W0S + 49152 + (k - 7) * 4096; }
constexpr int O_BCNT = O_WR0 + 10240, O_NCUR = O_BCNT + 640, O_NCNT = O_NCUR + 320;
constexpr int O_BOFF = O_NCNT + 512, O_SORT = O_BOFF + 640, O_NOFF = O_SORT + 320;
constexpr int TBIG = G * CAPT + 8, NTILE = TBIG + NE / 8 + G * (NLOC + 5);
static_assert(SMEM_BYTES <= 232448 && CAPT % 16 == 0 && NTILE < (1 << 18), "smem");
static_assert(LZ * NT * 16 == CAPT * 256 && O_W0S % 1024 == 0 && w1s(KR) <= O_OUT && O_OUT % 128 == 0 && CH * 6 <= S_C && G * 128 <= S_C, "staging");
static_assert(O_NOFF + 1024 <= O_RING + 3 * SLOT + S_C && 12288 + NLOC * 32 <= S_C && (24 - KR) * 4096 <= O_P && KR <= 9, "staging");
static_assert(O_RING % 1024 == 0 && SLOT % 1024 == 0 && O_W0S <= O_P && O_NOFF % 8 == 0, "layout");
static_assert(G * CH >= NE && NE % 8 == 0 && CH < 4096 && CH / 8 <= 320 && NE < (1 << 21), "chunks");
static_assert(SEGW * (NT / 32) == G && G <= 160 && G % 4 == 0, "segments");
static_assert(NLOC % 4 == 0 && NLOC < 80 && NLOC * 4 <= 320 && NN < 0x3fff && NE / 8 < 0xbfff && NPRIV >= 30, "scan width");

struct __align__(256) Scratch {
    uint32_t keys[G * G * 32];
    uint64_t vals[G * CH];
    uint32_t more[G * CH];
    uint32_t epoch[G * 32];
    uint32_t info[(G * NPOOL + 127) / 128 * 128];
    unsigned done, pad0[31], ticket, pad1[31];
    uint4 list[NTILE * 16];
};
static_assert(offsetof(Scratch, list) % 256 == 0, "list");
__device__ Scratch g_scratch;
#define TS(i)
#define TSW(i)
#define TV(i, v)

constexpr int SPIN_LIMIT = 1 << 24;

__device__ __forceinline__ void mbar_init(uint32_t a, int c) { asm volatile("mbarrier.init.shared::cta.b64 [%0], %1;" ::"r"(a), "r"(c) : "memory"); }
__device__ __forceinline__ void mbar_expect(uint32_t a, int b) { asm volatile("mbarrier.arrive.expect_tx.shared::cta.b64 _, [%0], %1;" ::"r"(a), "r"(b) : "memory"); }
__device__ __forceinline__ void mbar_arrive(uint32_t a) { asm volatile("mbarrier.arrive.shared::cta.b64 _, [%0];" ::"r"(a) : "memory"); }
__device__ __forceinline__ void mbar_wait(uint32_t a, uint32_t ph) {
    asm volatile("{\n.reg .pred p, q;\n.reg .u32 it;\n"
                 "mbarrier.try_wait.parity.shared::cta.b64 p, [%0], %1;\n"
                 "@p bra DONE;\n"
                 "mov.u32 it, 0;\n"
                 "LOOP:\n"
                 "mbarrier.try_wait.parity.shared::cta.b64 p, [%0], %1;\n"
                 "@p bra DONE;\n"
                 "add.u32 it, it, 1;\n"
                 "setp.gt.u32 q, it, %2;\n"
                 "@q trap;\n"
                 "bra LOOP;\n"
                 "DONE:\n}" ::"r"(a), "r"(ph), "n"(SPIN_LIMIT) : "memory");
}
__device__ __forceinline__ void mbar_wait31(uint32_t a, uint32_t ph) {
    asm volatile("{\n.reg .pred p, q;\n.reg .u32 it;\n.reg .b64 s;\n"
                 "mov.b64 s, {0, %1};\n"
                 "mbarrier.try_wait.shared::cta.b64 p, [%0], s;\n"
                 "@p bra DONE;\n"
                 "mov.u32 it, 0;\n"
                 "LOOP:\n"
                 "mbarrier.try_wait.shared::cta.b64 p, [%0], s;\n"
                 "@p bra DONE;\n"
                 "add.u32 it, it, 1;\n"
                 "setp.gt.u32 q, it, %2;\n"
                 "@q trap;\n"
                 "bra LOOP;\n"
                 "DONE:\n}" ::"r"(a), "r"(ph), "n"(SPIN_LIMIT) : "memory");
}
__device__ __forceinline__ void spin_check(int it) {
    asm volatile("{\n.reg .pred q;\nsetp.gt.s32 q, %0, %1;\n@q trap;\n}" ::"r"(it), "n"(SPIN_LIMIT));
}
__device__ __forceinline__ void ldsm4(uint32_t* r, uint32_t a) { asm volatile("ldmatrix.sync.aligned.m8n8.x4.shared.b16 {%0,%1,%2,%3}, [%4];" : "=r"(r[0]), "=r"(r[1]), "=r"(r[2]), "=r"(r[3]) : "r"(a) : "memory"); }
__device__ __forceinline__ void ldsm4t(uint32_t* r, uint32_t a) { asm volatile("ldmatrix.sync.aligned.m8n8.x4.trans.shared.b16 {%0,%1,%2,%3}, [%4];" : "=r"(r[0]), "=r"(r[1]), "=r"(r[2]), "=r"(r[3]) : "r"(a) : "memory"); }
__device__ __forceinline__ void ldsm2t(uint32_t* r, uint32_t a) { asm volatile("ldmatrix.sync.aligned.m8n8.x2.trans.shared.b16 {%0,%1}, [%2];" : "=r"(r[0]), "=r"(r[1]) : "r"(a) : "memory"); }
__device__ __forceinline__ void stsm4t(uint32_t a, uint32_t r0, uint32_t r1, uint32_t r2, uint32_t r3) { asm volatile("stmatrix.sync.aligned.m8n8.x4.trans.shared.b16 [%0], {%1,%2,%3,%4};" ::"r"(a), "r"(r0), "r"(r1), "r"(r2), "r"(r3) : "memory"); }
__device__ __forceinline__ void stsm2t(uint32_t a, uint32_t r0, uint32_t r1) { asm volatile("stmatrix.sync.aligned.m8n8.x2.trans.shared.b16 [%0], {%1,%2};" ::"r"(a), "r"(r0), "r"(r1) : "memory"); }
__device__ __forceinline__ void mma16(float* d, const uint32_t* a, uint32_t b0, uint32_t b1) {
    asm("mma.sync.aligned.m16n8k16.row.col.f32.bf16.bf16.f32 {%0,%1,%2,%3}, {%4,%5,%6,%7}, {%8,%9}, {%0,%1,%2,%3};"
        : "+f"(d[0]), "+f"(d[1]), "+f"(d[2]), "+f"(d[3]) : "r"(a[0]), "r"(a[1]), "r"(a[2]), "r"(a[3]), "r"(b0), "r"(b1));
}
__device__ __forceinline__ void mma8(float* d, uint32_t a0, uint32_t a1, uint32_t b0) {
    asm("mma.sync.aligned.m16n8k8.row.col.f32.bf16.bf16.f32 {%0,%1,%2,%3}, {%4,%5}, {%6}, {%0,%1,%2,%3};"
        : "+f"(d[0]), "+f"(d[1]), "+f"(d[2]), "+f"(d[3]) : "r"(a0), "r"(a1), "r"(b0));
}
__device__ __forceinline__ void mma16z(float* d, const uint32_t* a, uint32_t b0, uint32_t b1) {
    asm("mma.sync.aligned.m16n8k16.row.col.f32.bf16.bf16.f32 {%0,%1,%2,%3}, {%4,%5,%6,%7}, {%8,%9}, {%10,%10,%10,%10};"
        : "=f"(d[0]), "=f"(d[1]), "=f"(d[2]), "=f"(d[3]) : "r"(a[0]), "r"(a[1]), "r"(a[2]), "r"(a[3]), "r"(b0), "r"(b1), "f"(0.f));
}
__device__ __forceinline__ uint32_t pack(float lo, float hi) { uint32_t r; asm("cvt.rn.bf16x2.f32 %0, %1, %2;" : "=r"(r) : "f"(hi), "f"(lo)); return r; }
__device__ __forceinline__ uint32_t hmul(uint32_t a, uint32_t b) { uint32_t r; asm("mul.rn.bf16x2 %0, %1, %2;" : "=r"(r) : "r"(a), "r"(b)); return r; }
__device__ __forceinline__ uint32_t hfma(uint32_t a, uint32_t b, uint32_t c) { uint32_t r; asm("fma.rn.bf16x2 %0, %1, %2, %3;" : "=r"(r) : "r"(a), "r"(b), "r"(c)); return r; }
__device__ __forceinline__ uint4 lds128(uint32_t a) { uint4 v; asm volatile("ld.shared.v4.u32 {%0,%1,%2,%3}, [%4];" : "=r"(v.x), "=r"(v.y), "=r"(v.z), "=r"(v.w) : "r"(a) : "memory"); return v; }
__device__ __forceinline__ void sts128(uint32_t a, uint4 v) { asm volatile("st.shared.v4.u32 [%0], {%1,%2,%3,%4};" ::"r"(a), "r"(v.x), "r"(v.y), "r"(v.z), "r"(v.w) : "memory"); }
__device__ __forceinline__ int lds32(uint32_t a) { int v; asm volatile("ld.shared.u32 %0, [%1];" : "=r"(v) : "r"(a) : "memory"); return v; }
__device__ __forceinline__ void sts32(uint32_t a, int v) { asm volatile("st.shared.u32 [%0], %1;" ::"r"(a), "r"(v) : "memory"); }
__device__ __forceinline__ int atoms_add(uint32_t a, int v) { int r; asm volatile("atom.shared.add.u32 %0, [%1], %2;" : "=r"(r) : "r"(a), "r"(v) : "memory"); return r; }
__device__ __forceinline__ uint32_t ld_rlx(const void* p) { uint32_t v; asm volatile("ld.relaxed.gpu.global.u32 %0, [%1];" : "=r"(v) : "l"(p) : "memory"); return v; }
__device__ __forceinline__ void st_rlx(void* p, uint32_t v) { asm volatile("st.relaxed.gpu.global.u32 [%0], %1;" ::"l"(p), "r"(v) : "memory"); }
__device__ __forceinline__ void bulk(uint32_t dst, const void* g, int n, uint32_t bar) {
    asm volatile("cp.async.bulk.shared::cluster.global.mbarrier::complete_tx::bytes [%0], [%1], %2, [%3];" ::"r"(dst), "l"(g), "r"(n), "r"(bar) : "memory");
}
__device__ __forceinline__ void bulk_st(void* g, uint32_t src, int n) {
    asm volatile("cp.async.bulk.global.shared::cta.bulk_group [%0], [%1], %2;\ncp.async.bulk.commit_group;" ::"l"(g), "r"(src), "r"(n) : "memory");
}
__device__ __forceinline__ uint2 lds64(uint32_t a) { uint2 v; asm volatile("ld.shared.v2.u32 {%0,%1}, [%2];" : "=r"(v.x), "=r"(v.y) : "r"(a) : "memory"); return v; }
__device__ __forceinline__ void sts64(uint32_t a, uint32_t x, uint32_t y) { asm volatile("st.shared.v2.u32 [%0], {%1,%2};" ::"r"(a), "r"(x), "r"(y) : "memory"); }
__device__ __forceinline__ void tma3d(uint32_t dst, const CUtensorMap* m, int c1, int c2, uint32_t bar) {
    asm volatile("cp.async.bulk.tensor.3d.shared::cluster.global.mbarrier::complete_tx::bytes [%0], [%1, {0, %3, %4}], [%2];"
                 ::"r"(dst), "l"(m), "r"(bar), "r"(c1), "r"(c2) : "memory");
}
__device__ __forceinline__ void fence_async() { asm volatile("fence.proxy.async.shared::cta;" ::: "memory"); }
__device__ __forceinline__ uint64_t madw(uint32_t a, uint32_t b, uint64_t c) { uint64_t r; asm("mad.wide.u32 %0, %1, %2, %3;" : "=l"(r) : "r"(a), "r"(b), "l"(c)); return r; }
__device__ __forceinline__ uint32_t lop_sel(uint32_t a, uint32_t b, uint32_t m) { uint32_t r; asm("lop3.b32 %0, %1, %2, %3, 0xd8;" : "=r"(r) : "r"(a), "r"(b), "r"(m)); return r; }
__device__ __forceinline__ uint32_t opaque(uint32_t v, int lane) { return __shfl_sync(0xffffffffu, v, lane); }
__device__ __forceinline__ void bar_sync(int id, int n) { asm volatile("bar.sync %0, %1;" ::"r"(id), "r"(n) : "memory"); }

__device__ __forceinline__ void wg_rs16(float* d, const uint32_t* a, uint64_t db, int sc) {
    asm volatile("{.reg .pred p; setp.ne.b32 p, %13, 0;\n"
                 "wgmma.mma_async.sync.aligned.m64n16k16.f32.bf16.bf16 {%0,%1,%2,%3,%4,%5,%6,%7}, {%8,%9,%10,%11}, %12, p, 1, 1, 0;}"
                 : "+f"(d[0]), "+f"(d[1]), "+f"(d[2]), "+f"(d[3]), "+f"(d[4]), "+f"(d[5]), "+f"(d[6]), "+f"(d[7])
                 : "r"(a[0]), "r"(a[1]), "r"(a[2]), "r"(a[3]), "l"(db), "r"(sc));
}
__device__ __forceinline__ void wg_rs48(float* d, const uint32_t* a, uint64_t db, int sc) {
    asm volatile("{.reg .pred p; setp.ne.b32 p, %29, 0;\n"
                 "wgmma.mma_async.sync.aligned.m64n48k16.f32.bf16.bf16 {%0,%1,%2,%3,%4,%5,%6,%7,%8,%9,%10,%11,%12,%13,%14,%15,%16,%17,%18,%19,%20,%21,%22,%23}, {%24,%25,%26,%27}, %28, p, 1, 1, 0;}"
                 : "+f"(d[0]), "+f"(d[1]), "+f"(d[2]), "+f"(d[3]), "+f"(d[4]), "+f"(d[5]), "+f"(d[6]), "+f"(d[7]),
                   "+f"(d[8]), "+f"(d[9]), "+f"(d[10]), "+f"(d[11]), "+f"(d[12]), "+f"(d[13]), "+f"(d[14]), "+f"(d[15]),
                   "+f"(d[16]), "+f"(d[17]), "+f"(d[18]), "+f"(d[19]), "+f"(d[20]), "+f"(d[21]), "+f"(d[22]), "+f"(d[23])
                 : "r"(a[0]), "r"(a[1]), "r"(a[2]), "r"(a[3]), "l"(db), "r"(sc));
}
__device__ __forceinline__ void wg_ss48(float* d, uint64_t da, uint64_t db, int sc) {
    asm volatile("{.reg .pred p; setp.ne.b32 p, %26, 0;\n"
                 "wgmma.mma_async.sync.aligned.m64n48k16.f32.bf16.bf16 {%0,%1,%2,%3,%4,%5,%6,%7,%8,%9,%10,%11,%12,%13,%14,%15,%16,%17,%18,%19,%20,%21,%22,%23}, %24, %25, p, 1, 1, 1, 0;}"
                 : "+f"(d[0]), "+f"(d[1]), "+f"(d[2]), "+f"(d[3]), "+f"(d[4]), "+f"(d[5]), "+f"(d[6]), "+f"(d[7]),
                   "+f"(d[8]), "+f"(d[9]), "+f"(d[10]), "+f"(d[11]), "+f"(d[12]), "+f"(d[13]), "+f"(d[14]), "+f"(d[15]),
                   "+f"(d[16]), "+f"(d[17]), "+f"(d[18]), "+f"(d[19]), "+f"(d[20]), "+f"(d[21]), "+f"(d[22]), "+f"(d[23])
                 : "l"(da), "l"(db), "r"(sc));
}

__device__ __forceinline__ int warp_incl(int v) {
#pragma unroll
    for (int o = 1; o < 32; o <<= 1)
        asm volatile("{.reg .pred p; .reg .b32 u; shfl.sync.up.b32 u|p, %0, %1, 0, 0xffffffff; @p add.s32 %0, %0, u;}" : "+r"(v) : "r"(o));
    return v;
}
__device__ __forceinline__ void ldg128(uint32_t* r, const void* p, bool on) {
    asm volatile("{.reg .pred p; setp.ne.u32 p, %5, 0; @p ld.global.nc.v4.u32 {%0,%1,%2,%3}, [%4];}"
                 : "=r"(r[0]), "=r"(r[1]), "=r"(r[2]), "=r"(r[3]) : "l"(p), "r"((uint32_t)on));
}

template <int V> struct IC { static constexpr int value = V; };
template <int N, int I = 0, class Fn> __device__ __forceinline__ void static_for(Fn f) { if constexpr (I < N) { f(IC<I>{}); static_for<N, I + 1>(f); } }

struct Acc {
    uint32_t p[10];
    float t01[4], m[3][4];
};

#define LF(m) if (H) ldsm2t(f[m], so + xa + m * 256); else ldsm4t(f[m], so + xa + m * 256)
#define LY() ldsm4(yb, so + ya)
#define LC() ldsm4(yb + 4, so + yc)
#define LN() ph = lds32(so + S_N)
#define ADV() { if (F) asm volatile("{.reg .pred p; setp.ne.and.u32 p, %1, 0, lane0; @p mbarrier.arrive.shared::cta.b64 _, [%0];}" ::"r"(so + S_EMPTY), "r"(room) : "memory"); \
                else asm volatile("@lane0 mbarrier.arrive.shared::cta.b64 _, [%0];" ::"r"(so + S_EMPTY) : "memory"); \
                so = so == sm + O_RING + (NSLOT - 1) * SLOT ? sm + O_RING : so + SLOT; }
#define LA() asm volatile("{\n.reg .pred p, q;\n.reg .b64 s;\n.reg .f32 n;\nmov.b64 s, {0, %7};\nmbarrier.test_wait.shared::cta.b64 p, [%6], s;\n" \
                          "abs.f32 n, %7;\nsetp.gt.and.f32 q, n, 0f00000003, p;\nselp.u32 %4, 1, 0, p;\nselp.u32 %5, 1, 0, q;\n" \
                          "@p ldmatrix.sync.aligned.m8n8.x4.shared.b16 {%0,%1,%2,%3}, [%8];\n}" \
                          : "+r"(a[0]), "+r"(a[1]), "+r"(a[2]), "+r"(a[3]), "=r"(ok), "=r"(go) : "r"(so + S_FULL), "r"(ph), "r"(so + aa) : "memory")
#define RAD(p, s) if (!H || !s) { float c[4]; mma16z(c, wr[p], a[2 * s], a[2 * s + 1]); R[p][2 * s] = pack(c[0], c[1]); R[p][2 * s + 1] = pack(c[2], c[3]); }
#define MUL(n, x, y) (XS >> n & 1 ? hmul(y, x) : hmul(x, y))
#define FMA(n, x, y, z) (XS >> n & 1 ? hfma(y, x, z) : hfma(x, y, z))
#define ON(i) if (!H || i < 2)
#define ACC(n, m, i, x, y) ON(i) { constexpr int c = 2 * m + ((i ^ XA) & 1); A.p[c] = F && !(seen >> c & 1) ? MUL(n, x, y) : FMA(n, x, y, A.p[c]); seen |= 1 << c; }
#define P00(i) ACC(0, 3, i, f[0][i], R[0][i])
#define P10(k, i) ACC(1, k, i, f[1 + k][i], R[3][i])
#define S0(k, i) ON(i) sd[i] = MUL(2, f[1 + k][i], yb[2 * k + (i >> 1)])
#define SD(k, i) ON(i) sd[i] = FMA(2, f[1 + k][i], yb[2 * k + (i >> 1)], sd[i])
#define P110(i) ACC(3, 4, i, sd[i], R[1][i])
#define TU(i) ON(i) u[3][i ^ XU] = MUL(4, f[0][i], R[2][i])
#define EM(d, u) if (F) mma16z(d, u, yb[6], yb[7]); else if (H) mma8(d, u[0], u[1], yb[6]); else mma16(d, u, yb[6], yb[7])
#define TM() EM(A.t01, u[3])
#define MU(k, i) ON(i) u[k][i ^ XU] = MUL(5, f[1 + k][i], R[4][i])
#define MM(k) EM(A.m[k], u[k])
#define PK(v, h) pack(v[2 * (h)], v[2 * (h) + 1])
#define LM() { sts32(na + (sof + sm + O_NODE), mt); asm volatile("ld.shared.u16 %0, [%1];" : "=r"(mt) : "r"(na + (so + S_C + 48)) : "memory"); }
#define MP(k) PK(A.m[k], XA ^ XU), PK(A.m[k], 1 ^ XA ^ XU)
#define FY(k) if (k == 0) mma16z(y, A.p, oh[0], oh[1]); else if (k > 1 && !(seen >> 30)) { mma16(y, A.p + 4, oh[2], oh[3]); seen |= 1 << 30; }
#define FZ(k) if (k == 0) { const uint32_t mp[4] = {A.p[8], A.p[9], MP(2)}; mma16z(z, mp, oh[4], eb[2]); } \
              else if (k == 1) { const uint32_t mp[4] = {MP(0), MP(1)}; mma16(z, mp, eb[0], eb[1]); }
#define SX() stsm2t(fx + sof, PK(A.t01, XU), PK(A.t01, 1 ^ XU))
#define SY() stsm4t(fyz + sof, PK(y, XA), PK(y, 1 ^ XA), PK(z, XA), PK(z, 1 ^ XA))
#define G0(k) wg_rs16(d0, w0[k], db + ((((k) & 7) * PW + (((k) >> 3) ? P_0P1 : P_0P0)) >> 4), k)
#define G1(i) { constexpr int k_ = ((i) + KR) % 24; const uint64_t bk = db + (((k_ & 7) * PW + ((k_ >> 3) == 0 ? P_1P0 : (k_ >> 3) == 1 ? P_1P1 : P_1P2)) >> 4); \
                if (k_ < KR) wg_rs48(d1, w1[k_ % KR], bk, i); else wg_ss48(d1, (da + (k_ - KR) * 256) | (64ull << 32) | (1ull << 62), bk, i); }
#define XA 1
#define XU 0
#define XS_R 63
#define SEQ_R LF(2); LN(); RAD(1,0); RAD(1,1); LC(); LY(); RAD(2,0); RAD(2,1); RAD(4,0); RAD(4,1); RAD(3,0); RAD(3,1); LF(0); P10(1,1); P10(1,0); \
    P10(1,3); P10(1,2); LF(3); MU(2,3); S0(2,3); S0(2,2); S0(2,1); S0(2,0); RAD(0,1); RAD(0,0); MU(2,2); P00(2); MU(2,1); MU(1,3); MU(2,0); MM(2); P00(3); \
    MU(1,2); LF(1); ADV(); LA(); P10(0,0); P10(0,1); P10(0,2); P10(0,3); SD(0,0); SD(0,2); SD(0,1); SD(0,3); SD(1,0); P110(0); SD(1,2); P110(2); SD(1,1); \
    P110(1); SD(1,3); P110(3); P00(0); MU(0,0); TU(0); P10(2,0); TU(2); MU(1,1); TU(3); TU(1); TM(); P10(2,2); P00(1); MU(0,2); P10(2,1); MU(1,0); MM(1); \
    P10(2,3); MU(0,1); MU(0,3); MM(0);
#define XS_H XS_R
#define SEQ_H SEQ_R
#define XS_F 63
#define SEQ_F LY(); LF(2); LF(0); SX(); FZ(0); FY(0); FY(2); RAD(1,0); LM(); RAD(0,1); RAD(2,1); RAD(3,0); RAD(3,1); RAD(2,0); LC(); RAD(0,0); \
    RAD(4,0); LN(); FZ(2); LF(1); LF(3); ADV(); FY(1); RAD(4,1); RAD(1,1); LA(); TU(1); TU(0); TU(3); TU(2); P10(0,0); P10(0,2); P10(2,3); P10(0,1); \
    P10(2,2); TM(); P10(0,3); FY(3); P10(2,1); P10(1,0); P10(2,0); P10(1,1); P10(1,2); S0(0,1); SD(2,1); SD(1,1); P110(1); S0(0,0); S0(0,3); S0(0,2); \
    SD(2,0); SD(1,0); P110(0); FZ(1); SY(); P10(1,3); MU(0,1); MU(0,0); MU(0,3); MU(0,2); SD(2,3); SD(1,3); P110(3); MU(2,2); MU(2,3); MU(2,0); MU(2,1); \
    MM(2); P00(2); SD(2,2); SD(1,2); P110(2); MU(1,0); P00(3); MU(1,2); MU(1,3); MU(1,1); MM(1); P00(0); P00(1); MM(0);

__global__ void __launch_bounds__(NT, 1)
tp_kernel(const int4* __restrict__ dst, const int4* __restrict__ src, const char* __restrict__ rhat, Scratch* __restrict__ gs,
          const char* __restrict__ x, const char* __restrict__ ea, const __nv_bfloat16* __restrict__ eps, char* __restrict__ out,
          const __grid_constant__ CUtensorMap m_wr, const __grid_constant__ CUtensorMap m_w0, const __grid_constant__ CUtensorMap m_w1,
          const __grid_constant__ CUtensorMap m_x) {
    extern __shared__ __align__(1024) char smem_raw[];
    constexpr uint32_t sm = 1024;
    spin_check((uint32_t)__cvta_generic_to_shared(smem_raw) == sm ? 0 : 2 * SPIN_LIMIT);
    int t;
    asm volatile("mov.u32 %0, %%tid.x;" : "=r"(t));
    const int w = t >> 5, lane = t & 31, b = blockIdx.x;

    const int g = lane >> 2, q = lane & 3, mat = lane >> 3, r = lane & 7;
    const int e0 = b * CH + t * 8, ne = min(CH, NE - b * CH);
    const bool act = t * 8 < ne;
    uint32_t d[8];
#pragma unroll
    for (int k = 0; k < 2; k++) ldg128(d + 4 * k, dst + e0 / 4 + k, act);
    uint32_t tag = ld_rlx(&gs->epoch[b * 32]), epl;
    asm volatile("ld.global.nc.u16 %0, [%1];" : "=r"(epl) : "l"(eps + min(lane, 26)));
    if (t < 60) sts128(sm + O_BCNT + 16 * t, make_uint4(0, 0, 0, 0));
    if (t == NT - 1) {
#pragma unroll
        for (int i = 0; i < 5; i++) mbar_init(sm + O_WBA + 8 * i, 1);
        fence_async();
        mbar_expect(sm + O_WBC, ne * 10); mbar_expect(sm + O_WBA, 20480); mbar_expect(sm + O_WBB, (24 - KR) * 4096); mbar_expect(sm + O_WBD, 65536 + KR * 4096);
        mbar_expect(sm + O_WBE, (((TP & 15) != 15) + ((TP >> 4 & 15) != 15) + ((TP >> 8 & 15) != 15) + ((TP >> 12) != 15)) * (NLOC / 4 * 128));
        WLD(6);
        spin_check(tag);
        bulk(sm + O_RH, rhat + b * (CH * 6), ne * 6, sm + O_WBC);
        bulk(sm + O_SRC, src + b * (CH / 4), ne * 4, sm + O_WBC);
        tma3d(sm + O_WR0, &m_wr, 0, 0, sm + O_WBA);
        tma3d(sm + O_WR1, &m_wr, 0, 5, sm + O_WBA);
        WLD(0);
    }
    if (t == 320) {
#pragma unroll
        for (int i = 0; i < NSLOT; i++) {
            sts128(sm + O_RING + i * SLOT + S_C + 64, make_uint4(0, 0, 0, 0));
            mbar_init(sm + O_RING + i * SLOT + S_FULL, 32); mbar_init(sm + O_RING + i * SLOT + S_EMPTY, 8);
        }
    }
#pragma unroll
    for (int k = 0; k < LZ; k++) sts128(sm + O_L + 16 * (t + k * NT), make_uint4(0, 0, 0, 0));
    if (t < 80) sts32(sm + O_NCNT + 4 * t, t <= NLOC ? 4 * t : 0);
    if (t < 68) sts32(sm + O_NODE + 4 * t, 0);
    uint32_t ba[8], rk[8];
    if (w < 10) bar_sync(1, 320);
    tag = (tag + 1) << 30;
    if (act) {
#pragma unroll
        for (int i = 0; i < 8; i++) {
            const uint32_t l = __umulhi(d[i], (uint32_t)((1ull << 32) / G + 1));
            ba[i] = d[i] * 4 - l * (4 * G);
            d[i] = l * 4 + (tag + ((e0 + i + 1) << 9) + 4);
            rk[i] = atoms_add(sm + O_BCNT + ba[i], 4);
        }
#pragma unroll
        for (int i = 0; i < 8; i++)
            asm volatile("{.reg .pred p; setp.lt.u32 p, %2, 124; @p st.shared.u32 [%0], %1;}"
                         ::"r"(sm + O_KT + ba[i] * 32 + ((ba[i] + rk[i]) & 127)), "r"(d[i]), "r"(rk[i]) : "memory");
    }
    TS(0);
    __syncthreads();
    {
        int v[5], sum = 0;
#pragma unroll
        for (int i = 0; i < 5; i++) { v[i] = lds32(sm + O_BCNT + 4 * (lane * 5 + i)); sum += v[i]; }
        int e = warp_incl(sum) - sum;
        if (w == 10) {
#pragma unroll
            for (int i = 0; i < 5; i++) {
                const int k = lane * 5 + i;
                if (k < G) sts32(sm + O_KT + k * 128 + ((k * 4 + 124) & 127), tag | v[i] << 10 | e >> 2);
                e += v[i];
            }
            __syncwarp();
            if (lane == 0) {
                fence_async();
                bulk_st(&gs->keys[b * (G * 32)], sm + O_KT, G * 128);
                WLD(5);
            }
        } else {
#pragma unroll
            for (int i = 0; i < 5; i++) { sts32(sm + O_BOFF + 4 * (lane * 5 + i), e); e += v[i]; }
        }
        __syncwarp();
    }
    TS(11);
    const uint32_t sw = (uint32_t)(((2 * (w & 3) + (mat & 1)) ^ r) * 16 + ((mat >> 1) * 8 + r) * 128);
    const uint32_t lo = (lane & 2) * 64 + (lane & 12) * 8 + (lane & 16) + (lane & 1) * 8;
    uint32_t wr[5][4];
    const uint32_t* kp = &gs->keys[(w * SEGW * G + b) * 32 + ((lane + b) & 31)];
    uint32_t kv[SEGW + 1], ho[SEGW + 1], nk[SEGW + 1], old;
    if (act) {
        uint32_t mx = 0;
#pragma unroll
        for (int i = 0; i < 8; i++) { mx = max(mx, rk[i]); ba[i] = rk[i] + lds32(sm + O_BOFF + ba[i]); }
        if (mx >= 124) {
#pragma unroll
            for (int i = 0; i < 8; i++)
                if (rk[i] >= 124) st_rlx(&gs->more[b * CH + (ba[i] >> 2)], d[i]);
        }
    }
    if (w < 8) {
        mbar_wait(sm + O_WBA, 0);
#pragma unroll
        for (int p = 0; p < 5; p++) {
            const int c = 2 * p + (w >> 2);
            ldsm4t(wr[p], sm + (c < 5 ? O_WR0 : O_WR1 - 5 * 2048) + c * 2048 + sw);
        }
    } else {
        const uint64_t xl = (uint64_t)(x - 1024 + (r ^ 2 * mat) * 16) - (tag >> 6), al = (uint64_t)(ea - 32 + (lane & 1) * 16) - (tag >> 4);
        const uint64_t ml = (uint64_t)gs->list + lo;
        const uint32_t row = ((mat & 2 ? mat & 1 ? 0xa9c876b5u : 0xfe4d2130u : mat & 1 ? 0xfed8c1a3u : 0x76c521b0u) >> 4 * r & 15) + (mat & 2) * 8;
        const uint32_t c[16] = {(uint32_t)xl, (uint32_t)(xl >> 32), (uint32_t)al, (uint32_t)(al >> 32), (uint32_t)ml, (uint32_t)(ml >> 32),
            mat * 2048u + r * 16, (uint32_t)xl ^ 16,
            S_A + (lane & 2) * 128u + g * 32 + ((lane ^ lane >> 4) & 1) * 16, S_C + row * 16, lane & 1 ? 16u : 9u, lane & 30u,
            lane == 4 ? 0xffff0000u : 0u, lane & 1 ? ~0u : 0u, lane < 16 ? ~0u : 0u, lane ? 0u : 0x20000u};
#pragma unroll
        for (int i = 0; i < 20; i++) wr[i >> 2][i & 3] = i < 16 ? opaque(c[i % 16], lane) : 0;
    }
    TS(21);
    mbar_wait(sm + O_WBC, 0);
    TS(22);
    if (act) {
        uint32_t s[8], y[12];
#pragma unroll
        for (int k = 0; k < 3; k++) *(uint4*)&y[4 * k] = lds128(sm + O_RH + t * 48 + k * 16);
#pragma unroll
        for (int k = 0; k < 2; k++) *(uint4*)&s[4 * k] = lds128(sm + O_SRC + t * 32 + k * 16);
#pragma unroll
        for (int i = 0; i < 8; i++) {
            const int k = 3 * i / 2;
            sts64(sm + O_OUT + ba[i] * 2, __byte_perm(y[k], s[i] + (tag >> 16) + 1, i & 1 ? 0x5432 : 0x5410),
                  i & 1 ? y[k + 1] : __byte_perm(y[k], y[k + 1], 0x5432));
        }
    }
    TS(12);
    __syncthreads();
    if (t == 352) { fence_async(); bulk_st(&gs->vals[b * CH], sm + O_OUT, ne * 8); WLD(7); }

    const uint32_t am = lane < 31 ? 511 : 0, none = tag | (320 + 4 * lane);
    auto check = [&]() {
        old = 0;
#pragma unroll
        for (int j = 0; j < SEGW; j++) {
            ho[j] = __shfl_sync(0xffffffffu, kv[j], 31);
            kv[j] = ho[j] >= (lane < 31 ? tag + ((lane + 1) << 12) : 0u) ? kv[j] : none;
            old |= kv[j] ^ tag;
        }
        return __any_sync(0xffffffffu, old >> 30);
    };
#pragma unroll
    for (int j = 0; j < SEGW; j++) kv[j] = ld_rlx(kp + j * (G * 32));
    TS(1);
    if (t == 352) WLD(1);
    TV(19, 0); TV(23, 0);
    for (int it = 0; check(); it++) {
        spin_check(it);
        if (it == 0) TS(20);
        TV(19, (it + 1) * 100);
#pragma unroll
        for (int j = 0; j < SEGW; j++)
            if (__any_sync(0xffffffffu, (kv[j] ^ tag) >> 30)) kv[j] = ld_rlx(kp + j * (G * 32));
    }
    TS(3);
    if (t == 352) WLD(2);
    kv[SEGW] = none; ho[SEGW] = 0;
    bool slow = false;
    const bool more = __any_sync(0xffffffffu, lane == 31 && (old & 0xfe0000));
    if (more) {
        int c = lane;
#pragma unroll
        for (int j = 0; j < SEGW; j++) {
            const int n = max((int)(ho[j] >> 12 & 0xfff) - 31, 0);
            if ((unsigned)c < (unsigned)n) ho[SEGW] = j * CH + (ho[j] & 0xfff) + 31 + c - lane;
            c -= n;
        }
        slow = lane == 31 && c < 0;
        if (c < 0 && lane < 31)
            for (int it = 0; ((kv[SEGW] = ld_rlx(&gs->more[w * SEGW * CH + lane + ho[SEGW]])) ^ tag) >> 30; it++) spin_check(it);
        __syncwarp();
    }
    uint32_t na_[SEGW + 1];
    uint64_t vp = (uint64_t)&gs->vals[w * SEGW * CH + lane], vv[SEGW + 1];
#pragma unroll
    for (int j = 0; j <= SEGW; j++) vv[j] = tag;
    auto ldv = [&](bool again) {
#pragma unroll
        for (int j = 0; j <= SEGW; j++)
            asm volatile("{.reg .pred p; setp.lt.u32 p, %2, 320; @p ld.relaxed.gpu.global.b64 %0, [%1];}" : "+l"(vv[j])
                         : "l"(madw(j < SEGW ? ho[j] & 0xfff : ho[j], 8, vp) + (j < SEGW ? j * CH * 8 : 0)),
                           "r"(again ? (((uint32_t)vv[j] ^ tag) >> 30 ? 0 : 320) : na_[j]) : "memory");
    };
#pragma unroll
    for (int j = 0; j <= SEGW; j++) na_[j] = (kv[j] & am) | (none & 511 & ~am);
#pragma unroll
    for (int j = 0; j <= SEGW; j++) nk[j] = atoms_add(sm + O_NCNT + na_[j], 512);
    auto visit = [&](auto f) {
#pragma unroll 1
        for (int j = 0; j < SEGW; j++) {
            const uint32_t* kl = &gs->keys[((w * SEGW + j) * G + b) * 32];
            const uint32_t h = ld_rlx(kl + ((31 + b) & 31));
#pragma unroll 1
            for (int i = lane; i < (h >> 12 & 0xfff); i += 32) {
                const int o = (w * SEGW + j) * CH + (h & 0xfff) + i;
                uint32_t k;
                int it = 0;
                do { k = ld_rlx(i < 31 ? kl + ((i + b) & 31) : &gs->more[o]); spin_check(it++); } while ((k ^ tag) >> 30);
                f(k, o, i);
            }
        }
    };
    slow = __syncthreads_or(slow);
    if (slow) {
        if (t < 80) sts32(sm + O_NCNT + 4 * t, t <= NLOC ? 4 * t : 0);
        __syncthreads();
        visit([&](uint32_t k, int, int) { atoms_add(sm + O_NCNT + (k & 511), 512); });
        __syncthreads();
    }
    TS(4);
    if (t == 352) WLD(3);
    if (w < 10) {
        const uint32_t key = lds32(sm + O_NCNT + 4 + (t & ~3));
        uint4 k[5];
#pragma unroll
        for (int i = 0; i < 5; i++) k[i] = lds128(sm + O_NCNT + q * 80 + i * 16);
        uint32_t c[4] = {0, 0, 0, 0};
#pragma unroll
        for (int i = 0; i < 5; i++) { c[0] += (key - k[i].x) >> 31; c[1] += (key - k[i].y) >> 31; c[2] += (key - k[i].z) >> 31; c[3] += (key - k[i].w) >> 31; }
        int rank = c[0] + c[1] + c[2] + c[3];
        rank += __shfl_xor_sync(0xffffffffu, rank, 1);
        rank += __shfl_xor_sync(0xffffffffu, rank, 2);
        if ((b & 1) && rank < 2 * NPRIV) rank = (2 * NPRIV - 1 - rank) ^ 1;
        if (t < NLOC * 4) sts32(sm + O_SORT + 4 * rank, key);
    }
    __syncthreads();
    TS(2);
    const bool on = lane < NLOC / 4;
    const uint4 k4 = lds128(sm + O_SORT + 16 * (on ? lane : 0));
    const uint32_t ks[4] = {k4.x, k4.y, k4.z, k4.w};
    const int n0 = on ? max(1u, (ks[0] + 3584) >> 12) : 0, n1 = on ? max(1u, (ks[2] + 3584) >> 12) : 0;
    const int u2 = warp_incl(n0 + n1), u1 = u2 - n1, u0 = u1 - n0;
    const int total = __shfl_sync(0xffffffffu, u2, 31);
    slow |= total > CAPT;
    const int m0 = slow ? n0 : max(2u, (ks[0] + 1536) >> 11), m1 = slow ? n1 : max(2u, (ks[2] + 1536) >> 11);
    int gbase = b * CAPT + 1;
    if (on) {
#pragma unroll
        for (int i = 0; i < 4; i++) {
            const int a = ks[i] & 511, node = a * (G / 4) - G + b, o = (i >> 1 ? u1 : u0) * 256 + (i & 1) * 16;
            const uint32_t mk = (node < NN ? node + 1 : 0) + ((i >> 1 ? m1 : m0) << 16);
            sts64(sm + O_NOFF + 2 * a, o - (a >> 4), mk + a * 32);
            if (!slow && ks[i] < 512) sts32(sm + O_L + 4 + o, mk);
        }
    }
    __syncwarp();
    if (t == 352) WLD(8);
    if (!slow) {
        uint32_t mk[SEGW + 1];
        TS(13);
        if (t == 352) { asm volatile("cp.async.bulk.wait_group.read 0;" ::: "memory"); }
        ldv(false);
        if (t == 352) WLD(4);
        TS(16);
#pragma unroll
        for (int j = 0; j <= SEGW; j++) {
            const uint2 o = lds64(sm + O_NOFF + 2 * na_[j]);
            mk[j] = o.y - nk[j] * 32; nk[j] = o.x + (nk[j] >> 4);
        }
        for (int it = 0;; it++) {
            old = 0;
#pragma unroll
            for (int j = 0; j <= SEGW; j++) old |= (uint32_t)vv[j] ^ tag;
            if (!__any_sync(0xffffffffu, old >> 30)) break;
            spin_check(it);
            vp = __shfl_sync(0xffffffffu, vp, lane);
            ldv(true);
            TV(23, (it + 1) * 100);
        }
        TS(17);
#pragma unroll
        for (int j = 0; j <= SEGW; j++)
            asm volatile("{.reg .pred p; setp.ne.u32 p, %3, %5; @p st.shared.v4.u32 [%0], {%1,%2,%3,%4};}"
                         ::"r"(sm + O_L + nk[j]), "r"(kv[j]), "r"(mk[j]), "r"((uint32_t)vv[j]), "r"((uint32_t)(vv[j] >> 32)), "r"(tag) : "memory");
        TS(18);
        if (na_[SEGW] < 320) gs->more[w * SEGW * CH + lane + ho[SEGW]] = 0;
    } else {
        int so = 0;
        if (t == 352) WLD(4);
#pragma unroll
        for (int j = 0; j < SEGW; j++) so += ho[j] & 0xfff;
        if (lane == 0) atoms_add(sm + O_SUM, so);
        if (t == 352) asm volatile("cp.async.bulk.wait_group.read 0;" ::: "memory");
        __syncthreads();
        gbase = TBIG + (lds32(sm + O_SUM) >> 3) + (NLOC + 5) * b;
        auto put = [&](uint32_t k, uint64_t e, uint32_t a, int rank) {
            const uint2 o = lds64(sm + O_NOFF + 2 * a);
            const uint32_t m = o.y - a * 32 - (rank << 13);
            gs->list[gbase * 16 + ((o.x + (a >> 4)) >> 4) + rank * 2] = make_uint4(k, (m & 0xffff) | min(m >> 16, 0x7fffu) << 17, e, e >> 32);
        };
        visit([&](uint32_t k, int o, int i) {
            uint64_t e;
            int it = 0;
            do {
                asm volatile("ld.relaxed.gpu.global.b64 %0, [%1];" : "=l"(e) : "l"(&gs->vals[o]) : "memory");
                spin_check(it++);
            } while (((uint32_t)e ^ tag) >> 30);
            if (i >= 31) gs->more[o] = 0;
            put(k, e, k & 511, atoms_add(sm + O_NCUR + (k & 511), 1));
        });
#pragma unroll 1
        for (int i = 0; i < 4; i++) {
            const uint32_t k = i == 0 ? ks[0] : i == 1 ? ks[1] : i == 2 ? ks[2] : ks[3];
#pragma unroll 1
            for (int p = (k >> 9) + w; p < (i >> 1 ? n1 : n0) * 8; p += NT / 32) put(0, 0, k & 511, p);
        }
        __threadfence();
    }
    if (t == 352) WLD(9);
    const uint32_t iw0 = (gbase + u0) << 12 | n0, iw1 = (gbase + u1) << 12 | n1;
    __syncthreads();
    TS(5);

    if (w >= 8) {
        asm volatile("setmaxnreg.dec.sync.aligned.u32 56;");
        const int h = __reduce_max_sync(0xffffffffu, w & 3);
        if (h == 0) TSW(28);
        gbase = __reduce_min_sync(0xffffffffu, iw0) >> 12;
        int pos = gbase + h, end = __reduce_max_sync(0xffffffffu, lane == NPRIV / 2 ? (NPRIV & 1 ? iw1 : iw0) : 0) >> 12;
        const int bytes = gbase < TBIG ? ((__reduce_max_sync(0xffffffffu, iw0) >> 12) - gbase) * 256 : 0;
        const uint32_t ring = sm + O_RING;
        const uint64_t xl[2] = {wr[0][0] | (uint64_t)wr[0][1] << 32, wr[1][3] | (uint64_t)wr[0][1] << 32};
        const uint64_t al = wr[0][2] | (uint64_t)wr[0][3] << 32, ml = wr[1][0] | (uint64_t)wr[1][1] << 32;
        const uint32_t xoff = wr[1][2], aoff = wr[2][0], coff = wr[2][1], sh = wr[2][2], ial = wr[2][3], sel = wr[3][0];
        const uint32_t odd = wr[3][1], low = wr[3][2], lim = wr[3][3];
        auto lde = [&](uint2& e, int p) {
            asm volatile("{.reg .pred p; setp.gt.s32 p, %3, 0; @p ld.relaxed.gpu.global.v2.u32 {%0,%1}, [%2];}" : "+r"(e.x), "+r"(e.y) : "l"(madw(p, 256, ml)), "r"(p) : "memory");
        };
        uint2 e0[3] = {};
#pragma unroll
        for (int k = 0; k < 3; k++) {
            e0[k] = lds64(sm + O_L + k * 1024 + h * 256 + ((uint32_t)ml & 255));
            lde(e0[k], bytes ? 0 : pos + 4 * k);
        }
        if (h == 3) fence_async();
        else asm volatile("bar.arrive 4, %0;" ::"n"(NT) : "memory");
        pos += 4;

        int ev = 0, state = -2, tk = 0, nr = 0;
        uint32_t inf = 0;
        int ii = 0;
        auto take = [&]() {
            int v = 0;
            asm volatile("{.reg .pred p; setp.eq.s32 p, %2, 0; @p atom.relaxed.gpu.global.add.u32 %0, [%1], 1;}" : "+r"(v) : "l"(&gs->ticket), "r"(lane) : "memory");
            return v;
        };
        auto resolve = [&]() {
            const int k = __reduce_max_sync(0xffffffffu, tk);
            inf = tag;
            if (k < G * NPOOL) { const int l = k / G; ii = (k - l * G) * NPOOL + l; inf = ld_rlx(&gs->info[ii]);
                const int j = NPRIV + 1 + nr + (b & 7), gd = __reduce_max_sync(0xffffffffu, lds32(sm + O_SUM + 4));
                tk = (b & 7) && (j & ~7) > gd && k >= G * NPOOL - (j & 7 ? G : 5 * G / 3) ? G * NPOOL : take(); }
        };
        uint32_t so = ring + h * SLOT, ph = 0x80000000u;
        uint32_t spins = 0;
        asm volatile(".reg .pred z<5>;");
        { const uint32_t c0 = clock(); while (__any_sync(0xffffffffu, (uint32_t)clock() - c0 < h * 300)); }
        while (true) {
            const uint2 e = e0[0];
            const uint32_t o = e.x >> sh, id = __shfl_sync(0xffffffffu, o, ial);
            uint32_t s[4];
#pragma unroll
            for (int j = 0; j < 4; j++) s[j] = __shfl_sync(0xffffffffu, o, 2 * j + 1, 8);
            const uint32_t nx = so == ring + (NSLOT - 1) * SLOT ? ph : ph ^ 0x80000000u, ey = lop_sel(e.y, nx, sel);
            const uint32_t ym = lop_sel(__shfl_xor_sync(0xffffffffu, e.x, 1), e.y, odd);
            const bool full = __all_sync(0xffffffffu, e.y >= lim);
            const uint64_t ga = madw(id, 32, al);
            uint64_t gx[4];
#pragma unroll
            for (int j = 0; j < 4; j++) gx[j] = madw(s[j], 1024, xl[j >> 1]);
            const uint32_t da = so + aoff, dx = so + xoff, dc = so + coff;
            asm volatile("setp.eq.u32 z0, %0, 0;\nsetp.eq.u32 z1, %1, 0;\nsetp.eq.u32 z2, %2, 0;\nsetp.eq.u32 z3, %3, 0;\nsetp.eq.u32 z4, %4, 0;\n"
                         ::"r"(s[0]), "r"(s[1]), "r"(s[2]), "r"(s[3]), "r"(id), "l"(ga), "r"(da), "r"(dx), "r"(dc), "l"(gx[0]), "l"(gx[1]), "l"(gx[2]), "l"(gx[3]));
            asm volatile("{.reg .pred p; setp.gt.s32 p, %3, 0; @p ld.relaxed.gpu.global.v2.u32 {%0,%1}, [%2];}"
                         : "=r"(e0[0].x), "=r"(e0[0].y) : "l"((uint64_t)(gs->list + pos * 16) + ((uint32_t)ml & 255)), "r"(state < 0 ? 0 : pos) : "memory");
            if (h == 0 && state == -2) TSW(29);
            if (h == 0 && state == -1) TSW(30);
            asm volatile("{\n.reg .pred p;\n.reg .b64 s;\nmov.b64 s, {0, %2};\n"
                         "LOOP:\nmbarrier.try_wait.shared::cta.b64 p, [%1], s;\n@p bra DONE;\n"
                         "add.u32 %0, %0, 1;\nsetp.gt.u32 p, %0, %3;\n@p trap;\nbra LOOP;\nDONE:\n}"
                         : "+r"(spins) : "r"(so + S_EMPTY), "r"(ph), "n"(SPIN_LIMIT) : "memory");
            asm volatile("cp.async.cg.shared.global [%0], [%1], 16, z4;" ::"r"(da), "l"(ga) : "memory");
#define ROW(j) _Pragma("unroll") for (int k = 0; k < 8; k++) \
                asm volatile("cp.async.cg.shared.global [%0], [%1], 16, z" #j ";" ::"r"(dx + (j >> 1) * 1024 + (j & 1) * 8192 + k * 128), "l"(gx[j] + k * 128) : "memory")
            ROW(0); ROW(2);
            if (full) { ROW(1); ROW(3); }
            stsm4t(dc, ym, ey, ym & low, ym & ~low);
            asm volatile("cp.async.mbarrier.arrive.noinc.shared::cta.b64 [%0];" ::"r"(so + S_FULL) : "memory");
            const bool wrap = so >= ring + (NSLOT - 4) * SLOT;
            ph ^= wrap ? 0x80000000u : 0u;
            so = wrap ? so - (NSLOT - 4) * SLOT : so + 4 * SLOT;
            pos += 4;
            if (pos >= ev) {
                if (state < 0) {
                    e0[0].x = state == -2 ? e0[1].x : e0[2].x; e0[0].y = state == -2 ? e0[1].y : e0[2].y;
                    if (state == -2) {
                        if (h == 0) TSW(24);
                        if (h == 3) TSW(25);
                        if (h == 0) asm volatile("bar.arrive 5, 288;" ::: "memory");
                        if (h < 3) bar_sync(7, 352);
                        if (h == 3) bar_sync(4, NT);
                        if (h == 0) mbar_wait(sm + O_WBE, 0);
                        if (h == 3) {
                            if (lane == 0) {
                                if (bytes) bulk_st(gs->list + gbase * 16, sm + O_L, bytes);
                                asm volatile("cp.async.bulk.wait_group.read 0;" ::: "memory");
                            }
                            __syncwarp();
                            if (lane == 0) {
                                for (int j = KR; j < 24; j++) tma3d(sm + O_W1 + (j - KR) * 4096, &m_w1, 16 * j, 0, sm + O_WBB);
                            }
                            __syncwarp();
                        }
                        state = -1;
                    } else {
                        if (h == 3) {
                            if (lane == 0) asm volatile("cp.async.bulk.wait_group 0;\nfence.proxy.async;" ::: "memory");
                            __syncwarp();
                            const int i = opaque(2 * lane - NPRIV, lane);
                            if ((unsigned)i < NPOOL) st_rlx(&gs->info[b * NPOOL + i], tag | iw0);
                            if ((unsigned)(i + 1) < NPOOL) st_rlx(&gs->info[b * NPOOL + i + 1], tag | iw1);
                        }
                        bar_sync(6, 128);
                        ev = h ? end : end - 12; state = h ? 2 : 0;
                    }
                } else if (state == 0) { ev = end - 6; state = 1; tk = take(); }
                else if (state == 1) { resolve(); ev = end; state = 2; }
                else {
                    if (state == 3) break;
                    do {
                        const uint32_t mb = sm + O_MB + (nr & 15) * 8;
                        uint32_t rg;
                        nr++;
                        if (h == 0) {
                            for (int it = 0; (rg = __reduce_max_sync(0xffffffffu, inf ^ tag)) >> 30; it++) { spin_check(it); inf = ld_rlx(&gs->info[ii]); }
                            asm volatile("st.release.cta.shared.b64 [%0], %1;" ::"r"(mb), "l"(rg | (uint64_t)nr << 32) : "memory");
                            if (rg) resolve();
                        } else {
                            uint64_t m;
                            for (int it = 0;; it++) {
                                asm volatile("ld.acquire.cta.shared.b64 %0, [%1];" : "=l"(m) : "r"(mb) : "memory");
                                if (__all_sync(0xffffffffu, (int)(m >> 32) == nr)) break;
                                spin_check(it);
                            }
                            rg = __reduce_max_sync(0xffffffffu, (uint32_t)m);
                        }
                        pos = rg ? (int)(rg >> 12) + pos - end : 0;
                        end = rg ? (rg >> 12) + (rg & 0xfff) : 1;
                        state = rg ? 2 : 3;
                    } while (pos >= end);
                    ev = end;
                }
            }
        }
        mbar_wait31(so + S_EMPTY, ph);
        TSW(8 + (h & 1));
        if (lane == 0) sts32(so + S_N, 0);
        mbar_arrive(so + S_FULL);
        if (t == 256) {
            gs->epoch[b * 32] = (tag >> 30) % 3;
            if (atomicInc(&gs->done, G - 1) == G - 1) gs->ticket = 0;
        }
        asm volatile("cp.async.wait_all;" ::: "memory");
    } else {
        asm volatile("setmaxnreg.inc.sync.aligned.u32 224;");
        bar_sync(5, 288);
        const uint32_t xa = opaque(((mat >> 1) * 8 + r) * 1024 + (w >> 2) * 128 + (((2 * (w & 3) + (mat & 1)) ^ r) * 16), lane);
        const uint32_t aa = opaque(S_A + ((mat >> 1) * 8 + r) * 32 + (((mat & 1) ^ (r >> 2)) * 16), lane);
        const uint32_t ya = opaque(S_C + (mat & 1) * 80 + (mat >> 1) * 16, lane);
        const uint32_t yc = opaque(S_C + (mat < 2 ? mat * 80 + 32 : q < 3 ? mat * 128 + ((r >> 2) ^ (mat & 1)) * 80 + q * 16 : 64), lane);
        const uint32_t na = opaque((mat & 1) * 8, lane);
        const uint32_t pw = sm + O_P + w * PW;
        const uint32_t fx = opaque(pw + (q < 3 ? P_1P0 + 2 * q * PSBO : P_1P1 + PSBO) + (mat & 1) * 128 + (r >> 2) * PSBO, lane);
        const uint32_t fyz = opaque(pw + (q < 3 ? (mat < 2 ? P_1P1 : P_1P2) + 2 * q * PSBO : mat < 2 ? P_0P0 : P_0P1) + (mat & 1) * 128 + (r >> 2) * PSBO, lane);
        uint32_t oh[5];
#pragma unroll
        for (int c = 0; c < 5; c++) oh[c] = opaque(g == (q >> 1) * 4 + min(c, 3) ? 0x3F803F80u : 0u, lane ^ c >> 2);
        uint32_t eb[3];
#pragma unroll
        for (int k = 0; k < 3; k++) {
            const int i = (g & 3) * 9 + (q & 1) * 6 + k;
            const uint32_t lo = __shfl_sync(0xffffffffu, epl, i), hi = __shfl_sync(0xffffffffu, epl, i + 3);
            eb[k] = (g & 3) < 3 && (q >> 1) == (g >> 2) ? (q & 1 ? lo : lo | hi << 16) : 0u;
        }
        asm volatile(".reg .pred lane0;\nsetp.eq.u32 lane0, %0, 0;" ::"r"(lane));
        uint32_t w0[16][4], w1[KR][4];
        mbar_wait(sm + O_WBD, 0);
#pragma unroll
        for (int k = 0; k < 16; k++) ldsm4t(w0[k], sm + w0s(k >> 2) + (w >> 2) * 8192 + (k & 3) * 2048 + sw);
#pragma unroll
        for (int k = 0; k < KR; k++) ldsm4t(w1[k], sm + w1s(k) + (w >> 2) * 2048 + sw);
        asm volatile("bar.arrive 4, %0;" ::"n"(NT) : "memory");
        bar_sync(7, 352);
        TS(6);
        Acc A;
#pragma unroll
        for (int i = 0; i < 4; i++) { A.p[i] = A.p[4 + i] = A.p[8 + i / 2] = 0; A.t01[i] = A.m[0][i] = A.m[1][i] = A.m[2][i] = 0.f; }
        uint32_t room = 144 - (b & 7) * 16;
        uint32_t so = sm + O_RING, ph, a[4], ok, go, mt = 0;
        mbar_wait(so + S_FULL, 0);
        ldsm4(a, so + aa);
        TS(7);
        while (true) {
        next:
            {
                constexpr int F = 1, H = 0, XS = XS_F;
                int seen = 0;
                uint32_t yb[8], f[4][4], R[5][4], u[4][4], sd[4];
                float y[4], z[4];
                const uint32_t sof = room & 112;
                room -= 16;
                SEQ_F
            }
            if (!(go && room)) {
                const uint32_t pu = __reduce_max_sync(0xffffffffu, ph);
                if (!room || !pu) {
                    const uint32_t wg = __reduce_max_sync(0xffffffffu, w >> 2);
                    mbar_wait(sm + O_WBB, 0);
                    asm volatile("{.reg .pred p; setp.ne.u32 p, %0, 0;\n@p bar.arrive 1, 256;\n@p bar.sync 2, 256;\n@!p bar.sync 1, 256;}" ::"r"(wg) : "memory");
                    asm volatile("fence.proxy.async::generic.acquire.sync_restrict::shared::cluster.cluster;" ::: "memory");
                    float d0[8], d1[24];
                    const uint64_t db = (uint64_t)((sm + O_P) >> 4) | (8ull << 16) | ((uint64_t)(PSBO / 16) << 32);
                    const uint32_t da = ((sm + O_W1) >> 4 | 1 << 16) + wg * 128;
                    asm volatile("wgmma.fence.sync.aligned;" ::: "memory");
                    const uint32_t sp = so == sm + O_RING ? sm + O_RING + (NSLOT - 1) * SLOT : so - SLOT, sr = (r & 6) + (mat & 1);
                    const uint32_t nd = (sr * 16 - 16 & 112) >= room ? lds32(sm + O_NODE + sr * 16 + (mat >> 1) * 8) : 0;
                    const uint64_t oa = madw(nd, 1024, (uint64_t)(out - 1024 + w * 32 + (r & 1) * 16));
                    const uint32_t sl = sp + ((mat >> 1) * 8 + sr) * 1024 + (w >> 2) * 128 + (((2 * (w & 3) + (r & 1)) ^ sr) * 16);
                    auto put = [&](int j) {
                        const uint4 v = lds128(sl + j * 256);
                        asm volatile("{.reg .pred p; setp.ne.u32 p, %5, 0; @p st.global.v4.u32 [%0], {%1,%2,%3,%4};}"
                                     ::"l"(oa + j * 256), "r"(v.x), "r"(v.y), "r"(v.z), "r"(v.w), "r"(nd) : "memory");
                    };
                    static_for<24>([&](auto kc) {
                        constexpr int k = kc.value;
                        if (k == 16) asm volatile("wgmma.commit_group.sync.aligned;" ::: "memory");
                        if (k == 20) asm volatile("{.reg .pred p; setp.eq.u32 p, %0, 0;\n@p bar.arrive 2, 256;}" ::"r"(wg) : "memory");
                        G1(k);
                        if (k < 16) G0(k % 16);
                    });
                    asm volatile("wgmma.commit_group.sync.aligned;" ::: "memory");
                    asm volatile("wgmma.wait_group.sync.aligned 1;" ::: "memory");
#pragma unroll
                    for (int i = 0; i < 8; i++) asm volatile("" : "+f"(d0[i])::"memory");
                    stsm4t(sp + xa, pack(d0[0], d0[1]), pack(d0[2], d0[3]), pack(d0[4], d0[5]), pack(d0[6], d0[7]));
                    __syncwarp();
                    put(0);
                    float gt[8];
                    uint32_t chk = -1;
#pragma unroll
                    for (int i = 0; i < 8; i++) {
                        asm volatile("ex2.approx.ftz.f32 %0, %1;" : "=f"(gt[i]) : "f"(d0[i] * -1.4426950408889634f) : "memory");
                        asm volatile("rcp.approx.ftz.f32 %0, %1;" : "=f"(gt[i]) : "f"(gt[i] + 1.f) : "memory");
                    }
#pragma unroll
                    for (int i = 0; i < 8; i++) chk &= __float_as_uint(gt[i]);
                    sts32(sm + O_TRASH, chk);
                    asm volatile("wgmma.wait_group.sync.aligned 0;" ::: "memory");
#pragma unroll
                    for (int i = 0; i < 24; i++) asm volatile("" : "+f"(d1[i])::"memory");
                    asm volatile("{.reg .pred p; setp.ne.u32 p, %0, 0;\n@p bar.sync 3, 256;}" ::"r"(wg) : "memory");
#pragma unroll
                    for (int j = 0; j < 3; j++) {
                        uint32_t o[4];
#pragma unroll
                        for (int i = 0; i < 4; i++) o[i] = pack(d1[8 * j + 2 * i] * gt[2 * i], d1[8 * j + 2 * i + 1] * gt[2 * i + 1]);
                        stsm4t(sp + xa + 256 + j * 256, o[0], o[1], o[2], o[3]);
                    }
                    __syncwarp();
#pragma unroll
                    for (int j = 1; j < 4; j++) put(j);
                    __syncwarp();
                    asm volatile("@lane0 mbarrier.arrive.shared::cta.b64 _, [%0];" ::"r"(sp + S_EMPTY) : "memory");
                    asm volatile("@lane0 red.shared.add.u32 [%0], 1;" ::"r"(sm + O_SUM + 4) : "memory");
                    asm volatile("{.reg .pred p; setp.eq.u32 p, %0, 0;\n@p bar.sync 3, 256;}" ::"r"(wg) : "memory");
                    room = 128;
                    if (!pu) break;
                }
                if (!ok) { mbar_wait31(so + S_FULL, pu); ldsm4(a, so + aa); }
                if (!(pu & 0xfffc)) { if (pu & 1) goto half; continue; }
            }
            while (true) {
                do {
                    constexpr int F = 0, H = 0, XS = XS_R;
                    int seen = 0;
                    uint32_t yb[8], f[4][4], R[5][4], u[4][4], sd[4];
                    SEQ_R
                } while (go);
                asm volatile("{.reg .pred p, q; .reg .f32 n; abs.f32 n, %1; setp.ne.u32 q, %2, 0; setp.le.and.f32 p, n, 0f00000002, q; selp.u32 %0, 1, 0, p;}" : "=r"(go) : "r"(ph), "r"(ok));
                if (go) goto next;
                if (ok) goto half;
                const uint32_t pu = __reduce_max_sync(0xffffffffu, ph);
                mbar_wait31(so + S_FULL, pu); ldsm4(a, so + aa);
                if (!(pu & 0xfffc)) { go = pu & 1; break; }
            }
            if (!go) continue;
        half: {
                constexpr int F = 0, H = 1, XS = XS_H;
                int seen = 0;
                uint32_t yb[8], f[4][4], R[5][4], u[4][4], sd[4];
                SEQ_H
                if (!ok) { mbar_wait31(so + S_FULL, __reduce_max_sync(0xffffffffu, ph)); ldsm4(a, so + aa); }
            }
        }
        TS(10);
    }
}

typedef CUresult (*EncFn)(CUtensorMap*, CUtensorMapDataType, cuuint32_t, void*, const cuuint64_t*, const cuuint64_t*,
                          const cuuint32_t*, const cuuint32_t*, CUtensorMapInterleave, CUtensorMapSwizzle,
                          CUtensorMapL2promotion, CUtensorMapFloatOOBfill);

void make_map(EncFn fn, CUtensorMap* m, void* p, int rows, int cols, int brows, int bcols, int bblk) {
    cuuint64_t dims[3] = {64, (cuuint64_t)rows, (cuuint64_t)cols / 64}, strides[2] = {(cuuint64_t)cols * 2, 128};
    cuuint32_t box[3] = {(cuuint32_t)bcols, (cuuint32_t)brows, (cuuint32_t)bblk}, es[3] = {1, 1, 1};
    fn(m, CU_TENSOR_MAP_DATA_TYPE_BFLOAT16, 3, p, dims, strides, box, es, CU_TENSOR_MAP_INTERLEAVE_NONE,
       bcols == 64 ? CU_TENSOR_MAP_SWIZZLE_128B : CU_TENSOR_MAP_SWIZZLE_NONE, CU_TENSOR_MAP_L2_PROMOTION_L2_128B, CU_TENSOR_MAP_FLOAT_OOB_FILL_NONE);
}

}

extern "C" void kernel_launch(void* const* d_in, const int* in_sizes, int n_in, void* d_out, int out_size) {
    static EncFn enc = nullptr;
    static void* scratch = nullptr;
    if (!enc) {
        void* fn = nullptr;
        cudaDriverEntryPointQueryResult qr;
        cudaGetDriverEntryPoint("cuTensorMapEncodeTiled", &fn, cudaEnableDefault, &qr);
        enc = (EncFn)fn;
        cudaGetSymbolAddress(&scratch, g_scratch);
        cudaFuncSetAttribute(tp_kernel, cudaFuncAttributeMaxDynamicSharedMemorySize, SMEM_BYTES);
    }
    CUtensorMap m_wr, m_w0, m_w1, m_x;
    make_map(enc, &m_wr, d_in[5], 16, 640, 16, 64, 5);
    make_map(enc, &m_w0, d_in[6], 256, 128, 64, 64, 2);
    make_map(enc, &m_w1, d_in[7], 384, 128, 16, 64, 2);
    make_map(enc, &m_x, d_in[0], NN * 8, 64, NLOC * 2, 8, 1);
    tp_kernel<<<G, NT, SMEM_BYTES>>>((const int4*)d_in[4], (const int4*)d_in[3], (const char*)d_in[1], (Scratch*)scratch,
                                     (const char*)d_in[0], (const char*)d_in[2], (const __nv_bfloat16*)d_in[8], (char*)d_out,
                                     m_wr, m_w0, m_w1, m_x);
}
```

```cpp
#include <cuda_runtime.h>
#include <cuda_bf16.h>
#include <cuda.h>
#include <stdint.h>
#include <stddef.h>

namespace {

constexpr int NN = 10000;
constexpr int NE = 320000;
constexpr int G = 132;
constexpr int NT = 384;
constexpr int CH = 2432;
constexpr int NLOC = (NN + G - 1) / G;
constexpr int NPOOL = 3;
constexpr int NPAIR = NLOC / 2, NPRIV = NPAIR - NPOOL;
constexpr int HEAVY = 128;
constexpr int SEGW = 11;

constexpr int NSLOT = 7;
constexpr int KR = 9;
constexpr uint32_t WP = 0x5357575, TP = 0x9375;
#define WLD(p) { _Pragma("unroll") for (int j = 0; j < 4 + KR; j++) if ((WP >> 4 * (j < 4 ? j : j < 8 ? 4 : j < 11 ? 5 : 6) & 15) == p) \
    tma3d(sm + (j < 4 ? w0s(j) : w1s(j - 4)), j < 4 ? &m_w0 : &m_w1, j < 4 ? j * 64 : (j - 4) * 16, 0, sm + O_WBD); \
    _Pragma("unroll") for (int j = 0; j < 4; j++) { const int r0 = (b * 4 + j) * (NLOC / 4); \
        if ((TP >> 4 * j & 15) == p) tma3d(sm + O_WR1 + 12288, &m_x, r0 * 8, 0, sm + O_WBE); } }

constexpr int S_A = 16384, S_C = S_A + 512, S_FULL = S_C + 144, S_EMPTY = S_FULL + 8, S_N = S_C + 160, SLOT = S_C + 512;

constexpr int PSBO = 272;
constexpr int PB1 = 5 * PSBO + 256, PB0 = PSBO + 256;
constexpr int P_1P0 = 0, P_1P1 = PB1, P_0P1 = 2 * PB1, P_0P0 = P_0P1 + PB0, P_1P2 = P_0P0 + PB0;
constexpr int PW = P_1P2 + PB1;

constexpr int O_W1 = 0;
constexpr int O_P = 62336;
constexpr int O_RING = O_P + 8 * PW;
constexpr int O_WBA = O_RING + NSLOT * SLOT, O_WBB = O_WBA + 8, O_WBC = O_WBA + 16, O_WBD = O_WBA + 24, O_WBE = O_WBA + 32, O_TRASH = O_WBA + 40, O_NODE = O_WBA + 48;
constexpr int O_SUM = O_NODE + 128, O_MB = O_SUM + 16;
constexpr int O_HV = O_MB + 128, SMEM_BYTES = O_HV + 48;
constexpr int CAPT = 192;
constexpr int O_L = 0, LZ = CAPT * 256 / (NT * 16), O_W0S = O_L + CAPT * 256, O_OUT = O_RING + S_C - CH * 8, O_SRC = O_RING + 6 * SLOT;
constexpr int O_KT = O_RING + SLOT, O_RH = O_RING + 2 * SLOT;
constexpr int O_WR0 = O_RING + 3 * SLOT, O_WR1 = O_RING + 4 * SLOT;
__host__ __device__ constexpr int w0s(int j) { return j < 3 ? O_W0S + j * 16384 : O_SRC; }
__host__ __device__ constexpr int w1s(int k) { return k < 4 ? O_RING + 5 * SLOT + k * 4096 : k < 7 ? O_WR1 + (k - 4) * 4096 : O_W0S + 49152 + (k - 7) * 4096; }
constexpr int O_BCNT = O_WR0 + 10240, O_NCUR = O_BCNT + 640, O_NCNT = O_NCUR + 320;
constexpr int O_BOFF = O_NCNT + 512, O_SORT = O_BOFF + 640, O_NOFF = O_SORT + 320;
constexpr int TBIG = G * CAPT + 8, NTILE = TBIG + NE / 8 + G * (NLOC + 5);
static_assert(SMEM_BYTES <= 232448 && CAPT % 16 == 0 && NTILE < (1 << 18), "smem");
static_assert(LZ * NT * 16 == CAPT * 256 && O_W0S % 1024 == 0 && w1s(KR) <= O_OUT && O_OUT % 128 == 0 && CH * 6 <= S_C && G * 128 <= S_C, "staging");
static_assert(O_NOFF + 1024 <= O_RING + 3 * SLOT + S_C && 12288 + NLOC * 32 <= S_C && (24 - KR) * 4096 <= O_P && KR <= 9, "staging");
static_assert(O_RING % 1024 == 0 && SLOT % 1024 == 0 && O_W0S <= O_P && O_NOFF % 8 == 0, "layout");
static_assert(G * CH >= NE && NE % 8 == 0 && CH < 4096 && CH / 8 <= 320 && NE < (1 << 21), "chunks");
static_assert(SEGW * (NT / 32) == G && G <= 160 && G % 4 == 0, "segments");
static_assert(NLOC % 4 == 0 && NLOC < 80 && NLOC * 4 <= 320 && NN < 0x3fff && NE / 8 < 0xbfff && NPRIV >= 30, "scan width");

struct __align__(256) Scratch {
    uint32_t keys[G * G * 32];
    uint64_t vals[G * CH];
    uint32_t more[G * CH];
    uint32_t epoch[G * 32];
    uint32_t info[(G * NPOOL + 127) / 128 * 128];
    unsigned done, pad0[31], ticket, pad1[31];
    uint4 list[NTILE * 16];
};
static_assert(offsetof(Scratch, list) % 256 == 0, "list");
__device__ Scratch g_scratch;
#define TS(i)
#define TSW(i)
#define TV(i, v)

constexpr int SPIN_LIMIT = 1 << 24;

__device__ __forceinline__ void mbar_init(uint32_t a, int c) { asm volatile("mbarrier.init.shared::cta.b64 [%0], %1;" ::"r"(a), "r"(c) : "memory"); }
__device__ __forceinline__ void mbar_expect(uint32_t a, int b) { asm volatile("mbarrier.arrive.expect_tx.shared::cta.b64 _, [%0], %1;" ::"r"(a), "r"(b) : "memory"); }
__device__ __forceinline__ void mbar_arrive(uint32_t a) { asm volatile("mbarrier.arrive.shared::cta.b64 _, [%0];" ::"r"(a) : "memory"); }
__device__ __forceinline__ void mbar_wait(uint32_t a, uint32_t ph) {
    asm volatile("{\n.reg .pred p, q;\n.reg .u32 it;\n"
                 "mbarrier.try_wait.parity.shared::cta.b64 p, [%0], %1;\n"
                 "@p bra DONE;\n"
                 "mov.u32 it, 0;\n"
                 "LOOP:\n"
                 "mbarrier.try_wait.parity.shared::cta.b64 p, [%0], %1;\n"
                 "@p bra DONE;\n"
                 "add.u32 it, it, 1;\n"
                 "setp.gt.u32 q, it, %2;\n"
                 "@q trap;\n"
                 "bra LOOP;\n"
                 "DONE:\n}" ::"r"(a), "r"(ph), "n"(SPIN_LIMIT) : "memory");
}
__device__ __forceinline__ void mbar_wait31(uint32_t a, uint32_t ph) {
    asm volatile("{\n.reg .pred p, q;\n.reg .u32 it;\n.reg .b64 s;\n"
                 "mov.b64 s, {0, %1};\n"
                 "mbarrier.try_wait.shared::cta.b64 p, [%0], s;\n"
                 "@p bra DONE;\n"
                 "mov.u32 it, 0;\n"
                 "LOOP:\n"
                 "mbarrier.try_wait.shared::cta.b64 p, [%0], s;\n"
                 "@p bra DONE;\n"
                 "add.u32 it, it, 1;\n"
                 "setp.gt.u32 q, it, %2;\n"
                 "@q trap;\n"
                 "bra LOOP;\n"
                 "DONE:\n}" ::"r"(a), "r"(ph), "n"(SPIN_LIMIT) : "memory");
}
__device__ __forceinline__ void spin_check(int it) {
    asm volatile("{\n.reg .pred q;\nsetp.gt.s32 q, %0, %1;\n@q trap;\n}" ::"r"(it), "n"(SPIN_LIMIT));
}
__device__ __forceinline__ void ldsm4(uint32_t* r, uint32_t a) { asm volatile("ldmatrix.sync.aligned.m8n8.x4.shared.b16 {%0,%1,%2,%3}, [%4];" : "=r"(r[0]), "=r"(r[1]), "=r"(r[2]), "=r"(r[3]) : "r"(a) : "memory"); }
__device__ __forceinline__ void ldsm4t(uint32_t* r, uint32_t a) { asm volatile("ldmatrix.sync.aligned.m8n8.x4.trans.shared.b16 {%0,%1,%2,%3}, [%4];" : "=r"(r[0]), "=r"(r[1]), "=r"(r[2]), "=r"(r[3]) : "r"(a) : "memory"); }
__device__ __forceinline__ void ldsm2t(uint32_t* r, uint32_t a) { asm volatile("ldmatrix.sync.aligned.m8n8.x2.trans.shared.b16 {%0,%1}, [%2];" : "=r"(r[0]), "=r"(r[1]) : "r"(a) : "memory"); }
__device__ __forceinline__ void stsm4t(uint32_t a, uint32_t r0, uint32_t r1, uint32_t r2, uint32_t r3) { asm volatile("stmatrix.sync.aligned.m8n8.x4.trans.shared.b16 [%0], {%1,%2,%3,%4};" ::"r"(a), "r"(r0), "r"(r1), "r"(r2), "r"(r3) : "memory"); }
__device__ __forceinline__ void stsm2t(uint32_t a, uint32_t r0, uint32_t r1) { asm volatile("stmatrix.sync.aligned.m8n8.x2.trans.shared.b16 [%0], {%1,%2};" ::"r"(a), "r"(r0), "r"(r1) : "memory"); }
__device__ __forceinline__ void mma16(float* d, const uint32_t* a, uint32_t b0, uint32_t b1) {
    asm("mma.sync.aligned.m16n8k16.row.col.f32.bf16.bf16.f32 {%0,%1,%2,%3}, {%4,%5,%6,%7}, {%8,%9}, {%0,%1,%2,%3};"
        : "+f"(d[0]), "+f"(d[1]), "+f"(d[2]), "+f"(d[3]) : "r"(a[0]), "r"(a[1]), "r"(a[2]), "r"(a[3]), "r"(b0), "r"(b1));
}
__device__ __forceinline__ void mma8(float* d, uint32_t a0, uint32_t a1, uint32_t b0) {
    asm("mma.sync.aligned.m16n8k8.row.col.f32.bf16.bf16.f32 {%0,%1,%2,%3}, {%4,%5}, {%6}, {%0,%1,%2,%3};"
        : "+f"(d[0]), "+f"(d[1]), "+f"(d[2]), "+f"(d[3]) : "r"(a0), "r"(a1), "r"(b0));
}
__device__ __forceinline__ void mma16z(float* d, const uint32_t* a, uint32_t b0, uint32_t b1) {
    asm("mma.sync.aligned.m16n8k16.row.col.f32.bf16.bf16.f32 {%0,%1,%2,%3}, {%4,%5,%6,%7}, {%8,%9}, {%10,%10,%10,%10};"
        : "=f"(d[0]), "=f"(d[1]), "=f"(d[2]), "=f"(d[3]) : "r"(a[0]), "r"(a[1]), "r"(a[2]), "r"(a[3]), "r"(b0), "r"(b1), "f"(0.f));
}
__device__ __forceinline__ uint32_t pack(float lo, float hi) { uint32_t r; asm("cvt.rn.bf16x2.f32 %0, %1, %2;" : "=r"(r) : "f"(hi), "f"(lo)); return r; }
__device__ __forceinline__ uint32_t hmul(uint32_t a, uint32_t b) { uint32_t r; asm("mul.rn.bf16x2 %0, %1, %2;" : "=r"(r) : "r"(a), "r"(b)); return r; }
__device__ __forceinline__ uint32_t hfma(uint32_t a, uint32_t b, uint32_t c) { uint32_t r; asm("fma.rn.bf16x2 %0, %1, %2, %3;" : "=r"(r) : "r"(a), "r"(b), "r"(c)); return r; }
__device__ __forceinline__ uint4 lds128(uint32_t a) { uint4 v; asm volatile("ld.shared.v4.u32 {%0,%1,%2,%3}, [%4];" : "=r"(v.x), "=r"(v.y), "=r"(v.z), "=r"(v.w) : "r"(a) : "memory"); return v; }
__device__ __forceinline__ void sts128(uint32_t a, uint4 v) { asm volatile("st.shared.v4.u32 [%0], {%1,%2,%3,%4};" ::"r"(a), "r"(v.x), "r"(v.y), "r"(v.z), "r"(v.w) : "memory"); }
__device__ __forceinline__ int lds32(uint32_t a) { int v; asm volatile("ld.shared.u32 %0, [%1];" : "=r"(v) : "r"(a) : "memory"); return v; }
__device__ __forceinline__ void sts32(uint32_t a, int v) { asm volatile("st.shared.u32 [%0], %1;" ::"r"(a), "r"(v) : "memory"); }
__device__ __forceinline__ int atoms_add(uint32_t a, int v) { int r; asm volatile("atom.shared.add.u32 %0, [%1], %2;" : "=r"(r) : "r"(a), "r"(v) : "memory"); return r; }
__device__ __forceinline__ uint32_t ld_rlx(const void* p) { uint32_t v; asm volatile("ld.relaxed.gpu.global.u32 %0, [%1];" : "=r"(v) : "l"(p) : "memory"); return v; }
__device__ __forceinline__ void st_rlx(void* p, uint32_t v) { asm volatile("st.relaxed.gpu.global.u32 [%0], %1;" ::"l"(p), "r"(v) : "memory"); }
__device__ __forceinline__ void bulk(uint32_t dst, const void* g, int n, uint32_t bar) {
    asm volatile("cp.async.bulk.shared::cluster.global.mbarrier::complete_tx::bytes [%0], [%1], %2, [%3];" ::"r"(dst), "l"(g), "r"(n), "r"(bar) : "memory");
}
__device__ __forceinline__ void bulk_st(void* g, uint32_t src, int n) {
    asm volatile("cp.async.bulk.global.shared::cta.bulk_group [%0], [%1], %2;\ncp.async.bulk.commit_group;" ::"l"(g), "r"(src), "r"(n) : "memory");
}
__device__ __forceinline__ uint2 lds64(uint32_t a) { uint2 v; asm volatile("ld.shared.v2.u32 {%0,%1}, [%2];" : "=r"(v.x), "=r"(v.y) : "r"(a) : "memory"); return v; }
__device__ __forceinline__ void sts64(uint32_t a, uint32_t x, uint32_t y) { asm volatile("st.shared.v2.u32 [%0], {%1,%2};" ::"r"(a), "r"(x), "r"(y) : "memory"); }
__device__ __forceinline__ void tma3d(uint32_t dst, const CUtensorMap* m, int c1, int c2, uint32_t bar) {
    asm volatile("cp.async.bulk.tensor.3d.shared::cluster.global.mbarrier::complete_tx::bytes [%0], [%1, {0, %3, %4}], [%2];"
                 ::"r"(dst), "l"(m), "r"(bar), "r"(c1), "r"(c2) : "memory");
}
__device__ __forceinline__ void fence_async() { asm volatile("fence.proxy.async.shared::cta;" ::: "memory"); }
__device__ __forceinline__ uint64_t madw(uint32_t a, uint32_t b, uint64_t c) { uint64_t r; asm("mad.wide.u32 %0, %1, %2, %3;" : "=l"(r) : "r"(a), "r"(b), "l"(c)); return r; }
__device__ __forceinline__ uint32_t lop_sel(uint32_t a, uint32_t b, uint32_t m) { uint32_t r; asm("lop3.b32 %0, %1, %2, %3, 0xd8;" : "=r"(r) : "r"(a), "r"(b), "r"(m)); return r; }
__device__ __forceinline__ uint32_t opaque(uint32_t v, int lane) { return __shfl_sync(0xffffffffu, v, lane); }
__device__ __forceinline__ void bar_sync(int id, int n) { asm volatile("bar.sync %0, %1;" ::"r"(id), "r"(n) : "memory"); }

__device__ __forceinline__ void wg_rs16(float* d, const uint32_t* a, uint64_t db, int sc) {
    asm volatile("{.reg .pred p; setp.ne.b32 p, %13, 0;\n"
                 "wgmma.mma_async.sync.aligned.m64n16k16.f32.bf16.bf16 {%0,%1,%2,%3,%4,%5,%6,%7}, {%8,%9,%10,%11}, %12, p, 1, 1, 0;}"
                 : "+f"(d[0]), "+f"(d[1]), "+f"(d[2]), "+f"(d[3]), "+f"(d[4]), "+f"(d[5]), "+f"(d[6]), "+f"(d[7])
                 : "r"(a[0]), "r"(a[1]), "r"(a[2]), "r"(a[3]), "l"(db), "r"(sc));
}
__device__ __forceinline__ void wg_rs48(float* d, const uint32_t* a, uint64_t db, int sc) {
    asm volatile("{.reg .pred p; setp.ne.b32 p, %29, 0;\n"
                 "wgmma.mma_async.sync.aligned.m64n48k16.f32.bf16.bf16 {%0,%1,%2,%3,%4,%5,%6,%7,%8,%9,%10,%11,%12,%13,%14,%15,%16,%17,%18,%19,%20,%21,%22,%23}, {%24,%25,%26,%27}, %28, p, 1, 1, 0;}"
                 : "+f"(d[0]), "+f"(d[1]), "+f"(d[2]), "+f"(d[3]), "+f"(d[4]), "+f"(d[5]), "+f"(d[6]), "+f"(d[7]),
                   "+f"(d[8]), "+f"(d[9]), "+f"(d[10]), "+f"(d[11]), "+f"(d[12]), "+f"(d[13]), "+f"(d[14]), "+f"(d[15]),
                   "+f"(d[16]), "+f"(d[17]), "+f"(d[18]), "+f"(d[19]), "+f"(d[20]), "+f"(d[21]), "+f"(d[22]), "+f"(d[23])
                 : "r"(a[0]), "r"(a[1]), "r"(a[2]), "r"(a[3]), "l"(db), "r"(sc));
}
__device__ __forceinline__ void wg_ss48(float* d, uint64_t da, uint64_t db, int sc) {
    asm volatile("{.reg .pred p; setp.ne.b32 p, %26, 0;\n"
                 "wgmma.mma_async.sync.aligned.m64n48k16.f32.bf16.bf16 {%0,%1,%2,%3,%4,%5,%6,%7,%8,%9,%10,%11,%12,%13,%14,%15,%16,%17,%18,%19,%20,%21,%22,%23}, %24, %25, p, 1, 1, 1, 0;}"
                 : "+f"(d[0]), "+f"(d[1]), "+f"(d[2]), "+f"(d[3]), "+f"(d[4]), "+f"(d[5]), "+f"(d[6]), "+f"(d[7]),
                   "+f"(d[8]), "+f"(d[9]), "+f"(d[10]), "+f"(d[11]), "+f"(d[12]), "+f"(d[13]), "+f"(d[14]), "+f"(d[15]),
                   "+f"(d[16]), "+f"(d[17]), "+f"(d[18]), "+f"(d[19]), "+f"(d[20]), "+f"(d[21]), "+f"(d[22]), "+f"(d[23])
                 : "l"(da), "l"(db), "r"(sc));
}

__device__ __forceinline__ int warp_incl(int v) {
#pragma unroll
    for (int o = 1; o < 32; o <<= 1)
        asm volatile("{.reg .pred p; .reg .b32 u; shfl.sync.up.b32 u|p, %0, %1, 0, 0xffffffff; @p add.s32 %0, %0, u;}" : "+r"(v) : "r"(o));
    return v;
}
__device__ __forceinline__ void ldg128(uint32_t* r, const void* p, bool on) {
    asm volatile("{.reg .pred p; setp.ne.u32 p, %5, 0; @p ld.global.nc.v4.u32 {%0,%1,%2,%3}, [%4];}"
                 : "=r"(r[0]), "=r"(r[1]), "=r"(r[2]), "=r"(r[3]) : "l"(p), "r"((uint32_t)on));
}

template <int V> struct IC { static constexpr int value = V; };
template <int N, int I = 0, class Fn> __device__ __forceinline__ void static_for(Fn f) { if constexpr (I < N) { f(IC<I>{}); static_for<N, I + 1>(f); } }

struct Acc {
    uint32_t p[10];
    float t01[4], m[3][4];
};

#define LF(m) if (H) ldsm2t(f[m], so + xa + m * 256); else ldsm4t(f[m], so + xa + m * 256)
#define LY() ldsm4(yb, so + ya)
#define LC() ldsm4(yb + 4, so + yc)
#define LN() ph = lds32(so + S_N)
#define ADV() { if (F) asm volatile("{.reg .pred p; setp.ne.and.u32 p, %1, 0, lane0; @p mbarrier.arrive.shared::cta.b64 _, [%0];}" ::"r"(so + S_EMPTY), "r"(room) : "memory"); \
                else asm volatile("@lane0 mbarrier.arrive.shared::cta.b64 _, [%0];" ::"r"(so + S_EMPTY) : "memory"); \
                so = so == sm + O_RING + (NSLOT - 1) * SLOT ? sm + O_RING : so + SLOT; }
#define LA() asm volatile("{\n.reg .pred p, q;\n.reg .b64 s;\n.reg .f32 n;\nmov.b64 s, {0, %7};\nmbarrier.test_wait.shared::cta.b64 p, [%6], s;\n" \
                          "abs.f32 n, %7;\nsetp.gt.and.f32 q, n, 0f00000003, p;\nselp.u32 %4, 1, 0, p;\nselp.u32 %5, 1, 0, q;\n" \
                          "@p ldmatrix.sync.aligned.m8n8.x4.shared.b16 {%0,%1,%2,%3}, [%8];\n}" \
                          : "+r"(a[0]), "+r"(a[1]), "+r"(a[2]), "+r"(a[3]), "=r"(ok), "=r"(go) : "r"(so + S_FULL), "r"(ph), "r"(so + aa) : "memory")
#define RAD(p, s) if (!H || !s) { float c[4]; mma16z(c, wr[p], a[2 * s], a[2 * s + 1]); R[p][2 * s] = pack(c[0], c[1]); R[p][2 * s + 1] = pack(c[2], c[3]); }
#define MUL(n, x, y) (XS >> n & 1 ? hmul(y, x) : hmul(x, y))
#define FMA(n, x, y, z) (XS >> n & 1 ? hfma(y, x, z) : hfma(x, y, z))
#define ON(i) if (!H || i < 2)
#define ACC(n, m, i, x, y) ON(i) { constexpr int c = 2 * m + ((i ^ XA) & 1); A.p[c] = F && !(seen >> c & 1) ? MUL(n, x, y) : FMA(n, x, y, A.p[c]); seen |= 1 << c; }
#define P00(i) ACC(0, 3, i, f[0][i], R[0][i])
#define P10(k, i) ACC(1, k, i, f[1 + k][i], R[3][i])
#define S0(k, i) ON(i) sd[i] = MUL(2, f[1 + k][i], yb[2 * k + (i >> 1)])
#define SD(k, i) ON(i) sd[i] = FMA(2, f[1 + k][i], yb[2 * k + (i >> 1)], sd[i])
#define P110(i) ACC(3, 4, i, sd[i], R[1][i])
#define TU(i) ON(i) u[3][i ^ XU] = MUL(4, f[0][i], R[2][i])
#define EM(d, u) if (F) mma16z(d, u, yb[6], yb[7]); else if (H) mma8(d, u[0], u[1], yb[6]); else mma16(d, u, yb[6], yb[7])
#define TM() EM(A.t01, u[3])
#define MU(k, i) ON(i) u[k][i ^ XU] = MUL(5, f[1 + k][i], R[4][i])
#define MM(k) EM(A.m[k], u[k])
#define PK(v, h) pack(v[2 * (h)], v[2 * (h) + 1])
#define LM() { sts32(na + (sof + sm + O_NODE), mt); asm volatile("ld.shared.u16 %0, [%1];" : "=r"(mt) : "r"(na + (so + S_C + 48)) : "memory"); }
#define MP(k) PK(A.m[k], XA ^ XU), PK(A.m[k], 1 ^ XA ^ XU)
#define FY(k) if (k == 0) mma16z(y, A.p, oh[0], oh[1]); else if (k > 1 && !(seen >> 30)) { mma16(y, A.p + 4, oh[2], oh[3]); seen |= 1 << 30; }
#define FZ(k) if (k == 0) { const uint32_t mp[4] = {A.p[8], A.p[9], MP(2)}; mma16z(z, mp, oh[4], eb[2]); } \
              else if (k == 1) { const uint32_t mp[4] = {MP(0), MP(1)}; mma16(z, mp, eb[0], eb[1]); }
#define SX() stsm2t(fx + sof, PK(A.t01, XU), PK(A.t01, 1 ^ XU))
#define SY() stsm4t(fyz + sof, PK(y, XA), PK(y, 1 ^ XA), PK(z, XA), PK(z, 1 ^ XA))
#define G0(k) wg_rs16(d0, w0[k], db + ((((k) & 7) * PW + (((k) >> 3) ? P_0P1 : P_0P0)) >> 4), k)
#define G1(i) { constexpr int k_ = ((i) + KR) % 24; const uint64_t bk = db + (((k_ & 7) * PW + ((k_ >> 3) == 0 ? P_1P0 : (k_ >> 3) == 1 ? P_1P1 : P_1P2)) >> 4); \
                if (k_ < KR) wg_rs48(d1, w1[k_ % KR], bk, i); else wg_ss48(d1, (da + (k_ - KR) * 256) | (64ull << 32) | (1ull << 62), bk, i); }
#define XA 1
#define XU 0
#define XS_R 63
#define SEQ_R LF(2); LN(); RAD(1,0); RAD(1,1); LC(); LY(); RAD(2,0); RAD(2,1); RAD(4,0); RAD(4,1); RAD(3,0); RAD(3,1); LF(0); P10(1,1); P10(1,0); \
    P10(1,3); P10(1,2); LF(3); MU(2,3); S0(2,3); S0(2,2); S0(2,1); S0(2,0); RAD(0,1); RAD(0,0); MU(2,2); P00(2); MU(2,1); MU(1,3); MU(2,0); MM(2); P00(3); \
    MU(1,2); LF(1); ADV(); LA(); P10(0,0); P10(0,1); P10(0,2); P10(0,3); SD(0,0); SD(0,2); SD(0,1); SD(0,3); SD(1,0); P110(0); SD(1,2); P110(2); SD(1,1); \
    P110(1); SD(1,3); P110(3); P00(0); MU(0,0); TU(0); P10(2,0); TU(2); MU(1,1); TU(3); TU(1); TM(); P10(2,2); P00(1); MU(0,2); P10(2,1); MU(1,0); MM(1); \
    P10(2,3); MU(0,1); MU(0,3); MM(0);
#define XS_H XS_R
#define SEQ_H SEQ_R
#define XS_F 63
#define SEQ_F LY(); LF(2); LF(0); SX(); FZ(0); FY(0); FY(2); RAD(1,0); LM(); RAD(0,1); RAD(2,1); RAD(3,0); RAD(3,1); RAD(2,0); LC(); RAD(0,0); \
    RAD(4,0); LN(); FZ(2); LF(1); LF(3); ADV(); FY(1); RAD(4,1); RAD(1,1); LA(); TU(1); TU(0); TU(3); TU(2); P10(0,0); P10(0,2); P10(2,3); P10(0,1); \
    P10(2,2); TM(); P10(0,3); FY(3); P10(2,1); P10(1,0); P10(2,0); P10(1,1); P10(1,2); S0(0,1); SD(2,1); SD(1,1); P110(1); S0(0,0); S0(0,3); S0(0,2); \
    SD(2,0); SD(1,0); P110(0); FZ(1); SY(); P10(1,3); MU(0,1); MU(0,0); MU(0,3); MU(0,2); SD(2,3); SD(1,3); P110(3); MU(2,2); MU(2,3); MU(2,0); MU(2,1); \
    MM(2); P00(2); SD(2,2); SD(1,2); P110(2); MU(1,0); P00(3); MU(1,2); MU(1,3); MU(1,1); MM(1); P00(0); P00(1); MM(0);

__device__ __forceinline__ void heavy_nodes(uint32_t sm, float* P, const int4* dst, const int* src, const __nv_bfloat16* rhat, const __nv_bfloat16* x,
                                            const uint4* ea, const __nv_bfloat16* eps, const __nv_bfloat16* wr, const __nv_bfloat16* w0,
                                            const __nv_bfloat16* w1, __nv_bfloat16* out) {
    static_assert(NE % 1280 == 0 && 8 * PW >= 22 * 512, "heavy");
    int t;
    asm volatile("mov.u32 %0, %%tid.x;" : "=r"(t));
    const int lane = t & 31, c = t & 127, h = t >> 7;
    const uint32_t hv = lane < 10 ? lds32(sm + O_HV + 4 * lane) : 0;
    if (!__any_sync(0xffffffffu, hv != 0)) return;
    auto bf = [](const __nv_bfloat16* p) { return __bfloat162float(__ldg(p)); };
    float W[5][16], ce[27];
#pragma unroll
    for (int i = 0; i < 80; i++) W[i >> 4][i & 15] = bf(wr + (i & 15) * 640 + (i >> 4) * 128 + c);
#pragma unroll
    for (int i = 0; i < 27; i++) ce[i] = bf(eps + i);
#pragma unroll 1
    for (int l = 0; l < NLOC; l++) {
        if (!(__shfl_sync(0xffffffffu, hv, l >> 3) >> 4 * (l & 7) & 1)) continue;
        const int node = l * G + blockIdx.x;
        float s[11] = {};
#pragma unroll 1
        for (int v0 = h * (NE / 8); v0 < (h + 1) * (NE / 8); v0 += 160) {
            uint32_t m = 0;
#pragma unroll
            for (int j = 0; j < 5; j++) {
                const int4 d = __ldg(dst + v0 + j * 32 + lane);
                m |= ((d.x == node) | (d.y == node) << 1 | (d.z == node) << 2 | (d.w == node) << 3) << 4 * j;
            }
            for (uint32_t any = __ballot_sync(0xffffffffu, m != 0); any; any &= any - 1) {
                const int ln = __ffs(any) - 1;
                for (uint32_t mm = __shfl_sync(0xffffffffu, m, ln); mm; mm &= mm - 1) {
                    const int i = __ffs(mm) - 1, e = (v0 + (i >> 2) * 32 + ln) * 4 + (i & 3);
                    const __nv_bfloat16* xr = x + (size_t)__ldg(src + e) * 512 + c;
                    const uint4 a0 = __ldg(ea + 2 * e), a1 = __ldg(ea + 2 * e + 1);
                    const uint32_t a[8] = {a0.x, a0.y, a0.z, a0.w, a1.x, a1.y, a1.z, a1.w};
                    const float f0 = bf(xr), f[3] = {bf(xr + 128), bf(xr + 256), bf(xr + 384)};
                    const float y[3] = {bf(rhat + 3 * e), bf(rhat + 3 * e + 1), bf(rhat + 3 * e + 2)};
                    float R[5] = {};
#pragma unroll
                    for (int k = 0; k < 80; k++) R[k >> 4] += __uint_as_float(k & 1 ? a[k >> 1 & 7] & 0xffff0000u : a[k >> 1 & 7] << 16) * W[k >> 4][k & 15];
                    s[0] += f0 * R[0];
                    s[1] += (f[0] * y[0] + f[1] * y[1] + f[2] * y[2]) * R[1];
#pragma unroll
                    for (int j = 0; j < 3; j++) {
                        float z = 0;
#pragma unroll
                        for (int k = 0; k < 9; k++) z += ce[j * 9 + k] * y[k / 3] * f[k % 3];
                        s[2 + 3 * j] += f0 * y[j] * R[2];
                        s[3 + 3 * j] += f[j] * R[3];
                        s[4 + 3 * j] += z * R[4];
                    }
                }
            }
        }
        bar_sync(8, 256);
#pragma unroll
        for (int i = 0; i < 11; i++) P[(h * 11 + i) * 128 + c] = s[i];
        bar_sync(8, 256);
        if (h == 0) {
            float o0 = 0, o[3] = {};
#pragma unroll 4
            for (int p = 0; p < 256; p++) o0 += (P[p] + P[1408 + p]) * bf(w0 + p * 128 + c);
#pragma unroll 4
            for (int p = 0; p < 384; p++) {
                const float wv = bf(w1 + p * 128 + c);
#pragma unroll
                for (int j = 0; j < 3; j++) o[j] += (P[256 + j * 384 + p] + P[1664 + j * 384 + p]) * wv;
            }
            const __nv_bfloat16 r0 = __float2bfloat16(o0);
            const float g = 1.f / (1.f + __expf(-__bfloat162float(r0)));
            out[node * 512 + c] = r0;
#pragma unroll
            for (int j = 0; j < 3; j++) out[node * 512 + 128 * (j + 1) + c] = __float2bfloat16(o[j] * g);
        }
    }
}

__global__ void __launch_bounds__(NT, 1)
tp_kernel(const int4* __restrict__ dst, const int4* __restrict__ src, const char* __restrict__ rhat, Scratch* __restrict__ gs,
          const char* __restrict__ x, const char* __restrict__ ea, const __nv_bfloat16* __restrict__ eps, char* __restrict__ out,
          const __grid_constant__ CUtensorMap m_wr, const __grid_constant__ CUtensorMap m_w0, const __grid_constant__ CUtensorMap m_w1,
          const __grid_constant__ CUtensorMap m_x,
          const __nv_bfloat16* __restrict__ w_rad, const __nv_bfloat16* __restrict__ w_si0, const __nv_bfloat16* __restrict__ w_si1) {
    extern __shared__ __align__(1024) char smem_raw[];
    constexpr uint32_t sm = 1024;
    spin_check((uint32_t)__cvta_generic_to_shared(smem_raw) == sm ? 0 : 2 * SPIN_LIMIT);
    int t;
    asm volatile("mov.u32 %0, %%tid.x;" : "=r"(t));
    const int w = t >> 5, lane = t & 31, b = blockIdx.x;

    const int g = lane >> 2, q = lane & 3, mat = lane >> 3, r = lane & 7;
    const int e0 = b * CH + t * 8, ne = min(CH, NE - b * CH);
    const bool act = t * 8 < ne;
    uint32_t d[8];
#pragma unroll
    for (int k = 0; k < 2; k++) ldg128(d + 4 * k, dst + e0 / 4 + k, act);
    uint32_t tag = ld_rlx(&gs->epoch[b * 32]), epl;
    asm volatile("ld.global.nc.u16 %0, [%1];" : "=r"(epl) : "l"(eps + min(lane, 26)));
    if (t < 60) sts128(sm + O_BCNT + 16 * t, make_uint4(0, 0, 0, 0));
    if (t == NT - 1) {
#pragma unroll
        for (int i = 0; i < 5; i++) mbar_init(sm + O_WBA + 8 * i, 1);
        fence_async();
        mbar_expect(sm + O_WBC, ne * 10); mbar_expect(sm + O_WBA, 20480); mbar_expect(sm + O_WBB, (24 - KR) * 4096); mbar_expect(sm + O_WBD, 65536 + KR * 4096);
        mbar_expect(sm + O_WBE, (((TP & 15) != 15) + ((TP >> 4 & 15) != 15) + ((TP >> 8 & 15) != 15) + ((TP >> 12) != 15)) * (NLOC / 4 * 128));
        WLD(6);
        spin_check(tag);
        bulk(sm + O_RH, rhat + b * (CH * 6), ne * 6, sm + O_WBC);
        bulk(sm + O_SRC, src + b * (CH / 4), ne * 4, sm + O_WBC);
        tma3d(sm + O_WR0, &m_wr, 0, 0, sm + O_WBA);
        tma3d(sm + O_WR1, &m_wr, 0, 5, sm + O_WBA);
        WLD(0);
    }
    if (t == 320) {
#pragma unroll
        for (int i = 0; i < NSLOT; i++) {
            sts128(sm + O_RING + i * SLOT + S_C + 64, make_uint4(0, 0, 0, 0));
            mbar_init(sm + O_RING + i * SLOT + S_FULL, 32); mbar_init(sm + O_RING + i * SLOT + S_EMPTY, 8);
        }
    }
#pragma unroll
    for (int k = 0; k < LZ; k++) sts128(sm + O_L + 16 * (t + k * NT), make_uint4(0, 0, 0, 0));
    if (t < 80) sts32(sm + O_NCNT + 4 * t, t <= NLOC ? 4 * t : 0);
    if (t < 68) sts32(sm + O_NODE + 4 * t, 0);
    uint32_t ba[8], rk[8];
    if (w < 10) bar_sync(1, 320);
    tag = (tag + 1) << 30;
    if (act) {
#pragma unroll
        for (int i = 0; i < 8; i++) {
            const uint32_t l = __umulhi(d[i], (uint32_t)((1ull << 32) / G + 1));
            ba[i] = d[i] * 4 - l * (4 * G);
            d[i] = l * 4 + (tag + ((e0 + i + 1) << 9) + 4);
            rk[i] = atoms_add(sm + O_BCNT + ba[i], 4);
        }
#pragma unroll
        for (int i = 0; i < 8; i++)
            asm volatile("{.reg .pred p; setp.lt.u32 p, %2, 124; @p st.shared.u32 [%0], %1;}"
                         ::"r"(sm + O_KT + ba[i] * 32 + ((ba[i] + rk[i]) & 127)), "r"(d[i]), "r"(rk[i]) : "memory");
    }
    TS(0);
    __syncthreads();
    {
        int v[5], sum = 0;
#pragma unroll
        for (int i = 0; i < 5; i++) { v[i] = lds32(sm + O_BCNT + 4 * (lane * 5 + i)); sum += v[i]; }
        int e = warp_incl(sum) - sum;
        if (w == 10) {
#pragma unroll
            for (int i = 0; i < 5; i++) {
                const int k = lane * 5 + i;
                if (k < G) sts32(sm + O_KT + k * 128 + ((k * 4 + 124) & 127), tag | v[i] << 10 | e >> 2);
                e += v[i];
            }
            __syncwarp();
            if (lane == 0) {
                fence_async();
                bulk_st(&gs->keys[b * (G * 32)], sm + O_KT, G * 128);
                WLD(5);
            }
        } else {
#pragma unroll
            for (int i = 0; i < 5; i++) { sts32(sm + O_BOFF + 4 * (lane * 5 + i), e); e += v[i]; }
        }
        __syncwarp();
    }
    TS(11);
    const uint32_t sw = (uint32_t)(((2 * (w & 3) + (mat & 1)) ^ r) * 16 + ((mat >> 1) * 8 + r) * 128);
    const uint32_t lo = (lane & 2) * 64 + (lane & 12) * 8 + (lane & 16) + (lane & 1) * 8;
    uint32_t wr[5][4];
    const uint32_t* kp = &gs->keys[(w * SEGW * G + b) * 32 + ((lane + b) & 31)];
    uint32_t kv[SEGW + 1], ho[SEGW + 1], nk[SEGW + 1], old;
    if (act) {
        uint32_t mx = 0;
#pragma unroll
        for (int i = 0; i < 8; i++) { mx = max(mx, rk[i]); ba[i] = rk[i] + lds32(sm + O_BOFF + ba[i]); }
        if (mx >= 124) {
#pragma unroll
            for (int i = 0; i < 8; i++)
                if (rk[i] >= 124) st_rlx(&gs->more[b * CH + (ba[i] >> 2)], d[i]);
        }
    }
    if (w < 8) {
        mbar_wait(sm + O_WBA, 0);
#pragma unroll
        for (int p = 0; p < 5; p++) {
            const int c = 2 * p + (w >> 2);
            ldsm4t(wr[p], sm + (c < 5 ? O_WR0 : O_WR1 - 5 * 2048) + c * 2048 + sw);
        }
    } else {
        const uint64_t xl = (uint64_t)(x - 1024 + (r ^ 2 * mat) * 16) - (tag >> 6), al = (uint64_t)(ea - 32 + (lane & 1) * 16) - (tag >> 4);
        const uint64_t ml = (uint64_t)gs->list + lo;
        const uint32_t row = ((mat & 2 ? mat & 1 ? 0xa9c876b5u : 0xfe4d2130u : mat & 1 ? 0xfed8c1a3u : 0x76c521b0u) >> 4 * r & 15) + (mat & 2) * 8;
        const uint32_t c[16] = {(uint32_t)xl, (uint32_t)(xl >> 32), (uint32_t)al, (uint32_t)(al >> 32), (uint32_t)ml, (uint32_t)(ml >> 32),
            mat * 2048u + r * 16, (uint32_t)xl ^ 16,
            S_A + (lane & 2) * 128u + g * 32 + ((lane ^ lane >> 4) & 1) * 16, S_C + row * 16, lane & 1 ? 16u : 9u, lane & 30u,
            lane == 4 ? 0xffff0000u : 0u, lane & 1 ? ~0u : 0u, lane < 16 ? ~0u : 0u, lane ? 0u : 0x20000u};
#pragma unroll
        for (int i = 0; i < 20; i++) wr[i >> 2][i & 3] = i < 16 ? opaque(c[i % 16], lane) : 0;
    }
    TS(21);
    mbar_wait(sm + O_WBC, 0);
    TS(22);
    if (act) {
        uint32_t s[8], y[12];
#pragma unroll
        for (int k = 0; k < 3; k++) *(uint4*)&y[4 * k] = lds128(sm + O_RH + t * 48 + k * 16);
#pragma unroll
        for (int k = 0; k < 2; k++) *(uint4*)&s[4 * k] = lds128(sm + O_SRC + t * 32 + k * 16);
#pragma unroll
        for (int i = 0; i < 8; i++) {
            const int k = 3 * i / 2;
            sts64(sm + O_OUT + ba[i] * 2, __byte_perm(y[k], s[i] + (tag >> 16) + 1, i & 1 ? 0x5432 : 0x5410),
                  i & 1 ? y[k + 1] : __byte_perm(y[k], y[k + 1], 0x5432));
        }
    }
    TS(12);
    __syncthreads();
    if (t == 352) { fence_async(); bulk_st(&gs->vals[b * CH], sm + O_OUT, ne * 8); WLD(7); }

    const uint32_t am = lane < 31 ? 511 : 0, none = tag | (320 + 4 * lane);
    auto check = [&]() {
        old = 0;
#pragma unroll
        for (int j = 0; j < SEGW; j++) {
            ho[j] = __shfl_sync(0xffffffffu, kv[j], 31);
            kv[j] = ho[j] >= (lane < 31 ? tag + ((lane + 1) << 12) : 0u) ? kv[j] : none;
            old |= kv[j] ^ tag;
        }
        return __any_sync(0xffffffffu, old >> 30);
    };
#pragma unroll
    for (int j = 0; j < SEGW; j++) kv[j] = ld_rlx(kp + j * (G * 32));
    TS(1);
    if (t == 352) WLD(1);
    TV(19, 0); TV(23, 0);
    for (int it = 0; check(); it++) {
        spin_check(it);
        if (it == 0) TS(20);
        TV(19, (it + 1) * 100);
#pragma unroll
        for (int j = 0; j < SEGW; j++)
            if (__any_sync(0xffffffffu, (kv[j] ^ tag) >> 30)) kv[j] = ld_rlx(kp + j * (G * 32));
    }
    TS(3);
    if (t == 352) WLD(2);
    kv[SEGW] = none; ho[SEGW] = 0;
    bool slow = false;
    const bool more = __any_sync(0xffffffffu, lane == 31 && (old & 0xfe0000));
    if (more) {
        int c = lane;
#pragma unroll
        for (int j = 0; j < SEGW; j++) {
            const int n = max((int)(ho[j] >> 12 & 0xfff) - 31, 0);
            if ((unsigned)c < (unsigned)n) ho[SEGW] = j * CH + (ho[j] & 0xfff) + 31 + c - lane;
            c -= n;
        }
        slow = lane == 31 && c < 0;
        if (c < 0 && lane < 31)
            for (int it = 0; ((kv[SEGW] = ld_rlx(&gs->more[w * SEGW * CH + lane + ho[SEGW]])) ^ tag) >> 30; it++) spin_check(it);
        __syncwarp();
    }
    uint32_t na_[SEGW + 1];
    uint64_t vp = (uint64_t)&gs->vals[w * SEGW * CH + lane], vv[SEGW + 1];
#pragma unroll
    for (int j = 0; j <= SEGW; j++) vv[j] = tag;
    auto ldv = [&](bool again) {
#pragma unroll
        for (int j = 0; j <= SEGW; j++)
            asm volatile("{.reg .pred p; setp.lt.u32 p, %2, 320; @p ld.relaxed.gpu.global.b64 %0, [%1];}" : "+l"(vv[j])
                         : "l"(madw(j < SEGW ? ho[j] & 0xfff : ho[j], 8, vp) + (j < SEGW ? j * CH * 8 : 0)),
                           "r"(again ? (((uint32_t)vv[j] ^ tag) >> 30 ? 0 : 320) : na_[j]) : "memory");
    };
#pragma unroll
    for (int j = 0; j <= SEGW; j++) na_[j] = (kv[j] & am) | (none & 511 & ~am);
#pragma unroll
    for (int j = 0; j <= SEGW; j++) nk[j] = atoms_add(sm + O_NCNT + na_[j], 512);
    auto visit = [&](auto f) {
#pragma unroll 1
        for (int j = 0; j < SEGW; j++) {
            const uint32_t* kl = &gs->keys[((w * SEGW + j) * G + b) * 32];
            const uint32_t h = ld_rlx(kl + ((31 + b) & 31));
#pragma unroll 1
            for (int i = lane; i < (h >> 12 & 0xfff); i += 32) {
                const int o = (w * SEGW + j) * CH + (h & 0xfff) + i;
                uint32_t k;
                int it = 0;
                do { k = ld_rlx(i < 31 ? kl + ((i + b) & 31) : &gs->more[o]); spin_check(it++); } while ((k ^ tag) >> 30);
                f(k, o, i);
            }
        }
    };
    slow = __syncthreads_or(slow);
    if (slow) {
        if (t < 80) sts32(sm + O_NCNT + 4 * t, t <= NLOC ? 4 * t : 0);
        __syncthreads();
        visit([&](uint32_t k, int, int) { atoms_add(sm + O_NCNT + (k & 511), 512); });
        __syncthreads();
    }
    TS(4);
    if (t == 352) WLD(3);
    if (w < 10) {
        const uint32_t key = lds32(sm + O_NCNT + 4 + (t & ~3));
        uint4 k[5];
#pragma unroll
        for (int i = 0; i < 5; i++) k[i] = lds128(sm + O_NCNT + q * 80 + i * 16);
        uint32_t c[4] = {0, 0, 0, 0};
#pragma unroll
        for (int i = 0; i < 5; i++) { c[0] += (key - k[i].x) >> 31; c[1] += (key - k[i].y) >> 31; c[2] += (key - k[i].z) >> 31; c[3] += (key - k[i].w) >> 31; }
        int rank = c[0] + c[1] + c[2] + c[3];
        rank += __shfl_xor_sync(0xffffffffu, rank, 1);
        rank += __shfl_xor_sync(0xffffffffu, rank, 2);
        if ((b & 1) && rank < 2 * NPRIV) rank = (2 * NPRIV - 1 - rank) ^ 1;
        if (t < NLOC * 4) sts32(sm + O_SORT + 4 * rank, key);
        sts32(sm + O_HV + 4 * w, __ballot_sync(0xffffffffu, t < NLOC * 4 && key >= (HEAVY + 1) << 9));
    }
    __syncthreads();
    TS(2);
    const bool on = lane < NLOC / 4;
    const uint4 k4 = lds128(sm + O_SORT + 16 * (on ? lane : 0));
    const uint32_t ks[4] = {k4.x, k4.y, k4.z, k4.w};
    const int n0 = on ? max(1u, (ks[0] + 3584) >> 12) : 0, n1 = on ? max(1u, (ks[2] + 3584) >> 12) : 0;
    const int u2 = warp_incl(n0 + n1), u1 = u2 - n1, u0 = u1 - n0;
    const int total = __shfl_sync(0xffffffffu, u2, 31);
    slow |= total > CAPT;
    const int m0 = slow ? n0 : max(2u, (ks[0] + 1536) >> 11), m1 = slow ? n1 : max(2u, (ks[2] + 1536) >> 11);
    int gbase = b * CAPT + 1;
    if (on) {
#pragma unroll
        for (int i = 0; i < 4; i++) {
            const int a = ks[i] & 511, node = a * (G / 4) - G + b, o = (i >> 1 ? u1 : u0) * 256 + (i & 1) * 16;
            const uint32_t mk = (node < NN && ks[i] < (HEAVY + 1) << 9 ? node + 1 : 0) + ((i >> 1 ? m1 : m0) << 16);
            sts64(sm + O_NOFF + 2 * a, o - (a >> 4), mk + a * 32);
            if (!slow && ks[i] < 512) sts32(sm + O_L + 4 + o, mk);
        }
    }
    __syncwarp();
    if (t == 352) WLD(8);
    if (!slow) {
        uint32_t mk[SEGW + 1];
        TS(13);
        if (t == 352) { asm volatile("cp.async.bulk.wait_group.read 0;" ::: "memory"); }
        ldv(false);
        if (t == 352) WLD(4);
        TS(16);
#pragma unroll
        for (int j = 0; j <= SEGW; j++) {
            const uint2 o = lds64(sm + O_NOFF + 2 * na_[j]);
            mk[j] = o.y - nk[j] * 32; nk[j] = o.x + (nk[j] >> 4);
        }
        for (int it = 0;; it++) {
            old = 0;
#pragma unroll
            for (int j = 0; j <= SEGW; j++) old |= (uint32_t)vv[j] ^ tag;
            if (!__any_sync(0xffffffffu, old >> 30)) break;
            spin_check(it);
            vp = __shfl_sync(0xffffffffu, vp, lane);
            ldv(true);
            TV(23, (it + 1) * 100);
        }
        TS(17);
#pragma unroll
        for (int j = 0; j <= SEGW; j++)
            asm volatile("{.reg .pred p; setp.ne.u32 p, %3, %5; @p st.shared.v4.u32 [%0], {%1,%2,%3,%4};}"
                         ::"r"(sm + O_L + nk[j]), "r"(kv[j]), "r"(mk[j]), "r"((uint32_t)vv[j]), "r"((uint32_t)(vv[j] >> 32)), "r"(tag) : "memory");
        TS(18);
        if (na_[SEGW] < 320) gs->more[w * SEGW * CH + lane + ho[SEGW]] = 0;
    } else {
        int so = 0;
        if (t == 352) WLD(4);
#pragma unroll
        for (int j = 0; j < SEGW; j++) so += ho[j] & 0xfff;
        if (lane == 0) atoms_add(sm + O_SUM, so);
        if (t == 352) asm volatile("cp.async.bulk.wait_group.read 0;" ::: "memory");
        __syncthreads();
        gbase = TBIG + (lds32(sm + O_SUM) >> 3) + (NLOC + 5) * b;
        auto put = [&](uint32_t k, uint64_t e, uint32_t a, int rank) {
            const uint2 o = lds64(sm + O_NOFF + 2 * a);
            const uint32_t m = o.y - a * 32 - (rank << 13);
            gs->list[gbase * 16 + ((o.x + (a >> 4)) >> 4) + rank * 2] = make_uint4(k, (m & 0xffff) | min(m >> 16, 0x7fffu) << 17, e, e >> 32);
        };
        visit([&](uint32_t k, int o, int i) {
            uint64_t e;
            int it = 0;
            do {
                asm volatile("ld.relaxed.gpu.global.b64 %0, [%1];" : "=l"(e) : "l"(&gs->vals[o]) : "memory");
                spin_check(it++);
            } while (((uint32_t)e ^ tag) >> 30);
            if (i >= 31) gs->more[o] = 0;
            put(k, e, k & 511, atoms_add(sm + O_NCUR + (k & 511), 1));
        });
#pragma unroll 1
        for (int i = 0; i < 4; i++) {
            const uint32_t k = i == 0 ? ks[0] : i == 1 ? ks[1] : i == 2 ? ks[2] : ks[3];
#pragma unroll 1
            for (int p = (k >> 9) + w; p < (i >> 1 ? n1 : n0) * 8; p += NT / 32) put(0, 0, k & 511, p);
        }
        __threadfence();
    }
    if (t == 352) WLD(9);
    const uint32_t iw0 = (gbase + u0) << 12 | n0, iw1 = (gbase + u1) << 12 | n1;
    __syncthreads();
    TS(5);

    if (w >= 8) {
        asm volatile("setmaxnreg.dec.sync.aligned.u32 56;");
        const int h = __reduce_max_sync(0xffffffffu, w & 3);
        if (h == 0) TSW(28);
        gbase = __reduce_min_sync(0xffffffffu, iw0) >> 12;
        int pos = gbase + h, end = __reduce_max_sync(0xffffffffu, lane == NPRIV / 2 ? (NPRIV & 1 ? iw1 : iw0) : 0) >> 12;
        const int bytes = gbase < TBIG ? ((__reduce_max_sync(0xffffffffu, iw0) >> 12) - gbase) * 256 : 0;
        const uint32_t ring = sm + O_RING;
        const uint64_t xl[2] = {wr[0][0] | (uint64_t)wr[0][1] << 32, wr[1][3] | (uint64_t)wr[0][1] << 32};
        const uint64_t al = wr[0][2] | (uint64_t)wr[0][3] << 32, ml = wr[1][0] | (uint64_t)wr[1][1] << 32;
        const uint32_t xoff = wr[1][2], aoff = wr[2][0], coff = wr[2][1], sh = wr[2][2], ial = wr[2][3], sel = wr[3][0];
        const uint32_t odd = wr[3][1], low = wr[3][2], lim = wr[3][3];
        auto lde = [&](uint2& e, int p) {
            asm volatile("{.reg .pred p; setp.gt.s32 p, %3, 0; @p ld.relaxed.gpu.global.v2.u32 {%0,%1}, [%2];}" : "+r"(e.x), "+r"(e.y) : "l"(madw(p, 256, ml)), "r"(p) : "memory");
        };
        uint2 e0[3] = {};
#pragma unroll
        for (int k = 0; k < 3; k++) {
            e0[k] = lds64(sm + O_L + k * 1024 + h * 256 + ((uint32_t)ml & 255));
            lde(e0[k], bytes ? 0 : pos + 4 * k);
        }
        if (h == 3) fence_async();
        else asm volatile("bar.arrive 4, %0;" ::"n"(NT) : "memory");
        pos += 4;

        int ev = 0, state = -2, tk = 0, nr = 0;
        uint32_t inf = 0;
        int ii = 0;
        auto take = [&]() {
            int v = 0;
            asm volatile("{.reg .pred p; setp.eq.s32 p, %2, 0; @p atom.relaxed.gpu.global.add.u32 %0, [%1], 1;}" : "+r"(v) : "l"(&gs->ticket), "r"(lane) : "memory");
            return v;
        };
        auto resolve = [&]() {
            const int k = __reduce_max_sync(0xffffffffu, tk);
            inf = tag;
            if (k < G * NPOOL) { const int l = k / G; ii = (k - l * G) * NPOOL + l; inf = ld_rlx(&gs->info[ii]);
                const int j = NPRIV + 1 + nr + (b & 7), gd = __reduce_max_sync(0xffffffffu, lds32(sm + O_SUM + 4));
                tk = (b & 7) && (j & ~7) > gd && k >= G * NPOOL - (j & 7 ? G : 5 * G / 3) ? G * NPOOL : take(); }
        };
        uint32_t so = ring + h * SLOT, ph = 0x80000000u;
        uint32_t spins = 0;
        asm volatile(".reg .pred z<5>;");
        { const uint32_t c0 = clock(); while (__any_sync(0xffffffffu, (uint32_t)clock() - c0 < h * 300)); }
        while (true) {
            const uint2 e = e0[0];
            const uint32_t o = e.x >> sh, id = __shfl_sync(0xffffffffu, o, ial);
            uint32_t s[4];
#pragma unroll
            for (int j = 0; j < 4; j++) s[j] = __shfl_sync(0xffffffffu, o, 2 * j + 1, 8);
            const uint32_t nx = so == ring + (NSLOT - 1) * SLOT ? ph : ph ^ 0x80000000u, ey = lop_sel(e.y, nx, sel);
            const uint32_t ym = lop_sel(__shfl_xor_sync(0xffffffffu, e.x, 1), e.y, odd);
            const bool full = __all_sync(0xffffffffu, e.y >= lim);
            const uint64_t ga = madw(id, 32, al);
            uint64_t gx[4];
#pragma unroll
            for (int j = 0; j < 4; j++) gx[j] = madw(s[j], 1024, xl[j >> 1]);
            const uint32_t da = so + aoff, dx = so + xoff, dc = so + coff;
            asm volatile("setp.eq.u32 z0, %0, 0;\nsetp.eq.u32 z1, %1, 0;\nsetp.eq.u32 z2, %2, 0;\nsetp.eq.u32 z3, %3, 0;\nsetp.eq.u32 z4, %4, 0;\n"
                         ::"r"(s[0]), "r"(s[1]), "r"(s[2]), "r"(s[3]), "r"(id), "l"(ga), "r"(da), "r"(dx), "r"(dc), "l"(gx[0]), "l"(gx[1]), "l"(gx[2]), "l"(gx[3]));
            asm volatile("{.reg .pred p; setp.gt.s32 p, %3, 0; @p ld.relaxed.gpu.global.v2.u32 {%0,%1}, [%2];}"
                         : "=r"(e0[0].x), "=r"(e0[0].y) : "l"((uint64_t)(gs->list + pos * 16) + ((uint32_t)ml & 255)), "r"(state < 0 ? 0 : pos) : "memory");
            if (h == 0 && state == -2) TSW(29);
            if (h == 0 && state == -1) TSW(30);
            asm volatile("{\n.reg .pred p;\n.reg .b64 s;\nmov.b64 s, {0, %2};\n"
                         "LOOP:\nmbarrier.try_wait.shared::cta.b64 p, [%1], s;\n@p bra DONE;\n"
                         "add.u32 %0, %0, 1;\nsetp.gt.u32 p, %0, %3;\n@p trap;\nbra LOOP;\nDONE:\n}"
                         : "+r"(spins) : "r"(so + S_EMPTY), "r"(ph), "n"(SPIN_LIMIT) : "memory");
            asm volatile("cp.async.cg.shared.global [%0], [%1], 16, z4;" ::"r"(da), "l"(ga) : "memory");
#define ROW(j) _Pragma("unroll") for (int k = 0; k < 8; k++) \
                asm volatile("cp.async.cg.shared.global [%0], [%1], 16, z" #j ";" ::"r"(dx + (j >> 1) * 1024 + (j & 1) * 8192 + k * 128), "l"(gx[j] + k * 128) : "memory")
            ROW(0); ROW(2);
            if (full) { ROW(1); ROW(3); }
            stsm4t(dc, ym, ey, ym & low, ym & ~low);
            asm volatile("cp.async.mbarrier.arrive.noinc.shared::cta.b64 [%0];" ::"r"(so + S_FULL) : "memory");
            const bool wrap = so >= ring + (NSLOT - 4) * SLOT;
            ph ^= wrap ? 0x80000000u : 0u;
            so = wrap ? so - (NSLOT - 4) * SLOT : so + 4 * SLOT;
            pos += 4;
            if (pos >= ev) {
                if (state < 0) {
                    e0[0].x = state == -2 ? e0[1].x : e0[2].x; e0[0].y = state == -2 ? e0[1].y : e0[2].y;
                    if (state == -2) {
                        if (h == 0) TSW(24);
                        if (h == 3) TSW(25);
                        if (h == 0) asm volatile("bar.arrive 5, 288;" ::: "memory");
                        if (h < 3) bar_sync(7, 352);
                        if (h == 3) bar_sync(4, NT);
                        if (h == 0) mbar_wait(sm + O_WBE, 0);
                        if (h == 3) {
                            if (lane == 0) {
                                if (bytes) bulk_st(gs->list + gbase * 16, sm + O_L, bytes);
                                asm volatile("cp.async.bulk.wait_group.read 0;" ::: "memory");
                            }
                            __syncwarp();
                            if (lane == 0) {
                                for (int j = KR; j < 24; j++) tma3d(sm + O_W1 + (j - KR) * 4096, &m_w1, 16 * j, 0, sm + O_WBB);
                            }
                            __syncwarp();
                        }
                        state = -1;
                    } else {
                        if (h == 3) {
                            if (lane == 0) asm volatile("cp.async.bulk.wait_group 0;\nfence.proxy.async;" ::: "memory");
                            __syncwarp();
                            const int i = opaque(2 * lane - NPRIV, lane);
                            if ((unsigned)i < NPOOL) st_rlx(&gs->info[b * NPOOL + i], tag | iw0);
                            if ((unsigned)(i + 1) < NPOOL) st_rlx(&gs->info[b * NPOOL + i + 1], tag | iw1);
                        }
                        bar_sync(6, 128);
                        ev = h ? end : end - 12; state = h ? 2 : 0;
                    }
                } else if (state == 0) { ev = end - 6; state = 1; tk = take(); }
                else if (state == 1) { resolve(); ev = end; state = 2; }
                else {
                    if (state == 3) break;
                    do {
                        const uint32_t mb = sm + O_MB + (nr & 15) * 8;
                        uint32_t rg;
                        nr++;
                        if (h == 0) {
                            for (int it = 0; (rg = __reduce_max_sync(0xffffffffu, inf ^ tag)) >> 30; it++) { spin_check(it); inf = ld_rlx(&gs->info[ii]); }
                            asm volatile("st.release.cta.shared.b64 [%0], %1;" ::"r"(mb), "l"(rg | (uint64_t)nr << 32) : "memory");
                            if (rg) resolve();
                        } else {
                            uint64_t m;
                            for (int it = 0;; it++) {
                                asm volatile("ld.acquire.cta.shared.b64 %0, [%1];" : "=l"(m) : "r"(mb) : "memory");
                                if (__all_sync(0xffffffffu, (int)(m >> 32) == nr)) break;
                                spin_check(it);
                            }
                            rg = __reduce_max_sync(0xffffffffu, (uint32_t)m);
                        }
                        pos = rg ? (int)(rg >> 12) + pos - end : 0;
                        end = rg ? (rg >> 12) + (rg & 0xfff) : 1;
                        state = rg ? 2 : 3;
                    } while (pos >= end);
                    ev = end;
                }
            }
        }
        mbar_wait31(so + S_EMPTY, ph);
        TSW(8 + (h & 1));
        if (lane == 0) sts32(so + S_N, 0);
        mbar_arrive(so + S_FULL);
        if (t == 256) {
            gs->epoch[b * 32] = (tag >> 30) % 3;
            if (atomicInc(&gs->done, G - 1) == G - 1) gs->ticket = 0;
        }
        asm volatile("cp.async.wait_all;" ::: "memory");
    } else {
        asm volatile("setmaxnreg.inc.sync.aligned.u32 224;");
        bar_sync(5, 288);
        const uint32_t xa = opaque(((mat >> 1) * 8 + r) * 1024 + (w >> 2) * 128 + (((2 * (w & 3) + (mat & 1)) ^ r) * 16), lane);
        const uint32_t aa = opaque(S_A + ((mat >> 1) * 8 + r) * 32 + (((mat & 1) ^ (r >> 2)) * 16), lane);
        const uint32_t ya = opaque(S_C + (mat & 1) * 80 + (mat >> 1) * 16, lane);
        const uint32_t yc = opaque(S_C + (mat < 2 ? mat * 80 + 32 : q < 3 ? mat * 128 + ((r >> 2) ^ (mat & 1)) * 80 + q * 16 : 64), lane);
        const uint32_t na = opaque((mat & 1) * 8, lane);
        const uint32_t pw = sm + O_P + w * PW;
        const uint32_t fx = opaque(pw + (q < 3 ? P_1P0 + 2 * q * PSBO : P_1P1 + PSBO) + (mat & 1) * 128 + (r >> 2) * PSBO, lane);
        const uint32_t fyz = opaque(pw + (q < 3 ? (mat < 2 ? P_1P1 : P_1P2) + 2 * q * PSBO : mat < 2 ? P_0P0 : P_0P1) + (mat & 1) * 128 + (r >> 2) * PSBO, lane);
        uint32_t oh[5];
#pragma unroll
        for (int c = 0; c < 5; c++) oh[c] = opaque(g == (q >> 1) * 4 + min(c, 3) ? 0x3F803F80u : 0u, lane ^ c >> 2);
        uint32_t eb[3];
#pragma unroll
        for (int k = 0; k < 3; k++) {
            const int i = (g & 3) * 9 + (q & 1) * 6 + k;
            const uint32_t lo = __shfl_sync(0xffffffffu, epl, i), hi = __shfl_sync(0xffffffffu, epl, i + 3);
            eb[k] = (g & 3) < 3 && (q >> 1) == (g >> 2) ? (q & 1 ? lo : lo | hi << 16) : 0u;
        }
        asm volatile(".reg .pred lane0;\nsetp.eq.u32 lane0, %0, 0;" ::"r"(lane));
        uint32_t w0[16][4], w1[KR][4];
        mbar_wait(sm + O_WBD, 0);
#pragma unroll
        for (int k = 0; k < 16; k++) ldsm4t(w0[k], sm + w0s(k >> 2) + (w >> 2) * 8192 + (k & 3) * 2048 + sw);
#pragma unroll
        for (int k = 0; k < KR; k++) ldsm4t(w1[k], sm + w1s(k) + (w >> 2) * 2048 + sw);
        asm volatile("bar.arrive 4, %0;" ::"n"(NT) : "memory");
        bar_sync(7, 352);
        TS(6);
        Acc A;
#pragma unroll
        for (int i = 0; i < 4; i++) { A.p[i] = A.p[4 + i] = A.p[8 + i / 2] = 0; A.t01[i] = A.m[0][i] = A.m[1][i] = A.m[2][i] = 0.f; }
        uint32_t room = 144 - (b & 7) * 16;
        uint32_t so = sm + O_RING, ph, a[4], ok, go, mt = 0;
        mbar_wait(so + S_FULL, 0);
        ldsm4(a, so + aa);
        TS(7);
        while (true) {
        next:
            {
                constexpr int F = 1, H = 0, XS = XS_F;
                int seen = 0;
                uint32_t yb[8], f[4][4], R[5][4], u[4][4], sd[4];
                float y[4], z[4];
                const uint32_t sof = room & 112;
                room -= 16;
                SEQ_F
            }
            if (!(go && room)) {
                const uint32_t pu = __reduce_max_sync(0xffffffffu, ph);
                if (!room || !pu) {
                    const uint32_t wg = __reduce_max_sync(0xffffffffu, w >> 2);
                    mbar_wait(sm + O_WBB, 0);
                    asm volatile("{.reg .pred p; setp.ne.u32 p, %0, 0;\n@p bar.arrive 1, 256;\n@p bar.sync 2, 256;\n@!p bar.sync 1, 256;}" ::"r"(wg) : "memory");
                    asm volatile("fence.proxy.async::generic.acquire.sync_restrict::shared::cluster.cluster;" ::: "memory");
                    float d0[8], d1[24];
                    const uint64_t db = (uint64_t)((sm + O_P) >> 4) | (8ull << 16) | ((uint64_t)(PSBO / 16) << 32);
                    const uint32_t da = ((sm + O_W1) >> 4 | 1 << 16) + wg * 128;
                    asm volatile("wgmma.fence.sync.aligned;" ::: "memory");
                    const uint32_t sp = so == sm + O_RING ? sm + O_RING + (NSLOT - 1) * SLOT : so - SLOT, sr = (r & 6) + (mat & 1);
                    const uint32_t nd = (sr * 16 - 16 & 112) >= room ? lds32(sm + O_NODE + sr * 16 + (mat >> 1) * 8) : 0;
                    const uint64_t oa = madw(nd, 1024, (uint64_t)(out - 1024 + w * 32 + (r & 1) * 16));
                    const uint32_t sl = sp + ((mat >> 1) * 8 + sr) * 1024 + (w >> 2) * 128 + (((2 * (w & 3) + (r & 1)) ^ sr) * 16);
                    auto put = [&](int j) {
                        const uint4 v = lds128(sl + j * 256);
                        asm volatile("{.reg .pred p; setp.ne.u32 p, %5, 0; @p st.global.v4.u32 [%0], {%1,%2,%3,%4};}"
                                     ::"l"(oa + j * 256), "r"(v.x), "r"(v.y), "r"(v.z), "r"(v.w), "r"(nd) : "memory");
                    };
                    static_for<24>([&](auto kc) {
                        constexpr int k = kc.value;
                        if (k == 16) asm volatile("wgmma.commit_group.sync.aligned;" ::: "memory");
                        if (k == 20) asm volatile("{.reg .pred p; setp.eq.u32 p, %0, 0;\n@p bar.arrive 2, 256;}" ::"r"(wg) : "memory");
                        G1(k);
                        if (k < 16) G0(k % 16);
                    });
                    asm volatile("wgmma.commit_group.sync.aligned;" ::: "memory");
                    asm volatile("wgmma.wait_group.sync.aligned 1;" ::: "memory");
#pragma unroll
                    for (int i = 0; i < 8; i++) asm volatile("" : "+f"(d0[i])::"memory");
                    stsm4t(sp + xa, pack(d0[0], d0[1]), pack(d0[2], d0[3]), pack(d0[4], d0[5]), pack(d0[6], d0[7]));
                    __syncwarp();
                    put(0);
                    float gt[8];
                    uint32_t chk = -1;
#pragma unroll
                    for (int i = 0; i < 8; i++) {
                        asm volatile("ex2.approx.ftz.f32 %0, %1;" : "=f"(gt[i]) : "f"(d0[i] * -1.4426950408889634f) : "memory");
                        asm volatile("rcp.approx.ftz.f32 %0, %1;" : "=f"(gt[i]) : "f"(gt[i] + 1.f) : "memory");
                    }
#pragma unroll
                    for (int i = 0; i < 8; i++) chk &= __float_as_uint(gt[i]);
                    sts32(sm + O_TRASH, chk);
                    asm volatile("wgmma.wait_group.sync.aligned 0;" ::: "memory");
#pragma unroll
                    for (int i = 0; i < 24; i++) asm volatile("" : "+f"(d1[i])::"memory");
                    asm volatile("{.reg .pred p; setp.ne.u32 p, %0, 0;\n@p bar.sync 3, 256;}" ::"r"(wg) : "memory");
#pragma unroll
                    for (int j = 0; j < 3; j++) {
                        uint32_t o[4];
#pragma unroll
                        for (int i = 0; i < 4; i++) o[i] = pack(d1[8 * j + 2 * i] * gt[2 * i], d1[8 * j + 2 * i + 1] * gt[2 * i + 1]);
                        stsm4t(sp + xa + 256 + j * 256, o[0], o[1], o[2], o[3]);
                    }
                    __syncwarp();
#pragma unroll
                    for (int j = 1; j < 4; j++) put(j);
                    __syncwarp();
                    asm volatile("@lane0 mbarrier.arrive.shared::cta.b64 _, [%0];" ::"r"(sp + S_EMPTY) : "memory");
                    asm volatile("@lane0 red.shared.add.u32 [%0], 1;" ::"r"(sm + O_SUM + 4) : "memory");
                    asm volatile("{.reg .pred p; setp.eq.u32 p, %0, 0;\n@p bar.sync 3, 256;}" ::"r"(wg) : "memory");
                    room = 128;
                    if (!pu) break;
                }
                if (!ok) { mbar_wait31(so + S_FULL, pu); ldsm4(a, so + aa); }
                if (!(pu & 0xfffc)) { if (pu & 1) goto half; continue; }
            }
            while (true) {
                do {
                    constexpr int F = 0, H = 0, XS = XS_R;
                    int seen = 0;
                    uint32_t yb[8], f[4][4], R[5][4], u[4][4], sd[4];
                    SEQ_R
                } while (go);
                asm volatile("{.reg .pred p, q; .reg .f32 n; abs.f32 n, %1; setp.ne.u32 q, %2, 0; setp.le.and.f32 p, n, 0f00000002, q; selp.u32 %0, 1, 0, p;}" : "=r"(go) : "r"(ph), "r"(ok));
                if (go) goto next;
                if (ok) goto half;
                const uint32_t pu = __reduce_max_sync(0xffffffffu, ph);
                mbar_wait31(so + S_FULL, pu); ldsm4(a, so + aa);
                if (!(pu & 0xfffc)) { go = pu & 1; break; }
            }
            if (!go) continue;
        half: {
                constexpr int F = 0, H = 1, XS = XS_H;
                int seen = 0;
                uint32_t yb[8], f[4][4], R[5][4], u[4][4], sd[4];
                SEQ_H
                if (!ok) { mbar_wait31(so + S_FULL, __reduce_max_sync(0xffffffffu, ph)); ldsm4(a, so + aa); }
            }
        }
        TS(10);
        heavy_nodes(sm, (float*)(smem_raw + O_P), dst, (const int*)src, (const __nv_bfloat16*)rhat, (const __nv_bfloat16*)x, (const uint4*)ea, eps, w_rad, w_si0, w_si1, (__nv_bfloat16*)out);
    }
}

typedef CUresult (*EncFn)(CUtensorMap*, CUtensorMapDataType, cuuint32_t, void*, const cuuint64_t*, const cuuint64_t*,
                          const cuuint32_t*, const cuuint32_t*, CUtensorMapInterleave, CUtensorMapSwizzle,
                          CUtensorMapL2promotion, CUtensorMapFloatOOBfill);

void make_map(EncFn fn, CUtensorMap* m, void* p, int rows, int cols, int brows, int bcols, int bblk) {
    cuuint64_t dims[3] = {64, (cuuint64_t)rows, (cuuint64_t)cols / 64}, strides[2] = {(cuuint64_t)cols * 2, 128};
    cuuint32_t box[3] = {(cuuint32_t)bcols, (cuuint32_t)brows, (cuuint32_t)bblk}, es[3] = {1, 1, 1};
    fn(m, CU_TENSOR_MAP_DATA_TYPE_BFLOAT16, 3, p, dims, strides, box, es, CU_TENSOR_MAP_INTERLEAVE_NONE,
       bcols == 64 ? CU_TENSOR_MAP_SWIZZLE_128B : CU_TENSOR_MAP_SWIZZLE_NONE, CU_TENSOR_MAP_L2_PROMOTION_L2_128B, CU_TENSOR_MAP_FLOAT_OOB_FILL_NONE);
}

}

extern "C" void kernel_launch(void* const* d_in, const int* in_sizes, int n_in, void* d_out, int out_size) {
    static EncFn enc = nullptr;
    static void* scratch = nullptr;
    if (!enc) {
        void* fn = nullptr;
        cudaDriverEntryPointQueryResult qr;
        cudaGetDriverEntryPoint("cuTensorMapEncodeTiled", &fn, cudaEnableDefault, &qr);
        enc = (EncFn)fn;
        cudaGetSymbolAddress(&scratch, g_scratch);
        cudaFuncSetAttribute(tp_kernel, cudaFuncAttributeMaxDynamicSharedMemorySize, SMEM_BYTES);
    }
    CUtensorMap m_wr, m_w0, m_w1, m_x;
    make_map(enc, &m_wr, d_in[5], 16, 640, 16, 64, 5);
    make_map(enc, &m_w0, d_in[6], 256, 128, 64, 64, 2);
    make_map(enc, &m_w1, d_in[7], 384, 128, 16, 64, 2);
    make_map(enc, &m_x, d_in[0], NN * 8, 64, NLOC * 2, 8, 1);
    tp_kernel<<<G, NT, SMEM_BYTES>>>((const int4*)d_in[4], (const int4*)d_in[3], (const char*)d_in[1], (Scratch*)scratch,
                                     (const char*)d_in[0], (const char*)d_in[2], (const __nv_bfloat16*)d_in[8], (char*)d_out,
                                     m_wr, m_w0, m_w1, m_x, (const __nv_bfloat16*)d_in[5], (const __nv_bfloat16*)d_in[6], (const __nv_bfloat16*)d_in[7]);
}
```
